```python
import torch

def _softmax(x, axis=-1):
    return torch.softmax(x, dim=axis)

def _gelu(x):
    return torch.nn.functional.gelu(x, approximate='tanh')

def _silu(x):
    return torch.nn.functional.silu(x)

def _sigmoid(x):
    return torch.sigmoid(x)

def _layernorm(x, axis=-1, eps=1e-05):
    m = x.mean(dim=axis, keepdim=True)
    v = x.var(dim=axis, keepdim=True, unbiased=False)
    return (x - m) / torch.sqrt(v + eps)

def _scatter_add(tgt, idx, src, axis=0):
    return tgt.clone().index_add_(axis, idx, src)

def _segment_sum(src, seg, n):
    out = torch.zeros((n,) + src.shape[1:], dtype=src.dtype)
    return out.index_add_(0, seg, src)

def _pad(x, pw):
    flat = tuple((v for pair in reversed(pw) for v in pair))
    return torch.nn.functional.pad(x, flat)
kernel_name = 'adaLN_cond__sliding_block_cached__moe_arch_mod__prompt'

def setup_inputs():

    _w = lambda a: (lambda t: t.to(torch.bfloat16) if t.is_floating_point() else t)(torch.as_tensor(a))

    def _A_setup():
        B, Sq, D = (1, 2048, 1024)
        Hq, Hkv, Sk, Dh = (32, 4, 2048, 128)
        assert Hq % Hkv == 0, (Hq, Hkv)
        return {'x': _w((lambda *s: torch.randn(*s, dtype=torch.bfloat16) * 0.05)(B, Sq, D)), 'k_cache': _w((lambda *s: torch.randn(*s, dtype=torch.bfloat16) * 3.2)(B, Hkv, Sk, Dh)), 'v_cache': _w((lambda *s: torch.randn(*s, dtype=torch.bfloat16) * 0.4)(B, Hkv, Sk, Dh)), 'wq': _w((lambda *s: torch.randn(*s, dtype=torch.bfloat16) * 3.2)(D, Hq * Dh) * D ** (-0.5)), 'wo': _w((lambda *s: torch.randn(*s, dtype=torch.bfloat16) * 0.4)(Hq * Dh, D) * (Hq * Dh) ** (-0.5))}
    _A_in = _A_setup()

    def _B_setup():
        B, S, D, F, C = (1, 2048, 1024, 3584, 1)
        return {'x': _w((lambda *s: torch.randn(*s, dtype=torch.bfloat16) * 0.05)(B, S, D)), 'w_r': _w((lambda *s: torch.randn(*s, dtype=torch.bfloat16) * 0.05)(D)), 'w_gate': _w((lambda *s: torch.randn(*s, dtype=torch.bfloat16) * 0.05)(D, F)), 'w_up': _w((lambda *s: torch.randn(*s, dtype=torch.bfloat16) * 0.05)(D, F)), 'w_down': _w((lambda *s: torch.randn(*s, dtype=torch.bfloat16) * 0.05)(F, D))}
    _B_in = _B_setup()
    return {'A_x': _A_in['x'], 'A_k_cache': _A_in['k_cache'], 'A_v_cache': _A_in['v_cache'], 'A_wq': _A_in['wq'], 'A_wo': _A_in['wo'], 'B_x': _B_in['x'], 'B_w_r': _B_in['w_r'], 'B_w_gate': _B_in['w_gate'], 'B_w_up': _B_in['w_up'], 'B_w_down': _B_in['w_down'], 'c': _w((lambda *s: torch.randn(*s, dtype=torch.bfloat16) * 0.1)(1, 1024) * 8.0), 'w_mod': _w((lambda *s: torch.randn(*s, dtype=torch.bfloat16) * 0.1)(1024, 6 * 1024) * 1024 ** (-0.5) * 8.0)}

def reference(A_x, A_k_cache, A_v_cache, A_wq, A_wo, B_x, B_w_r, B_w_gate, B_w_up, B_w_down, c, w_mod):

    def _A_ref(x, k_cache, v_cache, wq, wo):
        B, Sq, D = x.shape
        Hq, Dh = (32, 128)
        Hkv, Sk = (k_cache.shape[1], k_cache.shape[2])
        W = min(4096, max(256, Sk // 4))
        rep = Hq // Hkv
        q = (lambda x, *d: x.permute(*d))((x @ wq).reshape(B, Sq, Hq, Dh), 0, 2, 1, 3)
        k = (lambda x, n, axis: torch.repeat_interleave(x, n, dim=axis))(k_cache[:, :, Sk - W:, :], rep, axis=1)
        v = (lambda x, n, axis: torch.repeat_interleave(x, n, dim=axis))(v_cache[:, :, Sk - W:, :], rep, axis=1)
        scores = torch.einsum('bhqd,bhkd->bhqk', q, k) * Dh ** (-0.5)
        p = _softmax(scores, axis=-1)
        o = torch.einsum('bhqk,bhkd->bhqd', p, v)
        return (lambda x, *d: x.permute(*d))(o, 0, 2, 1, 3).reshape(B, Sq, Hq * Dh) @ wo

    def _B_ref(x, w_r, w_gate, w_up, w_down):
        B, S, D = x.shape
        C = 1
        r = x @ w_r
        idx = torch.argsort(-r, axis=-1)[:, :C]
        idx_e = (lambda x, n, axis: torch.repeat_interleave(x, n, dim=axis))(idx.reshape(B, C, 1), D, axis=2)
        x_sel = (lambda x, i, axis: torch.take_along_dim(x, i, dim=axis))(x, idx_e, axis=1)
        g = _silu(x_sel @ w_gate)
        u = x_sel @ w_up
        y = g * u @ w_down
        r_sel = _sigmoid((lambda x, i, axis: torch.take_along_dim(x, i, dim=axis))(r, idx, axis=1))
        y = y * r_sel.reshape(B, C, 1)
        b_off = (torch.arange(B) * S).reshape(B, 1)
        flat_idx = (idx + b_off).reshape(B * C)
        zero = (x * 0.0).reshape(B * S, D)
        upd = _scatter_add(zero, flat_idx, y.reshape(B * C, D), axis=0)
        return x + upd.reshape(B, S, D)
    x = A_x
    mod = (_silu(c) @ w_mod).reshape(c.shape[0], 6, 1, -1)
    sa, ca, ga, sb, cb, gb = (mod[:, 0].clone(), mod[:, 1].clone(), mod[:, 2].clone(), mod[:, 3].clone(), mod[:, 4].clone(), mod[:, 5].clone())
    h = _layernorm(x, axis=-1) * (1 + ca) + sa
    x = x + ga * _A_ref(h, A_k_cache, A_v_cache, A_wq, A_wo)
    h = _layernorm(x, axis=-1) * (1 + cb) + sb
    x = x + gb * _B_ref(h, B_w_r, B_w_gate, B_w_up, B_w_down)
    return x
```

```cpp
#include <cuda_runtime.h>
#include <cuda_bf16.h>
#include <cuda.h>
#include <stdint.h>
#include <stddef.h>

#define UPD 200
#define GATED 1500
#define WL 3500
#define XD 0
#define PLD 200
#define SPD 0
#define PFW 100
#define OD0 300
#define OD1 100
#define X_PEEL 1
#define WU1 12

namespace {

typedef __nv_bfloat16 bf16;

constexpr int NTHREADS = 384;
constexpr int NMAIN = 128;
constexpr int NCTA = 132;
constexpr int NREP = 4;
constexpr int NFFN = 112;

constexpr uint32_t SM_RING = 0;
constexpr uint32_t ST1 = 49152;
constexpr uint32_t ST2 = 32768;
constexpr int NST2 = 6;
constexpr uint32_t SM_STASH = 196608;
constexpr uint32_t SM_MISC = 229376;
constexpr uint32_t BAR_FULL1 = SM_MISC + 0;
constexpr uint32_t BAR_EMPTY1 = SM_MISC + 40;
constexpr uint32_t BAR_FULL2 = SM_MISC + 0;
constexpr uint32_t BAR_EMPTY2 = SM_MISC + 48;
constexpr uint32_t BAR_STASH = SM_MISC + 160;
constexpr uint32_t BAR_SFREE = SM_MISC + 176;
constexpr uint32_t BAR_TFREE = SM_MISC + 184;
constexpr uint32_t BAR_FFN = SM_MISC + 192;
constexpr uint32_t BAR_VEC = SM_MISC + 208;
constexpr uint32_t BAR_RED = SM_MISC + 216;
constexpr uint32_t BAR_XH = SM_MISC + 152;
constexpr uint32_t BAR_HS = SM_MISC + 80;
constexpr uint32_t BAR_G = SM_MISC + 112;
constexpr uint32_t BAR_T1 = SM_MISC + 120;
constexpr uint32_t BAR_HF = SM_MISC + 128;
constexpr uint32_t BAR_X = SM_MISC + 136;
constexpr uint32_t BAR_OF = SM_MISC + 224;
constexpr uint32_t BAR_ROLE = SM_MISC + 240;
constexpr uint32_t SM_ROLE = SM_MISC + 248;
constexpr uint32_t SM_GA = SM_MISC + 256;
constexpr uint32_t SM_SCAL = SM_MISC + 512;
constexpr uint32_t SM_WROW = SM_MISC + 520;
constexpr uint32_t SM_AMAX = SM_MISC + 528;
constexpr uint32_t SM_YRED = SM_MISC + 656;
constexpr uint32_t SM_X2 = 2 * ST1, SM_OUT = 3 * ST1;
constexpr uint32_t SM_REC = SM_MISC + 1024;
constexpr uint32_t BAR_TAB = SM_MISC + 1000;
constexpr uint32_t BAR_CAND = SM_MISC + 880;
constexpr uint32_t SM_CAND = SM_MISC + 888;
constexpr uint32_t SM_WSLAB = 2 * 49152 + 16384;
constexpr uint32_t SM_XROW = 2 * 49152;
constexpr uint32_t SM_RED = SM_MISC + 2048;
constexpr uint32_t SM_B1 = SM_MISC + 2048;
constexpr uint32_t SMEM_BYTES = 232448;

constexpr int NB_CONS = 1, NB_WIN = 2  , NB_OST = 4  , NB_AMAX = 6;

struct __align__(1024) Scratch {
  uint32_t epoch[32];
  uint32_t hflag[16 * 32];
  uint32_t oflag[64 * 32];
  uint2 vdone[4 * 16];
  uint32_t pad[96 + 512];
  uint32_t ticket[8 * 32];
  uint2 mod[3072];
  uint4 rec[2][NREP][256];
  uint4 lnst[1024];
  uint4 entry[8 * 16 * 8];
  uint4 cand[16 * 8 * 32];
  uint4 stats[16 * 8 * 128];
  uint4 ypart[128 * NFFN * 4];
  unsigned long long ts[NCTA * 64];
  uint16_t h[2048 * 1024];
  uint16_t o[2048 * 4096];
};
__device__ Scratch g_scratch;
#define g_epoch (p.sc->epoch[0])
#define g_hflag (p.sc->hflag)
#define g_oflag (p.sc->oflag)
#define g_mod (p.sc->mod)
#define g_entry (p.sc->entry)
#define g_cand (p.sc->cand)
#define g_stats (p.sc->stats)
#define g_ypart (p.sc->ypart)
#define g_vdone (p.sc->vdone)
#define g_lnst (p.sc->lnst)
#define g_rec (p.sc->rec)
#define g_ts (p.sc->ts)
#define g_h (p.sc->h)

struct Params {
  const bf16* w_mod; const bf16* c; Scratch* sc; const bf16* x; const bf16* w_r; bf16* out;
  const bf16* wq; const bf16* wo; const bf16* wg; const bf16* wu; const bf16* wd; const bf16* kc; const bf16* vc;
};

__device__ __forceinline__ uint32_t smem_u32(const void* p) { return (uint32_t)__cvta_generic_to_shared(p); }
__device__ __forceinline__ void mbar_init(uint32_t bar, uint32_t cnt) { asm volatile("mbarrier.init.shared::cta.b64 [%0], %1;" :: "r"(bar), "r"(cnt) : "memory"); }
__device__ __forceinline__ void mbar_expect_tx(uint32_t bar, uint32_t bytes) { asm volatile("mbarrier.arrive.expect_tx.shared::cta.b64 _, [%0], %1;" :: "r"(bar), "r"(bytes) : "memory"); }
__device__ __forceinline__ void mbar_arrive(uint32_t bar) { asm volatile("mbarrier.arrive.shared::cta.b64 _, [%0];" :: "r"(bar) : "memory"); }
__device__ __forceinline__ void mbar_arrive_cl(uint32_t cluster_addr) { asm volatile("mbarrier.arrive.shared::cluster.b64 _, [%0];" :: "r"(cluster_addr) : "memory"); }
__device__ __forceinline__ uint32_t mapa(uint32_t addr, uint32_t cta) { uint32_t r; asm("mapa.shared::cluster.u32 %0, %1, %2;" : "=r"(r) : "r"(addr), "r"(cta)); return r; }
__device__ __forceinline__ bool mbar_test(uint32_t bar, uint32_t parity) {
  uint32_t ok;
  asm volatile("{\n.reg .pred p;\nmbarrier.test_wait.parity.shared::cta.b64 p, [%1], %2;\nselp.u32 %0, 1, 0, p;\n}" : "=r"(ok) : "r"(bar), "r"(parity) : "memory");
  return ok;
}
constexpr int SPIN_LIMIT = 300000;
__device__ __forceinline__ void spin_guard(int& it) {
  asm volatile("{\n.reg .pred p;\n.reg .b64 z;\nadd.s32 %0, %0, 1;\nsetp.gt.s32 p, %0, %1;\nmov.b64 z, 0;\n@p st.volatile.global.u32 [z], %0;\n}" : "+r"(it) : "n"(SPIN_LIMIT));
}
__device__ __forceinline__ void mbar_wait_g(uint32_t bar, uint32_t parity) {
  asm volatile("{\n.reg .pred p, q;\n.reg .b32 c;\n.reg .b64 z;\nmov.b32 c, 0;\nmov.b64 z, 0;\nMW_LOOP:\n"
               "mbarrier.try_wait.parity.shared::cta.b64 p, [%0], %1;\nadd.s32 c, c, 1;\nsetp.gt.s32 q, c, %2;\n"
               "@q st.volatile.global.u32 [z], c;\n@!p bra MW_LOOP;\n}" :: "r"(bar), "r"(parity), "n"(SPIN_LIMIT) : "memory");
}
__device__ __forceinline__ void mbar_wait(uint32_t bar, uint32_t parity) {
  asm volatile("{\n.reg .pred p;\nMW_LOOP:\nmbarrier.try_wait.parity.shared::cta.b64 p, [%0], %1;\n@!p bra MW_LOOP;\n}" :: "r"(bar), "r"(parity) : "memory");
}
__device__ __forceinline__ void bb_fence(uint32_t v) {
  asm volatile("{\n.reg .pred p;\n.reg .u32 c;\nsetp.ne.u32 p, %0, 0;\n@p bra.uni BF_DONE;\nBF_LOOP:\nnanosleep.u32 1;\nmov.u32 c, %%clock;\nsetp.eq.u32 p, c, 0;\n@p bra.uni BF_LOOP;\nBF_DONE:\n}" :: "r"(v) : "memory");
}
__device__ __forceinline__ bool elect_one() {
  uint32_t pred;
  asm volatile("{\n.reg .pred P;\nelect.sync _|P, 0xffffffff;\nselp.u32 %0, 1, 0, P;\n}" : "=r"(pred));
  return pred;
}
__device__ __forceinline__ void tma_ld(uint32_t dst, const CUtensorMap* m, int c0, int c1, uint32_t bar) {
  asm volatile("cp.async.bulk.tensor.2d.shared::cluster.global.mbarrier::complete_tx::bytes [%0], [%1, {%3, %4}], [%2];"
    :: "r"(dst), "l"(m), "r"(bar), "r"(c0), "r"(c1) : "memory");
}
__device__ __forceinline__ void tma_ld_hint(uint32_t dst, const CUtensorMap* m, int c0, int c1, uint32_t bar, uint64_t pol) {
  asm volatile("cp.async.bulk.tensor.2d.shared::cluster.global.mbarrier::complete_tx::bytes.L2::cache_hint [%0], [%1, {%3, %4}], [%2], %5;"
    :: "r"(dst), "l"(m), "r"(bar), "r"(c0), "r"(c1), "l"(pol) : "memory");
}
__device__ __forceinline__ void tma_ld_mc(uint32_t dst, const CUtensorMap* m, int c0, int c1, uint32_t bar) {
  asm volatile("cp.async.bulk.tensor.2d.shared::cluster.global.mbarrier::complete_tx::bytes.multicast::cluster [%0], [%1, {%3, %4}], [%2], %5;"
    :: "r"(dst), "l"(m), "r"(bar), "r"(c0), "r"(c1), "h"((uint16_t)3) : "memory");
}
__device__ __forceinline__ void tma_ld_mc_hint(uint32_t dst, const CUtensorMap* m, int c0, int c1, uint32_t bar, uint64_t pol) {
  asm volatile("cp.async.bulk.tensor.2d.shared::cluster.global.mbarrier::complete_tx::bytes.multicast::cluster.L2::cache_hint [%0], [%1, {%3, %4}], [%2], %5, %6;"
    :: "r"(dst), "l"(m), "r"(bar), "r"(c0), "r"(c1), "h"((uint16_t)3), "l"(pol) : "memory");
}
__device__ __forceinline__ void tma_ld3_hint(uint32_t dst, const CUtensorMap* m, int row, int blk, uint32_t bar, uint64_t pol) {
  asm volatile("cp.async.bulk.tensor.3d.shared::cluster.global.mbarrier::complete_tx::bytes.L2::cache_hint [%0], [%1, {0, %3, %4}], [%2], %5;"
    :: "r"(dst), "l"(m), "r"(bar), "r"(row), "r"(blk), "l"(pol) : "memory");
}
__device__ __forceinline__ void tma_st(const CUtensorMap* m, int c0, int c1, uint32_t src) {
  asm volatile("cp.async.bulk.tensor.2d.global.shared::cta.bulk_group [%0, {%2, %3}], [%1];" :: "l"(m), "r"(src), "r"(c0), "r"(c1) : "memory");
}
__device__ __forceinline__ void tma_prefetch_desc(const CUtensorMap* m) { asm volatile("prefetch.tensormap [%0];" :: "l"(m) : "memory"); }
__device__ __forceinline__ void l2_prefetch(const void* p, uint32_t bytes) { asm volatile("cp.async.bulk.prefetch.L2.global [%0], %1;" :: "l"(p), "r"(bytes) : "memory"); }
__device__ __forceinline__ void bulk_commit() { asm volatile("cp.async.bulk.commit_group;" ::: "memory"); }
__device__ __forceinline__ void bulk_wait_read() { asm volatile("cp.async.bulk.wait_group.read 0;" ::: "memory"); }
__device__ __forceinline__ void bulk_wait_all() { asm volatile("cp.async.bulk.wait_group 0;" ::: "memory"); }
__device__ __forceinline__ void fence_async_smem() { asm volatile("fence.proxy.async.shared::cta;" ::: "memory"); }
__device__ __forceinline__ void fence_async_global() { asm volatile("fence.proxy.async.global;" ::: "memory"); }
__device__ __forceinline__ void fence_acquire_gpu() { asm volatile("fence.acquire.gpu;" ::: "memory"); }
__device__ __forceinline__ void fence_release_gpu() { asm volatile("fence.release.gpu;" ::: "memory"); }
__device__ __forceinline__ void st_async_f32x4(uint32_t cluster_addr, const float* v, uint32_t cluster_bar) {
  asm volatile("st.async.weak.shared::cluster.mbarrier::complete_tx::bytes.v4.f32 [%0], {%1,%2,%3,%4}, [%5];"
    :: "r"(cluster_addr), "f"(v[0]), "f"(v[1]), "f"(v[2]), "f"(v[3]), "r"(cluster_bar) : "memory");
}
__device__ __forceinline__ void nb_sync(int id, int n) { asm volatile("bar.sync %0, %1;" :: "r"(id), "r"(n) : "memory"); }
__device__ __forceinline__ void nb_arrive(int id, int n) { asm volatile("bar.arrive %0, %1;" :: "r"(id), "r"(n) : "memory"); }
__device__ __forceinline__ void wg_fence() { asm volatile("wgmma.fence.sync.aligned;" ::: "memory"); }
__device__ __forceinline__ void wg_commit() { asm volatile("wgmma.commit_group.sync.aligned;" ::: "memory"); }
template <int N> __device__ __forceinline__ void wg_wait() { asm volatile("wgmma.wait_group.sync.aligned %0;" :: "n"(N) : "memory"); }
template <int N> __device__ __forceinline__ void reg_fence(float* a) {
#pragma unroll
  for (int i = 0; i < N; i++) asm volatile("" : "+f"(a[i]) :: "memory");
}
template <int N> __device__ __forceinline__ void reg_fence(uint32_t* a) {
#pragma unroll
  for (int i = 0; i < N; i++) asm volatile("" : "+r"(a[i]) :: "memory");
}
__device__ __forceinline__ uint64_t mk_desc(uint32_t addr, uint32_t lbo) {
  return (uint64_t)((addr & 0x3FFFF) >> 4) | ((uint64_t)(lbo >> 4) << 16) | ((uint64_t)(1024 >> 4) << 32) | (1ull << 62);
}

__device__ __forceinline__ uint64_t policy_evict_first() { uint64_t pol; asm("createpolicy.fractional.L2::evict_first.b64 %0, 1.0;" : "=l"(pol)); return pol; }
__device__ __forceinline__ uint32_t ld_relaxed(const uint32_t* p) { uint32_t v; asm volatile("ld.relaxed.gpu.global.u32 %0, [%1];" : "=r"(v) : "l"(p) : "memory"); return v; }
__device__ __forceinline__ void st_relaxed(uint32_t* p, uint32_t v) { asm volatile("st.relaxed.gpu.global.u32 [%0], %1;" :: "l"(p), "r"(v) : "memory"); }
__device__ __forceinline__ void red_add_relaxed(uint32_t* p, uint32_t v) { asm volatile("red.relaxed.gpu.global.add.u32 [%0], %1;" :: "l"(p), "r"(v) : "memory"); }
__device__ __forceinline__ uint2 ld_pkt8(const uint2* p) {
  uint2 v; asm volatile("{\n.reg .b64 t;\nld.relaxed.gpu.global.b64 t, [%2];\nmov.b64 {%0,%1}, t;\n}" : "=r"(v.x), "=r"(v.y) : "l"(p) : "memory"); return v;
}
__device__ __forceinline__ void st_pkt8(uint2* p, uint32_t a, uint32_t b) {
  asm volatile("{\n.reg .b64 t;\nmov.b64 t, {%1,%2};\nst.relaxed.gpu.global.b64 [%0], t;\n}" :: "l"(p), "r"(a), "r"(b) : "memory");
}
__device__ __forceinline__ uint4 ld_pkt16(const uint4* p) {
  uint4 v; asm volatile("{\n.reg .b128 t;\n.reg .b64 a, b;\nld.relaxed.gpu.global.b128 t, [%4];\nmov.b128 {a, b}, t;\nmov.b64 {%0,%1}, a;\nmov.b64 {%2,%3}, b;\n}"
    : "=r"(v.x), "=r"(v.y), "=r"(v.z), "=r"(v.w) : "l"(p) : "memory"); return v;
}
__device__ __forceinline__ void st_pkt16(uint4* p, uint32_t x, uint32_t y, uint32_t z, uint32_t w) {
  asm volatile("{\n.reg .b128 t;\n.reg .b64 a, b;\nmov.b64 a, {%1,%2};\nmov.b64 b, {%3,%4};\nmov.b128 t, {a, b};\nst.relaxed.gpu.global.b128 [%0], t;\n}"
    :: "l"(p), "r"(x), "r"(y), "r"(z), "r"(w) : "memory");
}
__device__ __forceinline__ uint32_t lds32(uint32_t a) { uint32_t v; asm volatile("ld.shared.u32 %0, [%1];" : "=r"(v) : "r"(a) : "memory"); return v; }
__device__ __forceinline__ float lds_f32(uint32_t a) { float v; asm volatile("ld.shared.f32 %0, [%1];" : "=f"(v) : "r"(a) : "memory"); return v; }
__device__ __forceinline__ uint2 lds64(uint32_t a) { uint2 v; asm volatile("ld.shared.v2.u32 {%0,%1}, [%2];" : "=r"(v.x), "=r"(v.y) : "r"(a) : "memory"); return v; }
__device__ __forceinline__ uint4 lds128(uint32_t a) { uint4 v; asm volatile("ld.shared.v4.u32 {%0,%1,%2,%3}, [%4];" : "=r"(v.x), "=r"(v.y), "=r"(v.z), "=r"(v.w) : "r"(a) : "memory"); return v; }
__device__ __forceinline__ void sts32(uint32_t a, uint32_t v) { asm volatile("st.shared.u32 [%0], %1;" :: "r"(a), "r"(v) : "memory"); }
__device__ __forceinline__ void sts64(uint32_t a, uint32_t x, uint32_t y) { asm volatile("st.shared.v2.u32 [%0], {%1,%2};" :: "r"(a), "r"(x), "r"(y) : "memory"); }
__device__ __forceinline__ void sts128(uint32_t a, uint32_t x, uint32_t y, uint32_t z, uint32_t w) { asm volatile("st.shared.v4.u32 [%0], {%1,%2,%3,%4};" :: "r"(a), "r"(x), "r"(y), "r"(z), "r"(w) : "memory"); }
__device__ __forceinline__ void stsm4(uint32_t a, uint32_t x, uint32_t y, uint32_t z, uint32_t w) {
  asm volatile("stmatrix.sync.aligned.m8n8.x4.shared.b16 [%0], {%1,%2,%3,%4};" :: "r"(a), "r"(x), "r"(y), "r"(z), "r"(w) : "memory");
}
__device__ __forceinline__ void ldsm4(uint32_t a, uint32_t* r) {
  asm volatile("ldmatrix.sync.aligned.m8n8.x4.shared.b16 {%0,%1,%2,%3}, [%4];" : "=r"(r[0]), "=r"(r[1]), "=r"(r[2]), "=r"(r[3]) : "r"(a) : "memory");
}
__device__ __forceinline__ void ldsm4t(uint32_t a, uint32_t* r) {
  asm volatile("ldmatrix.sync.aligned.m8n8.x4.trans.shared.b16 {%0,%1,%2,%3}, [%4];" : "=r"(r[0]), "=r"(r[1]), "=r"(r[2]), "=r"(r[3]) : "r"(a) : "memory");
}
__device__ __forceinline__ void mma16816(float* d, const uint32_t* a, uint32_t b0, uint32_t b1) {
  asm volatile("mma.sync.aligned.m16n8k16.row.col.f32.bf16.bf16.f32 {%0,%1,%2,%3}, {%4,%5,%6,%7}, {%8,%9}, {%0,%1,%2,%3};"
    : "+f"(d[0]), "+f"(d[1]), "+f"(d[2]), "+f"(d[3]) : "r"(a[0]), "r"(a[1]), "r"(a[2]), "r"(a[3]), "r"(b0), "r"(b1));
}
__device__ __forceinline__ void mma1688(float* d, uint32_t a0, uint32_t a1, uint32_t b0) {
  asm volatile("mma.sync.aligned.m16n8k8.row.col.f32.bf16.bf16.f32 {%0,%1,%2,%3}, {%4,%5}, {%6}, {%0,%1,%2,%3};"
    : "+f"(d[0]), "+f"(d[1]), "+f"(d[2]), "+f"(d[3]) : "r"(a0), "r"(a1), "r"(b0));
}
__device__ __forceinline__ uint32_t pack2(float lo, float hi) { uint32_t r; asm("cvt.rn.bf16x2.f32 %0, %1, %2;" : "=r"(r) : "f"(hi), "f"(lo)); return r; }
__device__ __forceinline__ float lo2f(uint32_t v) { return __uint_as_float(v << 16); }
__device__ __forceinline__ float hi2f(uint32_t v) { return __uint_as_float(v & 0xffff0000u); }
__device__ __forceinline__ uint32_t hmul2(uint32_t a, uint32_t b) { uint32_t r; asm("mul.rn.bf16x2 %0, %1, %2;" : "=r"(r) : "r"(a), "r"(b)); return r; }
__device__ __forceinline__ uint32_t hadd2(uint32_t a, uint32_t b) { uint32_t r; asm("add.rn.bf16x2 %0, %1, %2;" : "=r"(r) : "r"(a), "r"(b)); return r; }
__device__ __forceinline__ uint32_t hsub2(uint32_t a, uint32_t b) { uint32_t r; asm("sub.rn.bf16x2 %0, %1, %2;" : "=r"(r) : "r"(a), "r"(b)); return r; }
__device__ __forceinline__ uint32_t hfma2(uint32_t a, uint32_t b, uint32_t c) { uint32_t r; asm("fma.rn.bf16x2 %0, %1, %2, %3;" : "=r"(r) : "r"(a), "r"(b), "r"(c)); return r; }
__device__ __forceinline__ float rbf(float v) { return lo2f(pack2(v, 0.f)); }
__device__ __forceinline__ float ex2(float v) { float r; asm("ex2.approx.ftz.f32 %0, %1;" : "=f"(r) : "f"(v)); return r; }
__device__ __forceinline__ float rcp_f(float v) { float r; asm("rcp.approx.ftz.f32 %0, %1;" : "=f"(r) : "f"(v)); return r; }
__device__ __forceinline__ float sqrt_f(float v) { float r; asm("sqrt.approx.ftz.f32 %0, %1;" : "=f"(r) : "f"(v)); return r; }
__device__ __forceinline__ float sigmoid_f(float v) { return rcp_f(1.f + ex2(-1.4426950408889634f * v)); }
__device__ __forceinline__ float silu_f(float v) { return v * sigmoid_f(v); }
constexpr uint32_t ONE2 = 0x3f803f80u;

#define R8(a,o) "+f"(a[o+0]), "+f"(a[o+1]), "+f"(a[o+2]), "+f"(a[o+3]), "+f"(a[o+4]), "+f"(a[o+5]), "+f"(a[o+6]), "+f"(a[o+7])
#define R64(a,o) R8(a,o), R8(a,o+8), R8(a,o+16), R8(a,o+24), R8(a,o+32), R8(a,o+40), R8(a,o+48), R8(a,o+56)
#define D64 "{%0,%1,%2,%3,%4,%5,%6,%7,%8,%9,%10,%11,%12,%13,%14,%15,%16,%17,%18,%19,%20,%21,%22,%23,%24,%25,%26,%27,%28,%29,%30,%31," \
            "%32,%33,%34,%35,%36,%37,%38,%39,%40,%41,%42,%43,%44,%45,%46,%47,%48,%49,%50,%51,%52,%53,%54,%55,%56,%57,%58,%59,%60,%61,%62,%63"
#define D128 D64 ",%64,%65,%66,%67,%68,%69,%70,%71,%72,%73,%74,%75,%76,%77,%78,%79,%80,%81,%82,%83,%84,%85,%86,%87,%88,%89,%90,%91,%92,%93,%94,%95," \
            "%96,%97,%98,%99,%100,%101,%102,%103,%104,%105,%106,%107,%108,%109,%110,%111,%112,%113,%114,%115,%116,%117,%118,%119,%120,%121,%122,%123,%124,%125,%126,%127"

template <int TB> __device__ __forceinline__ void wgmma_ss128(float* d, uint64_t da, uint64_t db, int acc) {
  asm volatile("{\n.reg .pred p;\nsetp.ne.b32 p, %66, 0;\nwgmma.mma_async.sync.aligned.m64n128k16.f32.bf16.bf16 " D64 "}, %64, %65, p, 1, 1, 0, %67;\n}"
    : R64(d, 0) : "l"(da), "l"(db), "r"(acc), "n"(TB));
}
template <int TB> __device__ __forceinline__ void wgmma_rs128(float* d, const uint32_t* a, uint64_t db, int acc) {
  asm volatile("{\n.reg .pred p;\nsetp.ne.b32 p, %69, 0;\nwgmma.mma_async.sync.aligned.m64n128k16.f32.bf16.bf16 " D64 "}, {%64,%65,%66,%67}, %68, p, 1, 1, %70;\n}"
    : R64(d, 0) : "r"(a[0]), "r"(a[1]), "r"(a[2]), "r"(a[3]), "l"(db), "r"(acc), "n"(TB));
}
template <int TB> __device__ __forceinline__ void wgmma_ss256(float* d, uint64_t da, uint64_t db, int acc) {
  asm volatile("{\n.reg .pred p;\nsetp.ne.b32 p, %130, 0;\nwgmma.mma_async.sync.aligned.m64n256k16.f32.bf16.bf16 " D128 "}, %128, %129, p, 1, 1, 0, %131;\n}"
    : R64(d, 0), R64(d, 64) : "l"(da), "l"(db), "r"(acc), "n"(TB));
}

#define W8(a,o) "=f"(a[o+0]), "=f"(a[o+1]), "=f"(a[o+2]), "=f"(a[o+3]), "=f"(a[o+4]), "=f"(a[o+5]), "=f"(a[o+6]), "=f"(a[o+7])
#define W64(a,o) W8(a,o), W8(a,o+8), W8(a,o+16), W8(a,o+24), W8(a,o+32), W8(a,o+40), W8(a,o+48), W8(a,o+56)
template <int TB> __device__ __forceinline__ void wgmma_ss128_z(float* d, uint64_t da, uint64_t db) {
  asm volatile("wgmma.mma_async.sync.aligned.m64n128k16.f32.bf16.bf16 " D64 "}, %64, %65, 0, 1, 1, 0, %66;"
    : W64(d, 0) : "l"(da), "l"(db), "n"(TB));
}
template <int TB> __device__ __forceinline__ void wgmma_rs128_z(float* d, const uint32_t* a, uint64_t db) {
  asm volatile("wgmma.mma_async.sync.aligned.m64n128k16.f32.bf16.bf16 " D64 "}, {%64,%65,%66,%67}, %68, 0, 1, 1, %69;"
    : W64(d, 0) : "r"(a[0]), "r"(a[1]), "r"(a[2]), "r"(a[3]), "l"(db), "n"(TB));
}
template <int TB> __device__ __forceinline__ void wgmma_ss256_z(float* d, uint64_t da, uint64_t db) {
  asm volatile("wgmma.mma_async.sync.aligned.m64n256k16.f32.bf16.bf16 " D128 "}, %128, %129, 0, 1, 1, 0, %130;"
    : W64(d, 0), W64(d, 64) : "l"(da), "l"(db), "n"(TB));
}

template <int TB> __device__ __forceinline__ void wgmma_rs256(float* d, const uint32_t* a, uint64_t db) {
  asm volatile("wgmma.mma_async.sync.aligned.m64n256k16.f32.bf16.bf16 " D128 "}, {%128,%129,%130,%131}, %132, 1, 1, 1, %133;"
    : R64(d, 0), R64(d, 64) : "r"(a[0]), "r"(a[1]), "r"(a[2]), "r"(a[3]), "l"(db), "n"(TB));
}
template <int TB> __device__ __forceinline__ void wgmma_rs256_z(float* d, const uint32_t* a, uint64_t db) {
  asm volatile("wgmma.mma_async.sync.aligned.m64n256k16.f32.bf16.bf16 " D128 "}, {%128,%129,%130,%131}, %132, 0, 1, 1, %133;"
    : W64(d, 0), W64(d, 64) : "r"(a[0]), "r"(a[1]), "r"(a[2]), "r"(a[3]), "l"(db), "n"(TB));
}
#define D32 "{%0,%1,%2,%3,%4,%5,%6,%7,%8,%9,%10,%11,%12,%13,%14,%15,%16,%17,%18,%19,%20,%21,%22,%23,%24,%25,%26,%27,%28,%29,%30,%31}"
__device__ __forceinline__ void wgmma_rs64(float* d, const uint32_t* a, uint64_t db) {
  asm volatile("wgmma.mma_async.sync.aligned.m64n64k16.f32.bf16.bf16 " D32 ", {%32,%33,%34,%35}, %36, 1, 1, 1, 0;"
    : R8(d, 0), R8(d, 8), R8(d, 16), R8(d, 24) : "r"(a[0]), "r"(a[1]), "r"(a[2]), "r"(a[3]), "l"(db));
}
__device__ __forceinline__ void wgmma_rs64_z(float* d, const uint32_t* a, uint64_t db) {
  asm volatile("wgmma.mma_async.sync.aligned.m64n64k16.f32.bf16.bf16 " D32 ", {%32,%33,%34,%35}, %36, 0, 1, 1, 0;"
    : W8(d, 0), W8(d, 8), W8(d, 16), W8(d, 24) : "r"(a[0]), "r"(a[1]), "r"(a[2]), "r"(a[3]), "l"(db));
}
__device__ __forceinline__ void issue_qk(float* S, const uint32_t* Q, uint64_t dk) {
  wgmma_rs64_z(S, Q, dk);
#pragma unroll
  for (int kk = 1; kk < 8; kk++) wgmma_rs64(S, Q + 4 * kk, dk + (kk >> 2) * 512 + (kk & 3) * 2);
}
__device__ __forceinline__ void issue_pv(float* O, const uint32_t* P, uint64_t dv, int acc) {
#pragma unroll
  for (int kk = 0; kk < 4; kk++) wgmma_rs128<1>(O, P + 4 * kk, dv + kk * 128, kk ? 1 : acc);
}

#define TS(i)
#define TSC(i)
#define TSX(i)
#define TSY(k) do { if ((tid & 127) == 0) TS((k) + 40 * wg); } while (0)
#define TT(k)
#define TR(k)
#define TH(k)
#define TA(k)
#define TAFLUSH()

struct SoftmaxState { float c0, c1, l0, l1; bool shifted; };
constexpr float SM_SCALE = 0.08838834764831845f * 1.4426950408889634f;
__device__ __forceinline__ void softmax_start(SoftmaxState& z) { z.c0 = z.c1 = z.l0 = z.l1 = 0.f; z.shifted = false; }
__device__ __forceinline__ void softmax_half(float* S, uint32_t* P, float* O, SoftmaxState& z, bool first, uint32_t tag) {
  const float lo0 = z.l0, lo1 = z.l1;
  float lim = 1.2676506002282294e30f;
  const float low = first ? 8.673617379884035e-19f : 0.f;
  if (z.shifted) {
#pragma unroll
    for (int j = 0; j < 32; j++) S[j] += (j & 2) ? z.c1 : z.c0;
  }
#pragma unroll 1
  while (true) {
    bb_fence(tag);
#pragma unroll
    for (int j = 0; j < 8; j++) {
      const float p0 = ex2(S[4 * j]), p1 = ex2(S[4 * j + 1]), p2 = ex2(S[4 * j + 2]), p3 = ex2(S[4 * j + 3]);
      z.l0 += p0; z.l1 += p2; z.l0 += p1; z.l1 += p3;
      P[2 * j] = pack2(p0, p1); P[2 * j + 1] = pack2(p2, p3);
    }
    if (!__any_sync(0xffffffffu, !(z.l0 < lim && z.l1 < lim && fminf(z.l0, z.l1) >= low) && lim > 0.f)) break;
    float d0 = fmaxf(S[0], S[1]), d1 = fmaxf(S[2], S[3]);
#pragma unroll
    for (int j = 1; j < 8; j++) { d0 = fmaxf(d0, fmaxf(S[4 * j], S[4 * j + 1])); d1 = fmaxf(d1, fmaxf(S[4 * j + 2], S[4 * j + 3])); }
    d0 = fmaxf(d0, __shfl_xor_sync(0xffffffffu, d0, 1)); d1 = fmaxf(d1, __shfl_xor_sync(0xffffffffu, d1, 1));
    d0 = fmaxf(d0, __shfl_xor_sync(0xffffffffu, d0, 2)); d1 = fmaxf(d1, __shfl_xor_sync(0xffffffffu, d1, 2));
    if (!first) { d0 = fmaxf(d0, 0.f); d1 = fmaxf(d1, 0.f); }
    z.shifted = true;
    z.c0 -= d0; z.c1 -= d1;
#pragma unroll
    for (int j = 0; j < 32; j++) S[j] -= (j & 2) ? d1 : d0;
    const float a0 = first ? 1.f : ex2(-d0), a1 = first ? 1.f : ex2(-d1);
    z.l0 = lo0 * a0; z.l1 = lo1 * a1;
    lim = -1.f;
    wg_wait<0>();
    reg_fence<64>(O);
#pragma unroll
    for (int j = 0; j < 16; j++) { O[4 * j] *= a0; O[4 * j + 1] *= a0; O[4 * j + 2] *= a1; O[4 * j + 3] *= a1; }
  }
}

__device__ __forceinline__ void modulate_frags(uint32_t* A, const uint32_t* V, const uint4* R, const uint32_t* ln) {
#pragma unroll
  for (int kk = 0; kk < 4; kk++) {
    const uint4 sa = R[kk >> 1], c1 = R[2 + (kk >> 1)];
#pragma unroll
    for (int j = 0; j < 4; j++) {
      const uint32_t n = hfma2(V[4 * kk + j], ln[(j & 1) * 2 + 1], ln[(j & 1) * 2]);
      A[4 * kk + j] = (kk & 1) ? ((j & 2) ? hfma2(n, c1.w, sa.x) : hfma2(n, c1.z, sa.w)) : ((j & 2) ? hfma2(n, c1.y, sa.z) : hfma2(n, c1.x, sa.y));
    }
  }
}
__device__ __forceinline__ void publish_record(uint4* dst, uint32_t pk, int src, int vec, bool doit) {
  const int r = vec ? 0 : 12;
  const uint32_t x = __shfl_sync(0xffffffffu, pk, src + r), y = __shfl_sync(0xffffffffu, pk, src + ((r + 4) & 12));
  const uint32_t z = __shfl_sync(0xffffffffu, pk, src + ((r + 8) & 12)), w = __shfl_sync(0xffffffffu, pk, src + ((r + 12) & 12));
  if (doit) st_pkt16(dst, ~x, y, z, w);
}
__device__ __forceinline__ void put_record(uint32_t sb, int idx, const uint4& v) {
  sts128(sb + SM_STASH + idx * 16, ~v.x, v.y, v.z, v.w);
  sts128(sb + SM_STASH + 16384 + idx * 16, ~v.x, v.y, v.z, v.w);
}
__device__ __forceinline__ float mod_value(float v, int vec) {
  v = rbf(v);
  return (vec ? rbf(1.f + v) : v) * SM_SCALE;
}

__device__ __forceinline__ void row_rcp(float& l0, float& l1) {
  l0 += __shfl_xor_sync(0xffffffffu, l0, 1); l1 += __shfl_xor_sync(0xffffffffu, l1, 1);
  l0 += __shfl_xor_sync(0xffffffffu, l0, 2); l1 += __shfl_xor_sync(0xffffffffu, l1, 2);
  l0 = rcp_f(l0); l1 = rcp_f(l1);
}
__device__ __forceinline__ void stage_o(const float* O, float r0, float r1, uint32_t stsm_addr) {
#pragma unroll
  for (int kk = 0; kk < 8; kk++) {
    stsm4((stsm_addr + (kk >> 2) * 8192) ^ ((kk & 3) * 32),
          pack2(O[8 * kk + 0] * r0, O[8 * kk + 1] * r0), pack2(O[8 * kk + 2] * r1, O[8 * kk + 3] * r1),
          pack2(O[8 * kk + 4] * r0, O[8 * kk + 5] * r0), pack2(O[8 * kk + 6] * r1, O[8 * kk + 7] * r1));
  }
}

__global__ void __cluster_dims__(2, 1, 1) __launch_bounds__(NTHREADS, 1)
fused_kernel(const Params p, const __grid_constant__ CUtensorMap mH, const __grid_constant__ CUtensorMap mWq,
             const __grid_constant__ CUtensorMap mK, const __grid_constant__ CUtensorMap mV,
             const __grid_constant__ CUtensorMap mO, const __grid_constant__ CUtensorMap mWo,
             const __grid_constant__ CUtensorMap mX, const __grid_constant__ CUtensorMap mOut,
             const __grid_constant__ CUtensorMap mWg, const __grid_constant__ CUtensorMap mWu,
             const __grid_constant__ CUtensorMap mWd, const __grid_constant__ CUtensorMap mWm,
             const __grid_constant__ CUtensorMap mWs) {
  extern __shared__ __align__(1024) uint8_t smem_raw[];
  TH(0);
  const uint32_t sb = smem_u32(smem_raw);
  const int tid = threadIdx.x;
  const int b0 = blockIdx.x;
  const int lane = tid & 31;
  const int role = __shfl_sync(0xffffffffu, tid >> 8, 0);

  if (b0 >= NMAIN) {
    const uint32_t tag = ld_relaxed(&g_epoch) + 1;
    const int sp = b0 - NMAIN, vec = 2 + sp;
    const int warp = __shfl_sync(0xffffffffu, tid >> 5, 0);
    float* sc = reinterpret_cast<float*>(smem_raw + SM_STASH);
    float* red = reinterpret_cast<float*>(smem_raw + SM_STASH + 4096);
    const int ridx = (lane >> 3) * 256 + (sp & 1) * 128 + 64 + (sp >> 1) * 16 + (warp & 1) * 8 + (lane & 7);
    if (warp < 8) st_pkt16(&g_rec[warp >> 2][0][ridx + (warp & 2) * 16], 0, 0, 0, 0);
#pragma unroll 1
    for (int i = tid; i < 1024; i += NTHREADS) sc[i] = rbf(silu_f(__bfloat162float(p.c[i])));
    if (tid == 0) {
      tma_prefetch_desc(&mWs);
      for (int s = 0; s < NST2; s++) { mbar_init(sb + BAR_FULL2 + 8 * s, 1); mbar_init(sb + BAR_EMPTY2 + 8 * s, 8); }
      fence_async_smem();
      int it = 0;
      do { __nanosleep(100); spin_guard(it); } while (ld_pkt16(&g_lnst[8 * 32 + 16 * sp]).w != tag);
      if (SPD) __nanosleep(SPD);
    }
    __syncthreads();
    int s = 0; uint32_t ph = 0;
    if (tid == 0) TS(0);
    if (warp == 8) {
      const uint64_t pol = policy_evict_first();
#pragma unroll 1
      for (int n = 0; n < 80; n++) {
        mbar_wait_g(sb + BAR_EMPTY2 + 8 * s, ph ^ 1);
        if (elect_one()) {
          mbar_expect_tx(sb + BAR_FULL2 + 8 * s, 32768);
          if (n < 16) {
            tma_ld_hint(sb + s * ST2, &mWs, (sp & 1) * 1024 + 512 + (n >> 3) * 256 + (sp >> 1) * 128, (n & 7) * 128, sb + BAR_FULL2 + 8 * s, pol);
          } else {
#pragma unroll
            for (int j = 0; j < 4; j++) tma_ld_hint(sb + s * ST2 + j * 8192, &mWm, vec * 1024 + j * 256, (n - 16) * 16, sb + BAR_FULL2 + 8 * s, pol);
          }
        }
        __syncwarp();
        if (++s == NST2) { s = 0; ph ^= 1; }
      }
    } else if (warp < 8) {
      float acc[8];
#pragma unroll
      for (int i = 0; i < 8; i++) acc[i] = 0.f;
      auto stage = [&](uint32_t a0, int da, const float* cp, int dc) {
        mbar_wait_g(sb + BAR_FULL2 + 8 * s, ph);
#pragma unroll
        for (int i = 0; i < 8; i++) {
          const uint4 v = lds128(a0 + s * ST2 + i * da);
          const float c = cp[i * dc];
          acc[0] = fmaf(lo2f(v.x), c, acc[0]); acc[1] = fmaf(hi2f(v.x), c, acc[1]);
          acc[2] = fmaf(lo2f(v.y), c, acc[2]); acc[3] = fmaf(hi2f(v.y), c, acc[3]);
          acc[4] = fmaf(lo2f(v.z), c, acc[4]); acc[5] = fmaf(hi2f(v.z), c, acc[5]);
          acc[6] = fmaf(lo2f(v.w), c, acc[6]); acc[7] = fmaf(hi2f(v.w), c, acc[7]);
        }
        if (__shfl_sync(0xffffffffu, lane, __float_as_uint(acc[7]) & 31) < 32 && lane == 0) mbar_arrive(sb + BAR_EMPTY2 + 8 * s);
        if (++s == NST2) { s = 0; ph ^= 1; }
      };
#pragma unroll 1
      for (int n = 0; n < 16; n++) {
        stage(sb + tid * 16, 4096, sc + (n & 7) * 128 + (tid >> 4), 16);
        if ((n & 7) == 7) {
          float* r2 = red + 2048 + (n & 8) * 256;
#pragma unroll
          for (int i = 0; i < 8; i++) { r2[tid * 8 + i] = acc[i]; acc[i] = 0.f; }
          nb_sync(NB_CONS, 256);
          if (warp < 2) {
            float v0 = 0.f, v1 = 0.f;
#pragma unroll 4
            for (int i = 0; i < 16; i++) { const float2 e = reinterpret_cast<const float2*>(r2)[i * 64 + tid]; v0 += e.x; v1 += e.y; }
            publish_record(&g_rec[tag & 1][0][ridx + (n >> 3) * 32], pack2(mod_value(v0, sp & 1), mod_value(v1, sp & 1)),
                           (lane & 4) * 4 + (lane & 3), sp & 1, true);
          }
          if (tid == 0) TS(1 + (n >> 3));
        }
      }
#pragma unroll 1
      for (int n = 0; n < 64; n++) {
        stage(sb + ((tid >> 5) & 3) * 8192 + (tid >> 7) * 4096 + (tid & 31) * 16, 512, sc + n * 16 + (tid >> 7) * 8, 1);
      }
#pragma unroll
      for (int i = 0; i < 8; i++) red[(tid >> 7) * 1024 + (tid & 127) * 8 + i] = acc[i];
    }
    __syncthreads();
    float dot = 0.f;
#pragma unroll 1
    for (int i = tid; i < 512; i += NTHREADS) {
      uint32_t v = pack2(red[2 * i] + red[1024 + 2 * i], red[2 * i + 1] + red[1024 + 2 * i + 1]);
      st_pkt8(&g_mod[vec * 512 + i], v, tag);
      if (vec == 4) v = hadd2(v, ONE2);
      const uint32_t wr = reinterpret_cast<const uint32_t*>(p.w_r)[i];
      dot = fmaf(lo2f(v), lo2f(wr), fmaf(hi2f(v), hi2f(wr), dot));
    }
#pragma unroll
    for (int o = 16; o; o >>= 1) dot += __shfl_xor_sync(0xffffffffu, dot, o);
    if (lane == 0) sc[warp] = dot;
    __syncthreads();
    if (tid == 0) {
      dot = 0.f;
      for (int w = 0; w < 12; w++) dot += sc[w];
      fence_release_gpu();
      st_pkt8(&g_vdone[(vec - 2) * 16], __float_as_uint(dot), tag);
      TS(11);
#pragma unroll 1
      for (int i = 0; i < 128; i++) {
        const int u = i * 4 + (b0 - NMAIN);
        l2_prefetch(p.wo + (size_t)((4 * ((u >> 4) & 7) + (u >> 7)) * 128 + (u & 15) * 8) * 1024, 16384);
        __nanosleep(PFW);
      }
    }
    return;
  }

  const uint32_t rank = b0 & 1;
  const bool slab = !(b0 & 32), late = b0 & 16;
  const uint32_t c0 = clock();
  if (tid == 352) TS(0);
  auto load_slab = [&]() {
    const bf16* wp = p.w_mod + (size_t)(512 * rank + 2 * (tid & ~31) + 2 * (lane & 3) + ((lane >> 2) & 1)) * 6144 + 32 * (b0 >> 1) + 8 * (lane >> 3);
    const uint64_t pef = policy_evict_first();
#pragma unroll
    for (int i = 0; i < 8; i++)
      asm volatile("cp.async.cg.shared.global.L2::cache_hint [%0], [%1], 16, %2;"
        :: "r"(sb + SM_WSLAB + tid * 16 + i * 4096), "l"(wp + (size_t)i * 8 * 6144), "l"(pef) : "memory");
  };
  if (tid == 256) {
    mbar_init(sb + BAR_XH, 1);
    fence_async_smem();
    mbar_expect_tx(sb + BAR_XH, 32768);
    if (XD) while ((uint32_t)clock() - c0 < XD) {}
#pragma unroll
    for (int i = 0; i < 2; i++)
      asm volatile("cp.async.bulk.shared::cluster.global.mbarrier::complete_tx::bytes [%0], [%1], 16384, [%2];"
        :: "r"(sb + SM_XROW + i * ST1), "l"(p.x + (size_t)b0 * 16384 + i * 8192), "r"(sb + BAR_XH) : "memory");
  }
  __syncwarp();
  uint32_t cw[8];
#pragma unroll
  for (int i = 0; i < 8; i++) cw[i] = 0;
  if (!role && slab) {
#pragma unroll
    for (int i = 0; i < 8; i++) cw[i] = ld_relaxed(reinterpret_cast<const uint32_t*>(p.c) + 256 * rank + (tid & ~28) + 4 * i);
  }
  uint32_t epoch = 0;
  if (!role) epoch = ld_relaxed(&p.sc->epoch[lane]);
  if (!role && slab && !late) load_slab();
#define TILE_ROLES() \
  mbar_wait(sb + BAR_ROLE, 0); \
  const int b = 2 * __shfl_sync(0xffffffffu, lds32(sb + SM_ROLE), 0) + rank; \
  const int rt = b >> 3;     \
  const int ct = b & 7;

  if (role) {
    asm volatile("setmaxnreg.dec.sync.aligned.u32 24;");
    const int warp = __shfl_sync(0xffffffffu, tid >> 5, 0);
    if (tid == 256) {
      mbar_init(sb + BAR_RED, 1);
      for (int s = 0; s < 2; s++) mbar_init(sb + BAR_OF + 8 * s, 1);
      mbar_init(sb + BAR_ROLE, 1);
      for (int s = 0; s < 5; s++) { mbar_init(sb + BAR_FULL1 + 8 * s, 1); mbar_init(sb + BAR_EMPTY1 + 8 * s, 4); }
      for (int s = 0; s < 2; s++) { mbar_init(sb + BAR_STASH + 8 * s, 1); mbar_init(sb + BAR_X + 8 * s, 1); }
      for (int s = 0; s < 4; s++) mbar_init(sb + BAR_HS + 8 * s, 1);
      mbar_init(sb + BAR_G, 16); mbar_init(sb + BAR_T1, 1); mbar_init(sb + BAR_HF, 1);
      mbar_init(sb + BAR_SFREE, 4); mbar_init(sb + BAR_TFREE, 8);
      mbar_init(sb + BAR_FFN, 4); mbar_init(sb + BAR_FFN + 8, 2);
      mbar_init(sb + BAR_CAND, 1); mbar_init(sb + BAR_VEC, 32); for (int s = 0; s < 3; s++) mbar_init(sb + BAR_TAB + 8 * s, 32);
      mbar_expect_tx(sb + BAR_RED, 1024);
      mbar_expect_tx(sb + BAR_ROLE, 4);
      asm volatile("fence.mbarrier_init.release.cluster;" ::: "memory");
    }
    __syncwarp();
    asm volatile("barrier.cluster.arrive.relaxed.aligned;" ::: "memory");
    const int ridx = ((lane >> 1) & 3) * 256 + (b0 >> 6) * 128 + ((b0 >> 1) & 31) * 4 + 2 * rank + (lane & 1);
    if (warp == 11 && slab && lane < 8) { st_pkt16(&g_rec[0][0][ridx], 0, 0, 0, 0); st_pkt16(&g_rec[1][0][ridx], 0, 0, 0, 0); }
    if (tid == 256) {
      tma_prefetch_desc(&mWq); tma_prefetch_desc(&mX); tma_prefetch_desc(&mH); tma_prefetch_desc(&mK); tma_prefetch_desc(&mV); tma_prefetch_desc(&mO);
    }
    uint32_t pairid = 0;
    if (tid == 320 && rank == 0) {
      uint32_t t;
      asm("mov.u32 %0, %%smid;" : "=r"(t));
      t >>= 1;
      uint32_t grp = ((0x73216540u >> (4 * ((t < 32 ? t : t < 60 ? 1 + (t - 32) % 7 : t < 62 ? t - 54 : 0) & 7))) & 7) - 1, slot;
      int it = 0;
      do {
        grp = (grp + 1) & 7;
        asm volatile("atom.relaxed.gpu.global.add.u32 %0, [%1], 1;" : "=r"(slot) : "l"(&p.sc->ticket[grp * 32]) : "memory");
        spin_guard(it);
      } while (slot >= 8);
      pairid = slot * 8 + grp;
    }
    __syncwarp();
    asm volatile("barrier.cluster.wait.aligned;" ::: "memory");
    if (tid == 320 && rank == 0) {
#pragma unroll
      for (int r = 0; r < 2; r++)
        asm volatile("st.async.weak.shared::cluster.mbarrier::complete_tx::bytes.b32 [%0], %1, [%2];"
          :: "r"(mapa(sb + SM_ROLE, r)), "r"(pairid), "r"(mapa(sb + BAR_ROLE, r)) : "memory");
    }
    __syncwarp();
    const uint32_t tag = ld_relaxed(&g_epoch) + 1;
    if (warp == 8) {
      TILE_ROLES();
      const int kvrow = (ct >> 1) * 2048 + 1536, arow = rt * 128 + rank * 64;
      const uint64_t pef = policy_evict_first();
#pragma unroll 1
      for (int pair = 0; pair < 2; pair++) {
        const int wblk = (4 * ct + 2 * pair) * 2;
        if (pair) { mbar_wait_g(sb + BAR_HF, 0); fence_async_global(); }
#pragma unroll 1
        for (int n = 0; n < 16; n++) {
          const uint32_t s = n & 3, st = sb + SM_RING + s * ST1, fb = sb + BAR_FULL1 + 8 * s;
          if (n == 2 && pair == 0) mbar_wait_g(sb + BAR_G, 0);
          mbar_wait_g(fb + (BAR_EMPTY1 - BAR_FULL1), ((n >> 2) & 1) ^ 1);
          if (elect_one()) {
            mbar_expect_tx(fb, 49152);
            tma_ld_mc(st + rank * 8192, pair ? &mH : &mX, n * 64, arow, fb);
            tma_ld3_hint(st + 16384, &mWq, n * 64, wblk, fb, pef);
          }
          __syncwarp();
        }
#pragma unroll 1
        for (int n = 0; n < 16; n++) {
          const uint32_t s = n & 3, st = sb + SM_RING + s * ST1 + rank * 8192, fb = sb + BAR_FULL1 + 8 * s;
          const int h0 = n == 0 ? 0 : n == 15 ? 14 : n + 1, h1 = n == 0 ? 1 : n == 15 ? 15 : n - 1;
          mbar_wait_g(fb + (BAR_EMPTY1 - BAR_FULL1), ((n >> 2) & 1) ^ 1);
          if (elect_one()) {
            mbar_expect_tx(fb, 32768);
            tma_ld_mc(st, n == 15 ? &mV : &mK, rank * 64, kvrow + (h0 & 7) * 64, fb);
            tma_ld_mc(st + 16384, n == 0 ? &mK : &mV, rank * 64, kvrow + (h1 & 7) * 64, fb);
            if (n == 3 && pair == 1) mbar_arrive(sb + BAR_T1);
          }
          __syncwarp();
        }
      }
      {
        uint32_t s = 0, ph = 1;
#pragma unroll 1
        for (int half = 0; half < 2; half++) {
          mbar_wait_g(sb + BAR_OF + 8 * half, 0);
          fence_async_global();
#pragma unroll 1
          for (int n = 32 * half; n < 32 * half + 32; n++) {
            const uint32_t st = sb + SM_RING + s * ST1, fb = sb + BAR_FULL1 + 8 * s;
            const int k0 = ((n & 14) * 2 + (n >> 4)) * 128 + (n & 1) * 64;
            mbar_wait_g(n == 8 ? sb + BAR_SFREE : fb + (BAR_EMPTY1 - BAR_FULL1), n == 8 ? 0 : ph ^ (s >> 2));
            if (elect_one()) {
              mbar_expect_tx(fb, 32768);
              tma_ld_mc_hint(st + rank * 8192, &mO, k0, arow, fb, pef);
              tma_ld3_hint(st + 16384, &mWo, k0, 2 * ct, fb, pef);
            }
            __syncwarp();
            if (++s == 5 || n == 3) { s = 0; ph ^= 1; }
          }
        }
        if (b < NFFN) {
#pragma unroll 1
          for (s = 0; s < 2; s++) {
            mbar_wait_g(sb + BAR_EMPTY1 + 8 * s, 0);
            if (elect_one()) {
              mbar_expect_tx(sb + BAR_FFN + 8, 32768);
              tma_ld3_hint(sb + SM_RING + s * ST1, &mWd, b * 32, s * 8, sb + BAR_FFN + 8, pef);
            }
            __syncwarp();
          }
        }
      }
    } else if (warp <= 10) {
      const int w = warp - 9;
      TILE_ROLES();
      const uint32_t st = sb + SM_STASH + w * 16384;
#pragma unroll 1
      for (int j = 0; j < 2; j++) {
        nb_sync(NB_OST + w, 160);
        if (elect_one()) {
          tma_st(&mH, (2 * ct + j) * 64, rt * 128 + w * 64, st + 4096);
          bulk_commit();
          bulk_wait_read();
          mbar_arrive(sb + BAR_HS + 16 * w + 8 * j);
          if (j) {
            bulk_wait_all();
            fence_async_global();
            fence_release_gpu();
            red_add_relaxed(&g_hflag[rt * 32], 1);
          }
        }
        __syncwarp();
      }
#pragma unroll 1
      for (int r = 0; r < 4; r++) {
        nb_sync(NB_OST + w, 160);
        if (elect_one()) {
          if (r == 3) __nanosleep(OD0 + w * OD1);
          tma_st(&mO, (4 * ct + r) * 128, rt * 128 + w * 64, st);
          if (r == 3) __nanosleep(2 * OD1);
          tma_st(&mO, (4 * ct + r) * 128 + 64, rt * 128 + w * 64, st + 8192);
          bulk_commit();
          bulk_wait_read();
          if (r < 2) {
            mbar_arrive(sb + BAR_STASH + 8 * w);
          } else if (r == 2) {
            mbar_expect_tx(sb + BAR_X + 8 * w, 16384);
            tma_ld(st, &mX, ct * 128, rt * 128 + w * 64, sb + BAR_X + 8 * w);
            tma_ld(st + 8192, &mX, ct * 128 + 64, rt * 128 + w * 64, sb + BAR_X + 8 * w);
          } else {
            mbar_arrive_cl(mapa(sb + BAR_SFREE, 0)); mbar_arrive_cl(mapa(sb + BAR_SFREE, 1));
          }
          bulk_wait_all();
          fence_async_global();
          fence_release_gpu();
          red_add_relaxed(&g_oflag[(rt * 4 + r) * 32], 1);
        }
        __syncwarp();
      }
      nb_sync(NB_OST + w, 160);
      int skip = -1;
      mbar_wait_g(sb + BAR_CAND, 0);
      const bool has_cand = (lds32(sb + SM_CAND) >> 6) == w;
      if (has_cand) {
        nb_sync(NB_WIN + w, 160);
        skip = (int)lds32(sb + SM_WROW + 4 * w) - (rt * 128 + w * 64);
      }
      if ((unsigned)skip >= 64u) {
        if (elect_one()) {
          tma_st(&mOut, ct * 128, rt * 128 + w * 64, sb + SM_OUT + w * 16384);
          tma_st(&mOut, ct * 128 + 64, rt * 128 + w * 64, sb + SM_OUT + w * 16384 + 8192);
          bulk_commit();
          bulk_wait_read();
        }
        __syncwarp();
      } else {
        uint4* dst = reinterpret_cast<uint4*>(p.out + (size_t)(rt * 128 + w * 64 + (lane >> 4)) * 1024 + ct * 128) + (lane & 15);
#pragma unroll 2
        for (int r = lane >> 4; r < 64; r += 2) {
          const uint4 v = lds128(sb + SM_OUT + w * 16384 + ((lane >> 3) & 1) * 8192 + r * 128 + (((lane ^ r) & 7) * 16));
          if (r != skip) *dst = v;
          dst += 256;
        }
      }
      if (!has_cand) nb_sync(NB_WIN + w, 160);
    } else {
      if (slab) {
        mbar_wait_g(sb + BAR_RED, 0);
        float v = 0.f;
#pragma unroll
        for (int w = 0; w < 8; w++) v += lds_f32(sb + SM_RED + w * 128 + lane * 4);
        v += __shfl_xor_sync(0xffffffffu, v, 16);
        v = mod_value(v, b0 >> 6);
        publish_record(&g_rec[tag & 1][0][ridx], pack2(v, __shfl_down_sync(0xffffffffu, v, 1)), 2 * (lane & 1), b0 >> 6, lane < 8);
        if (lane == 0) TS(1);
      }
      mbar_wait_g(sb + BAR_G, 0);
#pragma unroll 1
      for (int i = 1; i < 4; i++) {
        const uint4* mp = &g_rec[tag & 1][(b0 >> 1) & (NREP - 1)][32 * i + lane];
        uint4 v0, v1; int it = 0;
        while (true) {
          v0 = ld_pkt16(mp); v1 = ld_pkt16(mp + 128);
          if (v0.x != 0 && v1.x != 0) break;
          spin_guard(it); __nanosleep(PLD);
        }
        put_record(sb, 32 * i + lane, v0);
        put_record(sb, 128 + 32 * i + lane, v1);
        mbar_arrive(sb + BAR_TAB - 8 + 8 * i);
        if (lane == 0) {
          TS(3 + i + (i > 2));
          if (i == 1) l2_prefetch(((b0 & 64) ? p.vc : p.kc) + (size_t)(((b0 >> 4) & 3) * 2048 + 1536) * 128 + (b0 & 15) * 4096, 8192);
        }
        __syncwarp();
      }
      TILE_ROLES();
      if (lane == 0) {
        int it = 0;
        do { __nanosleep(500); spin_guard(it); } while (ld_relaxed(&g_hflag[rt * 32]) != tag * 16u);
        fence_acquire_gpu();
        mbar_arrive(sb + BAR_HF);
      }
      __syncwarp();
      {
        uint2 v; int it = 0;
        do { __nanosleep(1000); v = ld_pkt8(&g_vdone[(lane & 3) * 16]); spin_guard(it); }
        while (!(v.y == tag));
        __syncwarp();
        fence_acquire_gpu();
        if (lane == 1 || lane == 2) sts32(sb + SM_SCAL + (2 - lane) * 4, v.x);
      }
#pragma unroll 1
      for (int i = 0; i < 2; i++) {
        const int q = i * 32 + lane, pi = ct * 64 + q;
        const uint32_t vga = g_mod[2 * 512 + pi].x, vsb = g_mod[3 * 512 + pi].x, vcb = g_mod[4 * 512 + pi].x, vgb = g_mod[5 * 512 + pi].x;
        const uint32_t wr = reinterpret_cast<const uint32_t*>(p.w_r)[pi];
        const uint32_t c1 = hadd2(vcb, ONE2);
        const float al = lo2f(c1) * lo2f(wr), ah = hi2f(c1) * hi2f(wr);
        const uint32_t o8 = (q & 3) * 8 + ((q >> 2) & 1) * 4;
        sts32(sb + SM_GA + (q >> 3) * 32 + o8, vga);
        sts128(sb + SM_REC + q * 16, c1, vsb, vgb, 0);
        const uint32_t ahi = pack2(al, ah), alo = pack2(al - lo2f(ahi), ah - hi2f(ahi));
        const uint32_t ba = sb + SM_B1 + (q >> 3) * 128 + o8;
        sts32(ba, ONE2); sts32(ba + 32, ahi); sts32(ba + 64, alo); sts32(ba + 96, 0);
      }
      if (lane == 0) TS(28);
      if (lane == 0) {
        tma_prefetch_desc(&mWo); tma_prefetch_desc(&mOut); tma_prefetch_desc(&mWd); tma_prefetch_desc(&mWg); tma_prefetch_desc(&mWu);
#pragma unroll 1
        for (int r = 0; r < 4; r++) {
          int it = 0;
          do { __nanosleep(200); spin_guard(it); } while (ld_relaxed(&g_oflag[(rt * 4 + r) * 32]) != tag * 16u);
          if (r & 1) { fence_acquire_gpu(); mbar_arrive(sb + BAR_OF + 8 * (r >> 1)); }
          if (r == 1 && b < NFFN) {
            const uint64_t pef = policy_evict_first();
            mbar_wait_g(sb + BAR_T1, 0);
#pragma unroll 1
            for (int i = 0; i < 4; i++) {
              mbar_expect_tx(sb + BAR_FFN, 16384);
              tma_ld_hint(sb + SM_RING + i * ST1 + 32768, &mWg, b * 32, i * 256, sb + BAR_FFN, pef);
              __nanosleep(GATED);
            }
          }
        }
      }
      __syncwarp();
      if (b < NFFN) {
        mbar_wait_g(sb + BAR_TFREE, 0);
        const uint64_t pef = policy_evict_first();
#pragma unroll 1
        for (int i = 0; i < 5; i++) {
          if (i > 0 && lane == 0) {
            mbar_expect_tx(sb + BAR_FFN, 16384);
            tma_ld_hint(sb + SM_RING + (i - 1) * ST1 + 32768, &mWu, b * 32, (i - 1) * 256, sb + BAR_FFN, pef);
          }
          if (i < 4) {
#pragma unroll 1
            for (int j = 0; j < 8; j++) {
              asm volatile("prefetch.global.L2 [%0];" :: "l"(p.wu + (size_t)(i * 256 + j * 32 + lane) * 3584 + b * 32) : "memory");
              __nanosleep(UPD);
            }
            __nanosleep(500);
          }
        }
      }
      if (lane == 0) TS(29);
#pragma unroll 1
      for (int i = lane; i < 128; i += 32) st_pkt16(&g_stats[b * 128 + i], 0, 0, 0, 0);
      st_pkt16(&g_cand[b * 32 + lane], 0, 0, 0, 0);
      if (lane < 8) st_pkt16(&g_entry[(ct * 16 + rt) * 8 + lane], 0, 0, 0, 0);
#pragma unroll 1
      for (int i = lane; i < (b < NFFN ? 512 : 0); i += 32) st_pkt16(&g_ypart[((i >> 2) * NFFN + b) * 4 + (i & 3)], 0, 0, 0, 0);
      mbar_arrive(sb + BAR_VEC);
      uint4* const cp = &g_cand[b * 32 + lane];
      uint4* const ep = &g_entry[(ct * 16 + rt) * 8];
      nb_sync(NB_AMAX, 288);
      const uint4 e = lds128(sb + SM_AMAX + (lane & 7) * 16);
      const int tmax = __reduce_max_sync(0xffffffffu, (int)e.x);
      const int wl = __ffs(__ballot_sync(0xffffffffu, (int)e.x == tmax)) - 1;
      const uint32_t row = __shfl_sync(0xffffffffu, e.y, wl);
      const uint32_t xa = sb + SM_X2 + (row >> 6) * 16384 + (lane >> 4) * 8192 + (row & 63) * 128 + (lane & 3) * 4
                        + ((((lane >> 1) & 6) ^ (row & 7)) * 16);
      const uint32_t v0 = lds32(xa), v1 = lds32(xa ^ 16);
      if (lane == wl) st_pkt16(ep, e.w, rt * 128 + row, e.z, tag);
      st_pkt16(cp, v0, v1, tag, 0);
      if (lane == 0) { sts32(sb + SM_CAND, row); mbar_arrive(sb + BAR_CAND); }
      if (lane == 0) TS(15);
    }
  } else {
    const int warp = tid >> 5;
    const int wg = warp >> 2, wq = warp & 3;
    const int g = lane >> 2, t = lane & 3;
    uint32_t tag;
    uint32_t ln[4];
    float acc[128];
    uint32_t bf[16];
    auto gemv = [&]() {
          asm volatile("cp.async.wait_all;" ::: "memory");
          float d0[4] = {0.f, 0.f, 0.f, 0.f}, d1[4] = {0.f, 0.f, 0.f, 0.f};
#pragma unroll
          for (int i = 0; i < 8; i++) {
            const uint4 wv = lds128(sb + SM_WSLAB + tid * 16 + i * 4096);
            const uint32_t a[4] = {wv.x, wv.y, wv.z, wv.w};
            mma16816((i & 1) ? d1 : d0, a, bf[2 * i], bf[2 * i + 1]);
          }
#pragma unroll
          for (int i = 0; i < 4; i++) { d0[i] += d1[i]; d0[i] += __shfl_xor_sync(0xffffffffu, d0[i], 6); }
          const uint32_t dst = mapa(sb + SM_MISC, t & 1) - SM_MISC;
          if (!(lane & 6)) st_async_f32x4(dst + SM_RED + warp * 128 + rank * 64 + g * 8, d0, dst + BAR_RED);
          TH(4);
    };
    {
      asm volatile("barrier.cluster.arrive.relaxed.aligned;" ::: "memory");
      if (lane == 0) st_pkt16(&g_lnst[8 * b0 + warp], 0, 0, 0, 0);
      TH(1);
      asm volatile("setmaxnreg.inc.sync.aligned.u32 240;");
      TH(2);
#pragma unroll
      for (int i = 0; i < 8; i++) {
        const float sv = silu_f((g & 4) ? hi2f(cw[i]) : lo2f(cw[i]));
        const uint32_t sp = (g & 1) ? pack2(0.f, sv) : pack2(sv, 0.f);
        bf[2 * i] = (g & 2) ? 0 : sp; bf[2 * i + 1] = (g & 2) ? sp : 0;
      }
      asm volatile("barrier.cluster.wait.aligned;" ::: "memory");
#pragma unroll
      for (int i = 0; i < 128; i++) acc[i] = 0.f;
      reg_fence<128>(acc);
      tag = __shfl_sync(0xffffffffu, epoch, 0) + 1;
      if (slab && late) { while ((uint32_t)clock() - c0 < WL) {} load_slab(); }
      TH(3);
      if (slab && !late) gemv();
      {
        {
          mbar_wait(sb + BAR_XH, 0);
          TH(5);
          float ds[4] = {0.f, 0.f, 0.f, 0.f}, dq[4][4];
#pragma unroll
          for (int i = 0; i < 4; i++) { dq[i][0] = dq[i][1] = dq[i][2] = dq[i][3] = 0.f; }
#pragma unroll
          for (int i = 0; i < 8; i++) {
            uint32_t a[4];
            ldsm4(sb + SM_XROW + wg * ST1 + wq * 4096 + ((lane >> 3) & 1) * 2048 + i * 256 + (lane >> 4) * 128 + (lane & 7) * 16, a);
            mma16816(ds, a, ONE2, ONE2);
            mma1688(dq[0], a[0], a[1], a[0]); mma1688(dq[1], a[0], a[1], a[1]);
            mma1688(dq[2], a[2], a[3], a[2]); mma1688(dq[3], a[2], a[3], a[3]);
          }
          const bool dg = t == (g >> 1);
          const float q0 = dg ? ((g & 1) ? dq[0][1] + dq[2][1] : dq[0][0] + dq[2][0]) : 0.f;
          const float q1 = dg ? ((g & 1) ? dq[1][3] + dq[3][3] : dq[1][2] + dq[3][2]) : 0.f;
          float q = ((lane & 1) ? q1 : q0) + __shfl_xor_sync(0xffffffffu, (lane & 1) ? q0 : q1, 1);
          float sm = (lane & 1) ? ds[2] : ds[0];
          q += __shfl_xor_sync(0xffffffffu, q, 2);
#pragma unroll
          for (int o = 4; o <= 16; o <<= 1) { q += __shfl_xor_sync(0xffffffffu, q, o); sm += __shfl_xor_sync(0xffffffffu, sm, o); }
          const float mean = sm * (1.f / 1024.f);
          const float rd = rcp_f(rbf(sqrt_f(rbf(rbf(fmaxf(fmaf(-mean, mean, q * (1.f / 1024.f)), 0.f)) + 1e-5f))));
          const float mean1 = __shfl_sync(0xffffffffu, mean, 1), rd1 = __shfl_sync(0xffffffffu, rd, 1);
          const uint32_t rh = pack2(rd, rd1);
          if (lane == 0) st_pkt16(&g_lnst[8 * b0 + warp], pack2(-rbf(mean) * lo2f(rh), -rbf(mean1) * hi2f(rh)), rh, 0, tag);
          TH(6);
          if (tid == 0) TS(2);
        }
      }
    }
    if (slab && late) gemv();
    TILE_ROLES();
    const uint32_t xa0 = sb + SM_RING + (warp * 16 + (lane & 15)) * 128 + (((lane >> 4) ^ (lane & 7)) * 16);
    uint32_t V[16];
    {
      const uint4* mp = &g_rec[tag & 1][(b0 >> 1) & (NREP - 1)][128 * wg + lane];
      const uint4* lp = &g_lnst[(8 * rt + warp) * 8 + (g >> 1)];
      mbar_wait(sb + BAR_FULL1, 0);
#pragma unroll
      for (int kk = 0; kk < 4; kk++) ldsm4(xa0 ^ (kk * 32), V + 4 * kk);
      uint4 v0 = make_uint4(1, 0, 0, 0), l0, l1;
      int it = 0;
      do { if (wq == 0) v0 = ld_pkt16(mp);
           l0 = ld_pkt16(lp); l1 = ld_pkt16(lp + 4); spin_guard(it); }
        while (!(__all_sync(0xffffffffu, v0.x != 0 && l0.w == tag && l1.w == tag)));
      TH(7);
      if (wq == 0) put_record(sb, 128 * wg + lane, v0);
      const uint32_t sel = (g & 1) ? 0x3232 : 0x1010;
      ln[0] = __byte_perm(l0.x, 0, sel); ln[1] = __byte_perm(l0.y, 0, sel);
      ln[2] = __byte_perm(l1.x, 0, sel); ln[3] = __byte_perm(l1.y, 0, sel);
      __syncwarp();
      if (lane < 2) mbar_arrive_cl(mapa(sb + BAR_G, lane));
      nb_sync(NB_CONS, 256);
      if (tid == 0) TS(3);
      TH(13);
    }

    const uint32_t rel = mapa(sb + SM_MISC, lane & 1) - SM_MISC;
    const uint32_t stsm_addr = sb + SM_STASH + wg * 16384 + (wq * 16 + (lane & 15)) * 128 + (((lane >> 4) ^ (lane & 7)) * 16);

    uint32_t ph = 0;
    uint32_t X[32];
    {
      const uint32_t tab0 = sb + SM_STASH + wg * 16384 + t * 16;
      const uint64_t db0 = mk_desc(sb + SM_RING + 16384, 8192);
      uint32_t A[2][16];
      uint32_t xa[4];
#pragma unroll
      for (int kk = 0; kk < 4; kk++) xa[kk] = xa0 ^ (kk * 32);
      uint32_t tab = tab0;
      reg_fence<4>(xa);
      asm volatile("{\n.reg .pred p;\nsetp.eq.u32 p, %4, 0;\n@p ld.shared.v4.u32 {%0,%1,%2,%3}, [%5];\n}"
        : "+r"(ln[2]), "+r"(ln[0]), "+r"(ln[3]), "+r"(ln[1]) : "r"(tag), "r"(sb));
      int hs = 2 * ct;
      uint4 R[4];
#pragma unroll
      for (int kk = 0; kk < 4; kk++) R[kk] = lds128(tab + (kk >> 1) * 2048 + (kk & 1) * 64);
#pragma unroll 1
      for (int k4 = 0; k4 < 4; k4++) {
#pragma unroll
        for (int s = 0; s < 4; s++) {
          uint32_t* a = A[s & 1];
          const int sn = (s + 1) & 3;
          const uint32_t pn = (k4 + (s == 3)) & 1;
          modulate_frags(a, V, R, ln);
          if (hs == (s & 2)) {
            if (s & 1) mbar_wait(sb + BAR_HS + 16 * wg, 0);
#pragma unroll
            for (int kk = 0; kk < 4; kk++) stsm4((stsm_addr + 4096) ^ (kk * 32), a[4 * kk], a[4 * kk + 1], a[4 * kk + 2], a[4 * kk + 3]);
            fence_async_smem();
            nb_arrive(NB_OST + wg, 160);
          }
          if (s == 0 && k4 == 0) TH(8);
          if (s == 0 && k4 == 0 && tid == 0) { TS(6); TSC(61); }
          wg_fence();
#pragma unroll
          for (int kk = 0; kk < 4; kk++) wgmma_rs256<1>(acc, a + 4 * kk, db0 + s * (ST1 >> 4) + kk * 128);
          wg_commit();
          if (s == 3 && k4 < 3) mbar_wait(sb + BAR_TAB + 8 * k4, 0);
#pragma unroll
          for (int kk = 0; kk < 4; kk++) R[kk] = lds128(tab + (s + 1) * 128 + (kk >> 1) * 2048 + (kk & 1) * 64);
          wg_wait<1>();
          if (k4 == 0) TH(9 + s);
          reg_fence<16>(A[(s & 1) ^ 1]);
          if ((tid & 127) < 2 && (s | k4)) mbar_arrive_cl(rel + BAR_EMPTY1 + 8 * ((s + 3) & 3));
          if (s < 3 || k4 < 3) {
            mbar_wait(sb + BAR_FULL1 + 8 * sn, pn);
#pragma unroll
            for (int kk = 0; kk < 4; kk++) ldsm4(xa[kk] + sn * ST1, V + 4 * kk);
          }
        }
        tab += 512; hs -= 4;
      }
      mbar_wait(sb + BAR_HS + 16 * wg + 8, 0);
      wg_wait<0>();
      reg_fence<128>(acc);
    }
#pragma unroll 1
    for (int pair = 0; pair < 2; pair++) {
      uint32_t Q[32];
      TR(0);
      {
        if ((tid & 127) < 2) mbar_arrive_cl(rel + BAR_EMPTY1 + 8 * 3);
        if (pair == 1) mbar_wait(sb + BAR_STASH + 8 * wg, 1);
#pragma unroll
        for (int i = 0; i < 32; i++) Q[i] = pack2(acc[2 * i], acc[2 * i + 1]);
        const uint32_t qs = sb + SM_STASH + wg * 16384 + wq * 2048 + lane * 16;
#pragma unroll
        for (int i = 0; i < 8; i++)
          sts128(qs + (i & 3) * 512 + (i >> 2) * 8192, pack2(acc[64 + 8 * i], acc[65 + 8 * i]), pack2(acc[66 + 8 * i], acc[67 + 8 * i]),
                 pack2(acc[68 + 8 * i], acc[69 + 8 * i]), pack2(acc[70 + 8 * i], acc[71 + 8 * i]));
      }
      if (tid == 0) TS(8 + pair * 2);
      TR(1);
      float O[64], SL[32], SH[32];
      uint32_t PL[16], PH[16];
      SoftmaxState z;
      const uint64_t d0 = mk_desc(sb + SM_RING, 8192);
      {
        mbar_wait(sb + BAR_FULL1, ph);
        wg_fence();
        issue_qk(SL, Q, d0);
        wg_commit();
        issue_qk(SH, Q, d0 + 1024);
        wg_commit();
#pragma unroll
        for (int i = 0; i < 64; i++) O[i] = 0.f;
        reg_fence<64>(O);
        wg_wait<1>();
        reg_fence<32>(SL);
        softmax_start(z);
        softmax_half(SL, PL, O, z, true, tag);
        wg_wait<0>();
        reg_fence<32>(SH);
        if ((tid & 127) < 2) mbar_arrive_cl(rel + BAR_EMPTY1);
      }
      float lp0 = 0.f, lp1 = 0.f;
      uint32_t dB = (uint32_t)d0 + 1 * (ST1 >> 4), dA = (uint32_t)d0 + 2 * (ST1 >> 4);
      const uint32_t dBx = dB ^ ((uint32_t)d0 + 3 * (ST1 >> 4)), dAx = dA ^ (uint32_t)d0;
      uint32_t so = 0;
      bool ready = false;
#pragma unroll 1
      for (int i = 0; i < 7; i++) {
        TA(0);
        TR(2 + i);
        if (!ready) mbar_wait(sb + BAR_FULL1 + 8 + so, ph);
        TA(1);
        TA(2);
        wg_fence();
        issue_qk(SL, Q, (d0 & 0xffffffff00000000ull) | dB);
        if (i == 4) {
          __syncwarp();
          stage_o(O, lp0, lp1, stsm_addr);
        }
        wg_fence();
        issue_pv(O, PL, ((d0 & 0xffffffff00000000ull) | dB) + 1024, i != 4);
        wg_commit();
        if (i == 4) {
          fence_async_smem();
          nb_arrive(NB_OST + wg, 160);
        }
        TA(3);
        ph ^= i & 1;
        ready = mbar_test(sb + BAR_FULL1 + 16 - so, ph);
        softmax_half(SH, PH, O, z, false, tag);
        TA(4);
        wg_wait<0>();
        TA(5);
        reg_fence<32>(SL); reg_fence<16>(PL);
        if ((tid & 127) < 2) mbar_arrive_cl(rel + BAR_EMPTY1 + 8 + so);
        if (!ready) mbar_wait(sb + BAR_FULL1 + 16 - so, ph);
        TA(6);
        wg_fence();
        issue_qk(SH, Q, (d0 & 0xffffffff00000000ull) | dA);
        wg_commit();
        issue_pv(O, PH, ((d0 & 0xffffffff00000000ull) | dA) + 1024, 1);
        wg_commit();
        if (i == 2) {
          wg_wait<1>();
          reg_fence<32>(Q);
          const uint32_t qs = sb + SM_STASH + wg * 16384 + wq * 2048 + lane * 16;
#pragma unroll
          for (int j = 0; j < 8; j++) { const uint4 v = lds128(qs + (j & 3) * 512 + (j >> 2) * 8192); Q[4 * j] = v.x; Q[4 * j + 1] = v.y; Q[4 * j + 2] = v.z; Q[4 * j + 3] = v.w; }
        }
        TA(10);
        if (i == 3) { lp0 = z.l0; lp1 = z.l1; row_rcp(lp0, lp1); softmax_start(z); }
        TA(7);
        so ^= 16; dB ^= dBx; dA ^= dAx;
        ready = mbar_test(sb + BAR_FULL1 + 8 + so, ph);
        softmax_half(SL, PL, O, z, i == 3, tag);
        TA(8);
        wg_wait<0>();
        TA(9);
        reg_fence<32>(SH); reg_fence<16>(PH); reg_fence<64>(O); reg_fence<32>(Q);
        if ((tid & 127) < 2) mbar_arrive_cl(rel + BAR_EMPTY1 + so);
      }
      TAFLUSH();
      TR(9);
      {
        if (!ready) mbar_wait(sb + BAR_FULL1 + 8 * 3, ph);
        ph ^= 1;
        const uint64_t dv = d0 + 3 * (ST1 >> 4);
        wg_fence();
        issue_pv(O, PL, dv, 1);
        wg_commit();
        bb_fence(tag);
        softmax_half(SH, PH, O, z, false, tag);
        wg_fence();
        issue_pv(O, PH, dv + 1024, 1);
        wg_commit();
        TR(10);
        row_rcp(z.l0, z.l1);
        mbar_wait(sb + (pair ? BAR_X : BAR_STASH) + 8 * wg, 0);
#pragma unroll
        for (int kk = 0; kk < 8; kk++) ldsm4((stsm_addr + (kk >> 2) * 8192) ^ ((kk & 3) * 32), X + 4 * kk);
        reg_fence<32>(X);
        __syncwarp();
        wg_wait<0>();
        reg_fence<64>(O);
        TR(11);
        if ((tid & 127) < 2) mbar_arrive_cl(rel + BAR_EMPTY1 + 8 * 3);
        stage_o(O, z.l0, z.l1, stsm_addr);
        fence_async_smem();
        nb_arrive(NB_OST + wg, 160);
      }
      TR(12);
      if (tid == 0) { TS(9 + pair * 2); TSC(62); }
      if (pair == 1) break;
      {
        mbar_wait(sb + BAR_FULL1, ph);
        const uint64_t da = mk_desc(sb + SM_RING + wg * 8192, 16), db = mk_desc(sb + SM_RING + 16384, 8192);
        wg_fence();
        wgmma_ss256_z<1>(acc, da, db);
#pragma unroll
        for (int kk = 1; kk < 4; kk++) wgmma_ss256<1>(acc, da + kk * 2, db + kk * 128, 1);
        wg_commit();
      }
#pragma unroll 1
      for (int kt = 1; kt < 16; kt++) {
        const uint32_t s = kt & 3;
        if (s == 0) ph ^= 1;
        mbar_wait(sb + BAR_FULL1 + 8 * s, ph);
        const uint32_t st = sb + SM_RING + s * ST1;
        const uint64_t da = mk_desc(st + wg * 8192, 16), db = mk_desc(st + 16384, 8192);
        wg_fence();
#pragma unroll
        for (int kk = 0; kk < 4; kk++) wgmma_ss256<1>(acc, da + kk * 2, db + kk * 128, 1);
        wg_commit();
        wg_wait<1>();
        if ((tid & 127) < 2) mbar_arrive_cl(rel + BAR_EMPTY1 + 8 * ((s + 3) & 3));
      }
      ph ^= 1;
      wg_wait<0>();
      reg_fence<128>(acc);
      TR(13);
    }

    uint4 WG[16], WU[16];
    const int fp = 64 * warp + 8 * g + t;
    uint32_t fsb0, fsb1, fcb0, fcb1, fgb0, fgb1;
    const uint32_t gu_base = sb + SM_RING + (warp >> 1) * ST1 + 32768 + (warp & 1) * 8192;
    const uint32_t gu_addr = gu_base + t * 128 + (g & 1) * 64 + ((g >> 1) ^ t) * 16;
    {
      const uint64_t da0 = mk_desc(sb + SM_RING + __shfl_sync(0xffffffffu, wg, 0) * 8192, 16), db0 = mk_desc(sb + SM_RING + 16384, 8192);
#pragma unroll
      for (int n = 0; n < 4 + 5 * X_PEEL; n++) {
        const int s = n < 4 ? n : (n - 4) % 5;
        mbar_wait(sb + BAR_FULL1 + 8 * s, n < 4 ? 0 : ((n - 4) / 5 + (s < 4)) & 1);
        if (n < 4) TSX(40 + wg * 6 + n);
        const uint64_t da = da0 + s * (ST1 >> 4), db = db0 + s * (ST1 >> 4);
        wg_fence();
        if (n == 0) wgmma_ss128_z<1>(acc, da, db); else wgmma_ss128<1>(acc, da, db, 1);
#pragma unroll
        for (int kk = 1; kk < 4; kk++) wgmma_ss128<1>(acc, da + kk * 2, db + kk * 128, 1);
        wg_commit();
        if (n == 1) {
          mbar_wait(sb + BAR_OF, 0);
          const uint2* mp = &g_mod[3 * 512 + fp];
          fsb0 = ld_pkt8(mp).x; fsb1 = ld_pkt8(mp + 4).x; fcb0 = ld_pkt8(mp + 512).x; fcb1 = ld_pkt8(mp + 516).x;
          fgb0 = ld_pkt8(mp + 1024).x; fgb1 = ld_pkt8(mp + 1028).x;
        }
        if (n == 0 && b < NFFN) mbar_wait(sb + BAR_FFN, 0);
        {
          constexpr int NT = 4 + 5 * X_PEEL, F0 = NT > 16 ? NT - 16 : 0;
#pragma unroll
          for (int i = 0; i < 16; i++) if (F0 + i * (NT - F0) / 16 == n) WG[i] = lds128(gu_addr + i * 512);
        }
        if (n > 0) {
          wg_wait<1>();
          if ((tid & 127) < 2) mbar_arrive_cl(rel + BAR_EMPTY1 + 8 * (n == 4 ? 3 : s ? s - 1 : 4));
        }
      }
      TSX(44 + wg * 6);
      {
        uint32_t dep = 0;
#pragma unroll
        for (int i = 0; i < 16; i++) dep ^= WG[i].x;
        if (__shfl_sync(0xffffffffu, tag, dep & 31) == tag && lane == 2) mbar_arrive(sb + BAR_TFREE);
      }
#pragma unroll 1
      for (int r = X_PEEL; r < 12; r++) {
#pragma unroll
        for (int s = 0; s < 5; s++) {
          mbar_wait(sb + BAR_FULL1 + 8 * s, (r + (s < 4)) & 1);
          const uint64_t da = da0 + s * (ST1 >> 4), db = db0 + s * (ST1 >> 4);
          wg_fence();
#pragma unroll
          for (int kk = 0; kk < 4; kk++) wgmma_ss128<1>(acc, da + kk * 2, db + kk * 128, 1);
          wg_commit();
          wg_wait<1>();
          if ((tid & 127) < 2) mbar_arrive_cl(rel + BAR_EMPTY1 + 8 * (s ? s - 1 : (r == 0 ? 3 : 4)));
        }
      }
    }
    mbar_wait(sb + BAR_VEC, 0);
    const int lrow = warp * 16 + g;
    uint2 ga[8], b1[8];
#pragma unroll
    for (int kk = 0; kk < 8; kk++) { ga[kk] = lds64(sb + SM_GA + kk * 32 + t * 8); b1[kk] = lds64(sb + SM_B1 + min(g, 3) * 32 + t * 8 + kk * 128); }
    uint4* const stp = &g_stats[b * 128 + lrow + 8 * t];
    bb_fence(tag);
    wg_wait<0>();
    reg_fence<64>(acc);
    if (tid == 0) { TS(12); TSC(63); }

    TT(0);
    {
      float d1[4] = {0.f, 0.f, 0.f, 0.f}, d2[4] = {0.f, 0.f, 0.f, 0.f}, d3[4] = {0.f, 0.f, 0.f, 0.f};
      float d4[4] = {0.f, 0.f, 0.f, 0.f}, d5[4] = {0.f, 0.f, 0.f, 0.f};
#pragma unroll
      for (int kk = 0; kk < 8; kk++) {
        uint32_t* x = X + 4 * kk;
        x[0] = hfma2(ga[kk].x, pack2(acc[8 * kk + 0], acc[8 * kk + 1]), x[0]);
        x[1] = hfma2(ga[kk].x, pack2(acc[8 * kk + 2], acc[8 * kk + 3]), x[1]);
        x[2] = hfma2(ga[kk].y, pack2(acc[8 * kk + 4], acc[8 * kk + 5]), x[2]);
        x[3] = hfma2(ga[kk].y, pack2(acc[8 * kk + 6], acc[8 * kk + 7]), x[3]);
        mma16816(d1, x, b1[kk].x, b1[kk].y);
        mma1688(d2, x[0], x[1], x[0]); mma1688(d3, x[0], x[1], x[1]);
        mma1688(d4, x[2], x[3], x[2]); mma1688(d5, x[2], x[3], x[3]);
      }
      const int qb = lane & 28;
      const float q0 = __shfl_sync(0xffffffffu, (g & 1) ? d2[1] + d4[1] : d2[0] + d4[0], qb | (g >> 1));
      const float q1 = __shfl_sync(0xffffffffu, (g & 1) ? d3[3] + d5[3] : d3[2] + d5[2], qb | (g >> 1));
      const float e0 = __shfl_xor_sync(0xffffffffu, t ? d1[0] : d1[3], 1);
      const float e1 = __shfl_sync(0xffffffffu, d1[2], qb);
      if (t < 2) st_pkt16(stp, __float_as_uint(t ? e1 : d1[0]), __float_as_uint(t ? q1 : q0),
                          __float_as_uint((t ? d1[2] : d1[1]) + e0), tag);
    }
    TSY(13);
    TT(1);
    float mb, rd, den, br;
    {
      const uint4* sp = &g_stats[(rt * 8 + 4 * (t & 1)) * 128 + lrow + 4 * (t & 2)];
      mbar_wait(sb + BAR_EMPTY1 + 8 * 3, 0);
#pragma unroll
      for (int kk = 0; kk < 8; kk++) stsm4((stsm_addr - SM_STASH + SM_X2 + (kk >> 2) * 8192) ^ ((kk & 3) * 32), X[4 * kk], X[4 * kk + 1], X[4 * kk + 2], X[4 * kk + 3]);
      if (b < NFFN) mbar_wait(sb + BAR_FFN, 1);
#pragma unroll
      for (int i = 0; i < WU1; i++) WU[i] = lds128(gu_addr + i * 512);
      bb_fence(tag);
      TT(2);
      uint4 v0, v1, v2, v3;
      int it = 0;
      do { v0 = ld_pkt16(sp); v1 = ld_pkt16(sp + 128); v2 = ld_pkt16(sp + 256); v3 = ld_pkt16(sp + 384); spin_guard(it); }
        while (!(__all_sync(0xffffffffu, v0.w == tag && v1.w == tag && v2.w == tag && v3.w == tag)));
      TT(3);
      float sm = (__uint_as_float(v0.x) + __uint_as_float(v1.x)) + (__uint_as_float(v2.x) + __uint_as_float(v3.x));
      float sq = (__uint_as_float(v0.y) + __uint_as_float(v1.y)) + (__uint_as_float(v2.y) + __uint_as_float(v3.y));
      float dt = (__uint_as_float(v0.z) + __uint_as_float(v1.z)) + (__uint_as_float(v2.z) + __uint_as_float(v3.z));
      sm += __shfl_xor_sync(0xffffffffu, sm, 1); sq += __shfl_xor_sync(0xffffffffu, sq, 1); dt += __shfl_xor_sync(0xffffffffu, dt, 1);
      const uint2 scal = lds64(sb + SM_SCAL);
      const float mu = sm * (1.f / 1024.f);
      mb = rbf(mu);
      den = rbf(sqrt_f(rbf(rbf(fmaxf(fmaf(-mu, mu, sq * (1.f / 1024.f)), 0.f)) + 1e-5f)));
      rd = rcp_f(den);
      br = fmaf(fmaf(-mb, __uint_as_float(scal.x), dt), rd, __uint_as_float(scal.y));
    }
    TSY(14);
    TT(4);
    {
      const int rb = __float_as_int(br);
      const int key = rb ^ ((rb >> 31) & 0x7fffffff);
      const int wmax = __reduce_max_sync(0xffffffffu, key);
      if (lane == __ffs(__ballot_sync(0xffffffffu, key == wmax)) - 1)
        sts128(sb + SM_AMAX + warp * 16, (uint32_t)key, lrow + 4 * (t & 2), pack2(mb, den), (uint32_t)rb);
      __syncwarp();
      nb_arrive(NB_AMAX, 288);
    }
    TT(5);
    const uint4* ep = &g_entry[(warp * 16 + (lane & 15)) * 8];
    uint4 ent = ld_pkt16(ep);
    bb_fence(tag);
    {
      const float rh = rbf(rd);
      const uint32_t u = pack2(mb, rh), w = pack2(rd - rh, 0.f);
      const int qb = lane & 28;
      const uint32_t u0 = __shfl_sync(0xffffffffu, u, qb), u1 = __shfl_sync(0xffffffffu, u, qb | 2);
      const uint32_t w0 = __shfl_sync(0xffffffffu, w, qb), w1 = __shfl_sync(0xffffffffu, w, qb | 2);
      const uint32_t m0 = __byte_perm(u0, 0, 0x1010), h0 = __byte_perm(u0, 0, 0x3232), l0 = __byte_perm(w0, 0, 0x1010);
      const uint32_t m1 = __byte_perm(u1, 0, 0x1010), h1 = __byte_perm(u1, 0, 0x3232), l1 = __byte_perm(w1, 0, 0x1010);
#pragma unroll
      for (int j = 0; j < 16; j++) {
        const uint4 rec = lds128(sb + SM_REC + (4 * j + t) * 16);
        const uint32_t e0 = hsub2(X[2 * j], m0), e1 = hsub2(X[2 * j + 1], m1);
        X[2 * j] = hfma2(rec.z, hfma2(hfma2(e0, h0, hmul2(e0, l0)), rec.x, rec.y), X[2 * j]);
        X[2 * j + 1] = hfma2(rec.z, hfma2(hfma2(e1, h1, hmul2(e1, l1)), rec.x, rec.y), X[2 * j + 1]);
      }
#pragma unroll
      for (int kk = 0; kk < 8; kk++) stsm4((stsm_addr - SM_STASH + SM_OUT + (kk >> 2) * 8192) ^ ((kk & 3) * 32), X[4 * kk], X[4 * kk + 1], X[4 * kk + 2], X[4 * kk + 3]);
    }
    TSY(16);
    TT(6);
    int wrow;
    uint32_t xs0, xs1, hs0, hs1;
    uint32_t WD[64];
    const uint32_t wd_addr = sb + SM_RING + wg * ST1 + wq * 8192 + ((lane & 7) + ((lane >> 4) << 3)) * 128 + ((((lane >> 3) & 1) ^ (lane & 7)) * 16);
    {
      auto leader = [&]() {
        const int key = ent.w == tag ? (int)ent.x ^ (((int)ent.x >> 31) & 0x7fffffff) : (int)0x80000000;
        const int gmax = __reduce_max_sync(0xffffffffu, key);
        return __ffs(__ballot_sync(0xffffffffu, key == gmax)) - 1;
      };
      int wt = leader(), it = 0;
      TT(7);
      fence_async_smem();
      nb_arrive(NB_OST + wg, 160);
      TT(8);
      uint4 v = ld_pkt16(&g_cand[(wt * 8 + warp) * 32 + lane]);
      if (ent.w != tag) ent = ld_pkt16(ep);
#pragma unroll
      for (int i = WU1; i < 16; i++) WU[i] = lds128(gu_addr + i * 512);
      if (b < NFFN) mbar_wait(sb + BAR_FFN + 8, 0);
#pragma unroll
      for (int mt = 0; mt < 8; mt++)
#pragma unroll
        for (int s = 0; s < 2; s++) ldsm4t((wd_addr + (mt >> 2) * 4096 + s * 2048) ^ ((mt & 3) * 32), WD + (mt * 2 + s) * 4);
      TT(9);
      while (true) {
        const int have = wt;
        wt = leader();
        if (__all_sync(0xffffffffu, ent.w == tag && have == wt && v.z == tag)) break;
        v = ld_pkt16(&g_cand[(wt * 8 + warp) * 32 + lane]);
        if (ent.w != tag) ent = ld_pkt16(ep);
        spin_guard(it);
      }
      TT(10);
      ent.x = __shfl_sync(0xffffffffu, ent.x, wt); wrow = __shfl_sync(0xffffffffu, ent.y, wt); ent.z = __shfl_sync(0xffffffffu, ent.z, wt);
      xs0 = v.x; xs1 = v.y;
      const uint32_t mm = __byte_perm(ent.z, 0, 0x1010);
      const float rs = rcp_f(hi2f(ent.z));
      const uint32_t e0 = hsub2(xs0, mm), e1 = hsub2(xs1, mm);
      hs0 = hfma2(pack2(lo2f(e0) * rs, hi2f(e0) * rs), hadd2(fcb0, ONE2), fsb0);
      hs1 = hfma2(pack2(lo2f(e1) * rs, hi2f(e1) * rs), hadd2(fcb1, ONE2), fsb1);
    }
    if ((tid & 127) == 0) sts32(sb + SM_WROW + 4 * wg, wrow);
    nb_arrive(NB_WIN + wg, 160);
    TSY(17);
    TT(11);
    if (b < NFFN) {
      float da[4][4];
#pragma unroll
      for (int i = 0; i < 4; i++) { da[i][0] = da[i][1] = da[i][2] = da[i][3] = 0.f; }
      const uint32_t selv = ((g & 1) ? 0x1044 : 0x4410) + ((g & 4) ? ((g & 1) ? 0x2200 : 0x0022) : 0);
      const uint32_t sel0 = (g & 2) ? 0x4444 : selv, sel1 = (g & 2) ? selv : 0x4444;
#pragma unroll
      for (int s = 0; s < 16; s++) {
        const uint32_t v = __shfl_sync(0xffffffffu, (s & 1) ? hs1 : hs0, 4 * (s >> 1) + t);
        const uint32_t b0 = __byte_perm(v, 0, sel0), b1 = __byte_perm(v, 0, sel1);
        const uint32_t a0[4] = {WG[s].x, WG[s].y, WG[s].z, WG[s].w};
        const uint32_t a1[4] = {WU[s].x, WU[s].y, WU[s].z, WU[s].w};
        mma16816(da[(s & 1) * 2], a0, b0, b1);
        mma16816(da[(s & 1) * 2 + 1], a1, b0, b1);
      }
      {
        float v[4];
#pragma unroll
        for (int i = 0; i < 4; i++) {
          const float vg = da[0][i] + da[2][i], vu = da[1][i] + da[3][i];
          v[i] = ((g & 1) ? vu : vg) + __shfl_xor_sync(0xffffffffu, (g & 1) ? vg : vu, 6);
        }
        if ((t >> 1) == (g & 1))
          sts128(gu_base + (g & 1) * 128 + (g >> 1) * 32 + (t & 1) * 16, __float_as_uint(v[0]), __float_as_uint(v[1]), __float_as_uint(v[2]), __float_as_uint(v[3]));
      }
      TT(12);
      nb_sync(NB_CONS, 256);
      float gp[8], up[8];
#pragma unroll
      for (int w = 0; w < 8; w++) {
        const uint32_t a = sb + SM_RING + (w >> 1) * ST1 + 32768 + (w & 1) * 8192 + lane * 4;
        gp[w] = lds_f32(a); up[w] = lds_f32(a + 128);
      }
      const float gsum = ((gp[0] + gp[1]) + (gp[2] + gp[3])) + ((gp[4] + gp[5]) + (gp[6] + gp[7]));
      const float usum = ((up[0] + up[1]) + (up[2] + up[3])) + ((up[4] + up[5]) + (up[6] + up[7]));
      const float act = rbf(silu_f(rbf(gsum))) * rbf(usum);
      TT(13);
      const uint32_t ap = pack2(act, __shfl_down_sync(0xffffffffu, act, 1));
      const uint32_t b00 = __shfl_sync(0xffffffffu, ap, 2 * t), b01 = __shfl_sync(0xffffffffu, ap, 2 * t + 8);
      const uint32_t b10 = __shfl_sync(0xffffffffu, ap, 2 * t + 16), b11 = __shfl_sync(0xffffffffu, ap, 2 * t + 24);
      float y[8][4];
#pragma unroll
      for (int mt = 0; mt < 8; mt++) {
        y[mt][0] = y[mt][1] = y[mt][2] = y[mt][3] = 0.f;
        mma16816(y[mt], WD + (mt * 2) * 4, b00, b01);
        mma16816(y[mt], WD + (mt * 2 + 1) * 4, b10, b11);
      }
#pragma unroll
      for (int e = 0; e < 2; e++) {
        const float v0 = t == 0 ? y[e][0] : t == 1 ? y[2 + e][0] : t == 2 ? y[4 + e][0] : y[6 + e][0];
        const float v1 = t == 0 ? y[e][2] : t == 1 ? y[2 + e][2] : t == 2 ? y[4 + e][2] : y[6 + e][2];
        const int f = 16 * warp + 2 * (2 * t + e) + (g >> 2);
        st_pkt16(&g_ypart[(f * NFFN + b) * 4 + (g & 3)], __float_as_uint(v0), __float_as_uint(v1), tag, 0);
      }
    }
    TSY(18);
    TT(14);
    {
      const int pw = warp - (warp > (b >> 4));
      if (warp != (b >> 4)) {
        const uint4* yp = &g_ypart[b * NFFN * 4 + pw * 64 + lane];
        uint4 v0, v1;
        int it = 0;
        do { v0 = ld_pkt16(yp); v1 = ld_pkt16(yp + 32); spin_guard(it); }
        while (!(__all_sync(0xffffffffu, v0.z == tag && v1.z == tag)));
        float y0 = __uint_as_float(v0.x) + __uint_as_float(v1.x), y1 = __uint_as_float(v0.y) + __uint_as_float(v1.y);
#pragma unroll
        for (int o = 4; o <= 16; o <<= 1) { y0 += __shfl_xor_sync(0xffffffffu, y0, o); y1 += __shfl_xor_sync(0xffffffffu, y1, o); }
        if (lane < 4) sts64(sb + SM_YRED + pw * 32 + lane * 8, __float_as_uint(y0), __float_as_uint(y1));
      }
    }
    TT(15);
    if (warp != (b >> 4)) {
      nb_arrive(NB_CONS, 256);
    } else {
      nb_sync(NB_CONS, 256);
      float y0 = 0.f, y1 = 0.f;
      if (lane < 28) { const uint2 e = lds64(sb + SM_YRED + lane * 8); y0 = __uint_as_float(e.x); y1 = __uint_as_float(e.y); }
#pragma unroll
      for (int o = 4; o <= 16; o <<= 1) { y0 += __shfl_xor_sync(0xffffffffu, y0, o); y1 += __shfl_xor_sync(0xffffffffu, y1, o); }
      const int src = 2 * (t & 1);
      const float ya = __shfl_sync(0xffffffffu, y0, src), yb = __shfl_sync(0xffffffffu, y0, src + 1);
      const float yc = __shfl_sync(0xffffffffu, y1, src), yd = __shfl_sync(0xffffffffu, y1, src + 1);
      if (g == ((b >> 1) & 7) && (t >> 1) == (b & 1)) {
        const float rs = rbf(__uint_as_float(ent.x));
        const float sg = sigmoid_f(rs);
        const uint32_t sg2 = pack2(sg, sg);
        const uint32_t o0 = hadd2(xs0, hmul2(fgb0, hadd2(hs0, hmul2(pack2(ya, yb), sg2))));
        const uint32_t o1 = hadd2(xs1, hmul2(fgb1, hadd2(hs1, hmul2(pack2(yc, yd), sg2))));
        uint32_t* op = reinterpret_cast<uint32_t*>(p.out + (size_t)wrow * 1024) + fp;
        op[0] = o0; op[4] = o1;
      }
      if (b == 0) {
        if (lane < 8) st_relaxed(&p.sc->ticket[lane * 32], 0);
        st_relaxed(&p.sc->epoch[lane], tag);
      }
      if (lane == 0) TS(19);
    }
  }
}

typedef CUresult (*EncodeFn)(CUtensorMap*, CUtensorMapDataType, cuuint32_t, void*, const cuuint64_t*, const cuuint64_t*,
                             const cuuint32_t*, const cuuint32_t*, CUtensorMapInterleave, CUtensorMapSwizzle,
                             CUtensorMapL2promotion, CUtensorMapFloatOOBfill);

CUtensorMap make_map(EncodeFn enc, const void* ptr, uint64_t rows, uint64_t cols, uint32_t box_rows, uint32_t box_cols, CUtensorMapSwizzle sw) {
  CUtensorMap m;
  cuuint64_t dims[2] = {cols, rows};
  cuuint64_t strides[1] = {cols * 2};
  cuuint32_t box[2] = {box_cols, box_rows};
  cuuint32_t es[2] = {1, 1};
  enc(&m, CU_TENSOR_MAP_DATA_TYPE_BFLOAT16, 2, const_cast<void*>(ptr), dims, strides, box, es, CU_TENSOR_MAP_INTERLEAVE_NONE, sw,
      CU_TENSOR_MAP_L2_PROMOTION_L2_128B, CU_TENSOR_MAP_FLOAT_OOB_FILL_NONE);
  return m;
}

CUtensorMap make_map3(EncodeFn enc, const void* ptr, uint64_t rows, uint64_t cols, uint32_t box_rows, uint32_t box_blks) {
  CUtensorMap m;
  cuuint64_t dims[3] = {64, rows, cols / 64};
  cuuint64_t strides[2] = {cols * 2, 128};
  cuuint32_t box[3] = {64, box_rows, box_blks};
  cuuint32_t es[3] = {1, 1, 1};
  enc(&m, CU_TENSOR_MAP_DATA_TYPE_BFLOAT16, 3, const_cast<void*>(ptr), dims, strides, box, es, CU_TENSOR_MAP_INTERLEAVE_NONE,
      CU_TENSOR_MAP_SWIZZLE_128B, CU_TENSOR_MAP_L2_PROMOTION_L2_128B, CU_TENSOR_MAP_FLOAT_OOB_FILL_NONE);
  return m;
}

}

extern "C" void kernel_launch(void* const* d_in, const int* in_sizes, int n_in, void* d_out, int out_size) {
  (void)in_sizes; (void)n_in; (void)out_size;
  Params p;
  p.x = (const bf16*)d_in[0]; p.kc = (const bf16*)d_in[1]; p.vc = (const bf16*)d_in[2];
  p.wq = (const bf16*)d_in[3]; p.wo = (const bf16*)d_in[4]; p.w_r = (const bf16*)d_in[6];
  p.wg = (const bf16*)d_in[7]; p.wu = (const bf16*)d_in[8]; p.wd = (const bf16*)d_in[9];
  p.c = (const bf16*)d_in[10]; p.w_mod = (const bf16*)d_in[11]; p.out = (bf16*)d_out;

  void* fn = nullptr;
  cudaDriverEntryPointQueryResult st;
  cudaGetDriverEntryPoint("cuTensorMapEncodeTiled", &fn, cudaEnableDefault, &st);
  EncodeFn enc = (EncodeFn)fn;
  void* scp = nullptr;
  cudaGetSymbolAddress(&scp, g_scratch);
  p.sc = (Scratch*)scp;
  void *hp = p.sc->h, *op = p.sc->o;
  const CUtensorMapSwizzle S128 = CU_TENSOR_MAP_SWIZZLE_128B;
  CUtensorMap mH = make_map(enc, hp, 2048, 1024, 64, 64, S128);
  CUtensorMap mWq = make_map3(enc, p.wq, 1024, 4096, 64, 4);
  CUtensorMap mK = make_map(enc, p.kc, 8192, 128, 64, 64, S128);
  CUtensorMap mV = make_map(enc, p.vc, 8192, 128, 64, 64, S128);
  CUtensorMap mO = make_map(enc, op, 2048, 4096, 64, 64, S128);
  CUtensorMap mWo = make_map3(enc, p.wo, 4096, 1024, 64, 2);
  CUtensorMap mX = make_map(enc, p.x, 2048, 1024, 64, 64, S128);
  CUtensorMap mOut = make_map(enc, p.out, 2048, 1024, 64, 64, S128);
  CUtensorMap mWg = make_map(enc, p.wg, 1024, 3584, 256, 32, CU_TENSOR_MAP_SWIZZLE_64B);
  CUtensorMap mWu = make_map(enc, p.wu, 1024, 3584, 256, 32, CU_TENSOR_MAP_SWIZZLE_64B);
  CUtensorMap mWd = make_map3(enc, p.wd, 3584, 1024, 32, 8);
  CUtensorMap mWm = make_map(enc, p.w_mod, 1024, 6144, 16, 256, CU_TENSOR_MAP_SWIZZLE_NONE);
  CUtensorMap mWs = make_map(enc, p.w_mod, 1024, 6144, 128, 128, CU_TENSOR_MAP_SWIZZLE_NONE);
  cudaFuncSetAttribute(fused_kernel, cudaFuncAttributeMaxDynamicSharedMemorySize, SMEM_BYTES);
  fused_kernel<<<NCTA, NTHREADS, SMEM_BYTES>>>(p, mH, mWq, mK, mV, mO, mWo, mX, mOut, mWg, mWu, mWd, mWm, mWs);
}
```

```cpp
#include <cuda_runtime.h>
#include <cuda_bf16.h>
#include <cuda.h>
#include <stdint.h>
#include <stddef.h>

#define UPD 200
#define GATED 1500
#define WL 3500
#define XD 0
#define PLD 200
#define ESTR 8
#define SPD 0
#define PFW 100
#define OD0 300
#define OD1 100
#define X_PEEL 1
#define WU1 12

namespace {

typedef __nv_bfloat16 bf16;

constexpr int NTHREADS = 384;
constexpr int NMAIN = 128;
constexpr int NCTA = 132;
#define RS 8
constexpr int RV = 16 * RS + 64;
constexpr int NREP = 4;
constexpr int NFFN = 112;

constexpr uint32_t SM_RING = 0;
constexpr uint32_t ST1 = 49152;
constexpr uint32_t ST2 = 32768;
constexpr int NST2 = 6;
constexpr uint32_t SM_STASH = 196608;
constexpr uint32_t SM_MISC = 229376;
constexpr uint32_t BAR_FULL1 = SM_MISC + 0;
constexpr uint32_t BAR_EMPTY1 = SM_MISC + 40;
constexpr uint32_t BAR_FULL2 = SM_MISC + 0;
constexpr uint32_t BAR_EMPTY2 = SM_MISC + 48;
constexpr uint32_t BAR_STASH = SM_MISC + 160;
constexpr uint32_t BAR_SFREE = SM_MISC + 176;
constexpr uint32_t BAR_TFREE = SM_MISC + 184;
constexpr uint32_t BAR_FFN = SM_MISC + 192;
constexpr uint32_t BAR_VEC = SM_MISC + 208;
constexpr uint32_t BAR_RED = SM_MISC + 216;
constexpr uint32_t BAR_XH = SM_MISC + 152;
constexpr uint32_t BAR_HS = SM_MISC + 80;
constexpr uint32_t BAR_G = SM_MISC + 112;
constexpr uint32_t BAR_T1 = SM_MISC + 120;
constexpr uint32_t BAR_HF = SM_MISC + 128;
constexpr uint32_t BAR_X = SM_MISC + 136;
constexpr uint32_t BAR_OF = SM_MISC + 224;
constexpr uint32_t BAR_ROLE = SM_MISC + 240;
constexpr uint32_t SM_ROLE = SM_MISC + 248;
constexpr uint32_t SM_GA = SM_MISC + 256;
constexpr uint32_t SM_SCAL = SM_MISC + 512;
constexpr uint32_t SM_WROW = SM_MISC + 520;
constexpr uint32_t SM_AMAX = SM_MISC + 528;
constexpr uint32_t SM_YRED = SM_MISC + 656;
constexpr uint32_t SM_X2 = 2 * ST1, SM_OUT = 3 * ST1;
constexpr uint32_t SM_REC = SM_MISC + 1024;
constexpr uint32_t BAR_TAB = SM_MISC + 1000;
constexpr uint32_t BAR_CAND = SM_MISC + 880;
constexpr uint32_t SM_CAND = SM_MISC + 888;
constexpr uint32_t SM_WSLAB = 2 * 49152 + 16384;
constexpr uint32_t SM_XROW = 2 * 49152;
constexpr uint32_t SM_RED = SM_MISC + 2048;
constexpr uint32_t SM_B1 = SM_MISC + 2048;
constexpr uint32_t SMEM_BYTES = 232448;

constexpr int NB_CONS = 1, NB_WIN = 2  , NB_OST = 4  , NB_AMAX = 6;

struct __align__(1024) Scratch {
  uint32_t epoch[32];
  uint32_t hflag[16 * 32];
  uint32_t oflag[64 * 32];
  uint2 vdone[4 * 16];
  uint32_t pad[96 + 512];
  uint32_t ticket[8 * 32];
  uint2 mod[3072];
  uint4 rec[2][NREP][2 * RV];
  uint4 lnst[1024];
  uint4 entry[8 * 16 * 8];
  uint4 cand[16 * 8 * 32];
  uint4 stats[16 * 8 * 128];
  uint4 ypart[128 * NFFN * 4];
  unsigned long long ts[NCTA * 64];
  uint16_t h[2048 * 1024];
  uint16_t o[2048 * 4096];
};
__device__ Scratch g_scratch;
#define g_epoch (p.sc->epoch[0])
#define g_hflag (p.sc->hflag)
#define g_oflag (p.sc->oflag)
#define g_mod (p.sc->mod)
#define g_entry (p.sc->entry)
#define g_cand (p.sc->cand)
#define g_stats (p.sc->stats)
#define g_ypart (p.sc->ypart)
#define g_vdone (p.sc->vdone)
#define g_lnst (p.sc->lnst)
#define g_rec (p.sc->rec)
#define g_ts (p.sc->ts)
#define g_h (p.sc->h)

struct Params {
  const bf16* w_mod; const bf16* c; Scratch* sc; const bf16* x; const bf16* w_r; bf16* out;
  const bf16* wq; const bf16* wo; const bf16* wg; const bf16* wu; const bf16* wd; const bf16* kc; const bf16* vc;
};

__device__ __forceinline__ uint32_t smem_u32(const void* p) { return (uint32_t)__cvta_generic_to_shared(p); }
__device__ __forceinline__ void mbar_init(uint32_t bar, uint32_t cnt) { asm volatile("mbarrier.init.shared::cta.b64 [%0], %1;" :: "r"(bar), "r"(cnt) : "memory"); }
__device__ __forceinline__ void mbar_expect_tx(uint32_t bar, uint32_t bytes) { asm volatile("mbarrier.arrive.expect_tx.shared::cta.b64 _, [%0], %1;" :: "r"(bar), "r"(bytes) : "memory"); }
__device__ __forceinline__ void mbar_arrive(uint32_t bar) { asm volatile("mbarrier.arrive.shared::cta.b64 _, [%0];" :: "r"(bar) : "memory"); }
__device__ __forceinline__ void mbar_arrive_cl(uint32_t cluster_addr) { asm volatile("mbarrier.arrive.shared::cluster.b64 _, [%0];" :: "r"(cluster_addr) : "memory"); }
__device__ __forceinline__ uint32_t mapa(uint32_t addr, uint32_t cta) { uint32_t r; asm("mapa.shared::cluster.u32 %0, %1, %2;" : "=r"(r) : "r"(addr), "r"(cta)); return r; }
__device__ __forceinline__ bool mbar_test(uint32_t bar, uint32_t parity) {
  uint32_t ok;
  asm volatile("{\n.reg .pred p;\nmbarrier.test_wait.parity.shared::cta.b64 p, [%1], %2;\nselp.u32 %0, 1, 0, p;\n}" : "=r"(ok) : "r"(bar), "r"(parity) : "memory");
  return ok;
}
constexpr int SPIN_LIMIT = 300000;
__device__ __forceinline__ void spin_guard(int& it) {
  asm volatile("{\n.reg .pred p;\n.reg .b64 z;\nadd.s32 %0, %0, 1;\nsetp.gt.s32 p, %0, %1;\nmov.b64 z, 0;\n@p st.volatile.global.u32 [z], %0;\n}" : "+r"(it) : "n"(SPIN_LIMIT));
}
__device__ __forceinline__ void mbar_wait_g(uint32_t bar, uint32_t parity) {
  asm volatile("{\n.reg .pred p, q;\n.reg .b32 c;\n.reg .b64 z;\nmov.b32 c, 0;\nmov.b64 z, 0;\nMW_LOOP:\n"
               "mbarrier.try_wait.parity.shared::cta.b64 p, [%0], %1;\nadd.s32 c, c, 1;\nsetp.gt.s32 q, c, %2;\n"
               "@q st.volatile.global.u32 [z], c;\n@!p bra MW_LOOP;\n}" :: "r"(bar), "r"(parity), "n"(SPIN_LIMIT) : "memory");
}
__device__ __forceinline__ void mbar_wait(uint32_t bar, uint32_t parity) {
  asm volatile("{\n.reg .pred p;\nMW_LOOP:\nmbarrier.try_wait.parity.shared::cta.b64 p, [%0], %1;\n@!p bra MW_LOOP;\n}" :: "r"(bar), "r"(parity) : "memory");
}
__device__ __forceinline__ void bb_fence(uint32_t v) {
  asm volatile("{\n.reg .pred p;\n.reg .u32 c;\nsetp.ne.u32 p, %0, 0;\n@p bra.uni BF_DONE;\nBF_LOOP:\nnanosleep.u32 1;\nmov.u32 c, %%clock;\nsetp.eq.u32 p, c, 0;\n@p bra.uni BF_LOOP;\nBF_DONE:\n}" :: "r"(v) : "memory");
}
__device__ __forceinline__ bool elect_one() {
  uint32_t pred;
  asm volatile("{\n.reg .pred P;\nelect.sync _|P, 0xffffffff;\nselp.u32 %0, 1, 0, P;\n}" : "=r"(pred));
  return pred;
}
__device__ __forceinline__ void tma_ld(uint32_t dst, const CUtensorMap* m, int c0, int c1, uint32_t bar) {
  asm volatile("cp.async.bulk.tensor.2d.shared::cluster.global.mbarrier::complete_tx::bytes [%0], [%1, {%3, %4}], [%2];"
    :: "r"(dst), "l"(m), "r"(bar), "r"(c0), "r"(c1) : "memory");
}
__device__ __forceinline__ void tma_ld_hint(uint32_t dst, const CUtensorMap* m, int c0, int c1, uint32_t bar, uint64_t pol) {
  asm volatile("cp.async.bulk.tensor.2d.shared::cluster.global.mbarrier::complete_tx::bytes.L2::cache_hint [%0], [%1, {%3, %4}], [%2], %5;"
    :: "r"(dst), "l"(m), "r"(bar), "r"(c0), "r"(c1), "l"(pol) : "memory");
}
__device__ __forceinline__ void tma_ld_mc(uint32_t dst, const CUtensorMap* m, int c0, int c1, uint32_t bar) {
  asm volatile("cp.async.bulk.tensor.2d.shared::cluster.global.mbarrier::complete_tx::bytes.multicast::cluster [%0], [%1, {%3, %4}], [%2], %5;"
    :: "r"(dst), "l"(m), "r"(bar), "r"(c0), "r"(c1), "h"((uint16_t)3) : "memory");
}
__device__ __forceinline__ void tma_ld_mc_hint(uint32_t dst, const CUtensorMap* m, int c0, int c1, uint32_t bar, uint64_t pol) {
  asm volatile("cp.async.bulk.tensor.2d.shared::cluster.global.mbarrier::complete_tx::bytes.multicast::cluster.L2::cache_hint [%0], [%1, {%3, %4}], [%2], %5, %6;"
    :: "r"(dst), "l"(m), "r"(bar), "r"(c0), "r"(c1), "h"((uint16_t)3), "l"(pol) : "memory");
}
__device__ __forceinline__ void tma_ld3_hint(uint32_t dst, const CUtensorMap* m, int row, int blk, uint32_t bar, uint64_t pol) {
  asm volatile("cp.async.bulk.tensor.3d.shared::cluster.global.mbarrier::complete_tx::bytes.L2::cache_hint [%0], [%1, {0, %3, %4}], [%2], %5;"
    :: "r"(dst), "l"(m), "r"(bar), "r"(row), "r"(blk), "l"(pol) : "memory");
}
__device__ __forceinline__ void tma_st(const CUtensorMap* m, int c0, int c1, uint32_t src) {
  asm volatile("cp.async.bulk.tensor.2d.global.shared::cta.bulk_group [%0, {%2, %3}], [%1];" :: "l"(m), "r"(src), "r"(c0), "r"(c1) : "memory");
}
__device__ __forceinline__ void tma_prefetch_desc(const CUtensorMap* m) { asm volatile("prefetch.tensormap [%0];" :: "l"(m) : "memory"); }
__device__ __forceinline__ void l2_prefetch(const void* p, uint32_t bytes) { asm volatile("cp.async.bulk.prefetch.L2.global [%0], %1;" :: "l"(p), "r"(bytes) : "memory"); }
__device__ __forceinline__ void bulk_commit() { asm volatile("cp.async.bulk.commit_group;" ::: "memory"); }
__device__ __forceinline__ void bulk_wait_read() { asm volatile("cp.async.bulk.wait_group.read 0;" ::: "memory"); }
__device__ __forceinline__ void bulk_wait_all() { asm volatile("cp.async.bulk.wait_group 0;" ::: "memory"); }
__device__ __forceinline__ void fence_async_smem() { asm volatile("fence.proxy.async.shared::cta;" ::: "memory"); }
__device__ __forceinline__ void fence_async_global() { asm volatile("fence.proxy.async.global;" ::: "memory"); }
__device__ __forceinline__ void fence_acquire_gpu() { asm volatile("fence.acquire.gpu;" ::: "memory"); }
__device__ __forceinline__ void fence_release_gpu() { asm volatile("fence.release.gpu;" ::: "memory"); }
__device__ __forceinline__ void st_async_f32x4(uint32_t cluster_addr, const float* v, uint32_t cluster_bar) {
  asm volatile("st.async.weak.shared::cluster.mbarrier::complete_tx::bytes.v4.f32 [%0], {%1,%2,%3,%4}, [%5];"
    :: "r"(cluster_addr), "f"(v[0]), "f"(v[1]), "f"(v[2]), "f"(v[3]), "r"(cluster_bar) : "memory");
}
__device__ __forceinline__ void nb_sync(int id, int n) { asm volatile("bar.sync %0, %1;" :: "r"(id), "r"(n) : "memory"); }
__device__ __forceinline__ void nb_arrive(int id, int n) { asm volatile("bar.arrive %0, %1;" :: "r"(id), "r"(n) : "memory"); }
__device__ __forceinline__ void wg_fence() { asm volatile("wgmma.fence.sync.aligned;" ::: "memory"); }
__device__ __forceinline__ void wg_commit() { asm volatile("wgmma.commit_group.sync.aligned;" ::: "memory"); }
template <int N> __device__ __forceinline__ void wg_wait() { asm volatile("wgmma.wait_group.sync.aligned %0;" :: "n"(N) : "memory"); }
template <int N> __device__ __forceinline__ void reg_fence(float* a) {
#pragma unroll
  for (int i = 0; i < N; i++) asm volatile("" : "+f"(a[i]) :: "memory");
}
template <int N> __device__ __forceinline__ void reg_fence(uint32_t* a) {
#pragma unroll
  for (int i = 0; i < N; i++) asm volatile("" : "+r"(a[i]) :: "memory");
}
__device__ __forceinline__ uint64_t mk_desc(uint32_t addr, uint32_t lbo) {
  return (uint64_t)((addr & 0x3FFFF) >> 4) | ((uint64_t)(lbo >> 4) << 16) | ((uint64_t)(1024 >> 4) << 32) | (1ull << 62);
}

__device__ __forceinline__ uint64_t policy_evict_first() { uint64_t pol; asm("createpolicy.fractional.L2::evict_first.b64 %0, 1.0;" : "=l"(pol)); return pol; }
__device__ __forceinline__ uint32_t ld_relaxed(const uint32_t* p) { uint32_t v; asm volatile("ld.relaxed.gpu.global.u32 %0, [%1];" : "=r"(v) : "l"(p) : "memory"); return v; }
__device__ __forceinline__ void st_relaxed(uint32_t* p, uint32_t v) { asm volatile("st.relaxed.gpu.global.u32 [%0], %1;" :: "l"(p), "r"(v) : "memory"); }
__device__ __forceinline__ void red_add_relaxed(uint32_t* p, uint32_t v) { asm volatile("red.relaxed.gpu.global.add.u32 [%0], %1;" :: "l"(p), "r"(v) : "memory"); }
__device__ __forceinline__ uint2 ld_pkt8(const uint2* p) {
  uint2 v; asm volatile("{\n.reg .b64 t;\nld.relaxed.gpu.global.b64 t, [%2];\nmov.b64 {%0,%1}, t;\n}" : "=r"(v.x), "=r"(v.y) : "l"(p) : "memory"); return v;
}
__device__ __forceinline__ void st_pkt8(uint2* p, uint32_t a, uint32_t b) {
  asm volatile("{\n.reg .b64 t;\nmov.b64 t, {%1,%2};\nst.relaxed.gpu.global.b64 [%0], t;\n}" :: "l"(p), "r"(a), "r"(b) : "memory");
}
__device__ __forceinline__ uint4 ld_pkt16(const uint4* p) {
  uint4 v; asm volatile("{\n.reg .b128 t;\n.reg .b64 a, b;\nld.relaxed.gpu.global.b128 t, [%4];\nmov.b128 {a, b}, t;\nmov.b64 {%0,%1}, a;\nmov.b64 {%2,%3}, b;\n}"
    : "=r"(v.x), "=r"(v.y), "=r"(v.z), "=r"(v.w) : "l"(p) : "memory"); return v;
}
__device__ __forceinline__ void st_pkt16(uint4* p, uint32_t x, uint32_t y, uint32_t z, uint32_t w) {
  asm volatile("{\n.reg .b128 t;\n.reg .b64 a, b;\nmov.b64 a, {%1,%2};\nmov.b64 b, {%3,%4};\nmov.b128 t, {a, b};\nst.relaxed.gpu.global.b128 [%0], t;\n}"
    :: "l"(p), "r"(x), "r"(y), "r"(z), "r"(w) : "memory");
}
__device__ __forceinline__ void cp_async16(uint32_t dst, const void* src) { asm volatile("cp.async.cg.shared.global [%0], [%1], 16;" :: "r"(dst), "l"(src) : "memory"); }
__device__ __forceinline__ void cp_async_wait() { asm volatile("cp.async.wait_all;" ::: "memory"); }
__device__ __forceinline__ uint32_t lds32(uint32_t a) { uint32_t v; asm volatile("ld.shared.u32 %0, [%1];" : "=r"(v) : "r"(a) : "memory"); return v; }
__device__ __forceinline__ float lds_f32(uint32_t a) { float v; asm volatile("ld.shared.f32 %0, [%1];" : "=f"(v) : "r"(a) : "memory"); return v; }
__device__ __forceinline__ uint2 lds64(uint32_t a) { uint2 v; asm volatile("ld.shared.v2.u32 {%0,%1}, [%2];" : "=r"(v.x), "=r"(v.y) : "r"(a) : "memory"); return v; }
__device__ __forceinline__ uint4 lds128(uint32_t a) { uint4 v; asm volatile("ld.shared.v4.u32 {%0,%1,%2,%3}, [%4];" : "=r"(v.x), "=r"(v.y), "=r"(v.z), "=r"(v.w) : "r"(a) : "memory"); return v; }
__device__ __forceinline__ void sts32(uint32_t a, uint32_t v) { asm volatile("st.shared.u32 [%0], %1;" :: "r"(a), "r"(v) : "memory"); }
__device__ __forceinline__ void sts64(uint32_t a, uint32_t x, uint32_t y) { asm volatile("st.shared.v2.u32 [%0], {%1,%2};" :: "r"(a), "r"(x), "r"(y) : "memory"); }
__device__ __forceinline__ void sts128(uint32_t a, uint32_t x, uint32_t y, uint32_t z, uint32_t w) { asm volatile("st.shared.v4.u32 [%0], {%1,%2,%3,%4};" :: "r"(a), "r"(x), "r"(y), "r"(z), "r"(w) : "memory"); }
__device__ __forceinline__ void stsm4(uint32_t a, uint32_t x, uint32_t y, uint32_t z, uint32_t w) {
  asm volatile("stmatrix.sync.aligned.m8n8.x4.shared.b16 [%0], {%1,%2,%3,%4};" :: "r"(a), "r"(x), "r"(y), "r"(z), "r"(w) : "memory");
}
__device__ __forceinline__ void ldsm4(uint32_t a, uint32_t* r) {
  asm volatile("ldmatrix.sync.aligned.m8n8.x4.shared.b16 {%0,%1,%2,%3}, [%4];" : "=r"(r[0]), "=r"(r[1]), "=r"(r[2]), "=r"(r[3]) : "r"(a) : "memory");
}
__device__ __forceinline__ void ldsm4t(uint32_t a, uint32_t* r) {
  asm volatile("ldmatrix.sync.aligned.m8n8.x4.trans.shared.b16 {%0,%1,%2,%3}, [%4];" : "=r"(r[0]), "=r"(r[1]), "=r"(r[2]), "=r"(r[3]) : "r"(a) : "memory");
}
__device__ __forceinline__ void mma16816(float* d, const uint32_t* a, uint32_t b0, uint32_t b1) {
  asm volatile("mma.sync.aligned.m16n8k16.row.col.f32.bf16.bf16.f32 {%0,%1,%2,%3}, {%4,%5,%6,%7}, {%8,%9}, {%0,%1,%2,%3};"
    : "+f"(d[0]), "+f"(d[1]), "+f"(d[2]), "+f"(d[3]) : "r"(a[0]), "r"(a[1]), "r"(a[2]), "r"(a[3]), "r"(b0), "r"(b1));
}
__device__ __forceinline__ void mma1688(float* d, uint32_t a0, uint32_t a1, uint32_t b0) {
  asm volatile("mma.sync.aligned.m16n8k8.row.col.f32.bf16.bf16.f32 {%0,%1,%2,%3}, {%4,%5}, {%6}, {%0,%1,%2,%3};"
    : "+f"(d[0]), "+f"(d[1]), "+f"(d[2]), "+f"(d[3]) : "r"(a0), "r"(a1), "r"(b0));
}
__device__ __forceinline__ uint32_t pack2(float lo, float hi) { uint32_t r; asm("cvt.rn.bf16x2.f32 %0, %1, %2;" : "=r"(r) : "f"(hi), "f"(lo)); return r; }
__device__ __forceinline__ float lo2f(uint32_t v) { return __uint_as_float(v << 16); }
__device__ __forceinline__ float hi2f(uint32_t v) { return __uint_as_float(v & 0xffff0000u); }
__device__ __forceinline__ uint32_t hmul2(uint32_t a, uint32_t b) { uint32_t r; asm("mul.rn.bf16x2 %0, %1, %2;" : "=r"(r) : "r"(a), "r"(b)); return r; }
__device__ __forceinline__ uint32_t hadd2(uint32_t a, uint32_t b) { uint32_t r; asm("add.rn.bf16x2 %0, %1, %2;" : "=r"(r) : "r"(a), "r"(b)); return r; }
__device__ __forceinline__ uint32_t hsub2(uint32_t a, uint32_t b) { uint32_t r; asm("sub.rn.bf16x2 %0, %1, %2;" : "=r"(r) : "r"(a), "r"(b)); return r; }
__device__ __forceinline__ uint32_t hfma2(uint32_t a, uint32_t b, uint32_t c) { uint32_t r; asm("fma.rn.bf16x2 %0, %1, %2, %3;" : "=r"(r) : "r"(a), "r"(b), "r"(c)); return r; }
__device__ __forceinline__ float rbf(float v) { return lo2f(pack2(v, 0.f)); }
__device__ __forceinline__ float ex2(float v) { float r; asm("ex2.approx.ftz.f32 %0, %1;" : "=f"(r) : "f"(v)); return r; }
__device__ __forceinline__ float rcp_f(float v) { float r; asm("rcp.approx.ftz.f32 %0, %1;" : "=f"(r) : "f"(v)); return r; }
__device__ __forceinline__ float sqrt_f(float v) { float r; asm("sqrt.approx.ftz.f32 %0, %1;" : "=f"(r) : "f"(v)); return r; }
__device__ __forceinline__ float sigmoid_f(float v) { return rcp_f(1.f + ex2(-1.4426950408889634f * v)); }
__device__ __forceinline__ float silu_f(float v) { return v * sigmoid_f(v); }
constexpr uint32_t ONE2 = 0x3f803f80u;

#define R8(a,o) "+f"(a[o+0]), "+f"(a[o+1]), "+f"(a[o+2]), "+f"(a[o+3]), "+f"(a[o+4]), "+f"(a[o+5]), "+f"(a[o+6]), "+f"(a[o+7])
#define R64(a,o) R8(a,o), R8(a,o+8), R8(a,o+16), R8(a,o+24), R8(a,o+32), R8(a,o+40), R8(a,o+48), R8(a,o+56)
#define D64 "{%0,%1,%2,%3,%4,%5,%6,%7,%8,%9,%10,%11,%12,%13,%14,%15,%16,%17,%18,%19,%20,%21,%22,%23,%24,%25,%26,%27,%28,%29,%30,%31," \
            "%32,%33,%34,%35,%36,%37,%38,%39,%40,%41,%42,%43,%44,%45,%46,%47,%48,%49,%50,%51,%52,%53,%54,%55,%56,%57,%58,%59,%60,%61,%62,%63"
#define D128 D64 ",%64,%65,%66,%67,%68,%69,%70,%71,%72,%73,%74,%75,%76,%77,%78,%79,%80,%81,%82,%83,%84,%85,%86,%87,%88,%89,%90,%91,%92,%93,%94,%95," \
            "%96,%97,%98,%99,%100,%101,%102,%103,%104,%105,%106,%107,%108,%109,%110,%111,%112,%113,%114,%115,%116,%117,%118,%119,%120,%121,%122,%123,%124,%125,%126,%127"

template <int TB> __device__ __forceinline__ void wgmma_ss128(float* d, uint64_t da, uint64_t db, int acc) {
  asm volatile("{\n.reg .pred p;\nsetp.ne.b32 p, %66, 0;\nwgmma.mma_async.sync.aligned.m64n128k16.f32.bf16.bf16 " D64 "}, %64, %65, p, 1, 1, 0, %67;\n}"
    : R64(d, 0) : "l"(da), "l"(db), "r"(acc), "n"(TB));
}
template <int TB> __device__ __forceinline__ void wgmma_rs128(float* d, const uint32_t* a, uint64_t db, int acc) {
  asm volatile("{\n.reg .pred p;\nsetp.ne.b32 p, %69, 0;\nwgmma.mma_async.sync.aligned.m64n128k16.f32.bf16.bf16 " D64 "}, {%64,%65,%66,%67}, %68, p, 1, 1, %70;\n}"
    : R64(d, 0) : "r"(a[0]), "r"(a[1]), "r"(a[2]), "r"(a[3]), "l"(db), "r"(acc), "n"(TB));
}
template <int TB> __device__ __forceinline__ void wgmma_ss256(float* d, uint64_t da, uint64_t db, int acc) {
  asm volatile("{\n.reg .pred p;\nsetp.ne.b32 p, %130, 0;\nwgmma.mma_async.sync.aligned.m64n256k16.f32.bf16.bf16 " D128 "}, %128, %129, p, 1, 1, 0, %131;\n}"
    : R64(d, 0), R64(d, 64) : "l"(da), "l"(db), "r"(acc), "n"(TB));
}

#define W8(a,o) "=f"(a[o+0]), "=f"(a[o+1]), "=f"(a[o+2]), "=f"(a[o+3]), "=f"(a[o+4]), "=f"(a[o+5]), "=f"(a[o+6]), "=f"(a[o+7])
#define W64(a,o) W8(a,o), W8(a,o+8), W8(a,o+16), W8(a,o+24), W8(a,o+32), W8(a,o+40), W8(a,o+48), W8(a,o+56)
template <int TB> __device__ __forceinline__ void wgmma_ss128_z(float* d, uint64_t da, uint64_t db) {
  asm volatile("wgmma.mma_async.sync.aligned.m64n128k16.f32.bf16.bf16 " D64 "}, %64, %65, 0, 1, 1, 0, %66;"
    : W64(d, 0) : "l"(da), "l"(db), "n"(TB));
}
template <int TB> __device__ __forceinline__ void wgmma_rs128_z(float* d, const uint32_t* a, uint64_t db) {
  asm volatile("wgmma.mma_async.sync.aligned.m64n128k16.f32.bf16.bf16 " D64 "}, {%64,%65,%66,%67}, %68, 0, 1, 1, %69;"
    : W64(d, 0) : "r"(a[0]), "r"(a[1]), "r"(a[2]), "r"(a[3]), "l"(db), "n"(TB));
}
template <int TB> __device__ __forceinline__ void wgmma_ss256_z(float* d, uint64_t da, uint64_t db) {
  asm volatile("wgmma.mma_async.sync.aligned.m64n256k16.f32.bf16.bf16 " D128 "}, %128, %129, 0, 1, 1, 0, %130;"
    : W64(d, 0), W64(d, 64) : "l"(da), "l"(db), "n"(TB));
}

template <int TB> __device__ __forceinline__ void wgmma_rs256(float* d, const uint32_t* a, uint64_t db) {
  asm volatile("wgmma.mma_async.sync.aligned.m64n256k16.f32.bf16.bf16 " D128 "}, {%128,%129,%130,%131}, %132, 1, 1, 1, %133;"
    : R64(d, 0), R64(d, 64) : "r"(a[0]), "r"(a[1]), "r"(a[2]), "r"(a[3]), "l"(db), "n"(TB));
}
template <int TB> __device__ __forceinline__ void wgmma_rs256_z(float* d, const uint32_t* a, uint64_t db) {
  asm volatile("wgmma.mma_async.sync.aligned.m64n256k16.f32.bf16.bf16 " D128 "}, {%128,%129,%130,%131}, %132, 0, 1, 1, %133;"
    : W64(d, 0), W64(d, 64) : "r"(a[0]), "r"(a[1]), "r"(a[2]), "r"(a[3]), "l"(db), "n"(TB));
}
#define D32 "{%0,%1,%2,%3,%4,%5,%6,%7,%8,%9,%10,%11,%12,%13,%14,%15,%16,%17,%18,%19,%20,%21,%22,%23,%24,%25,%26,%27,%28,%29,%30,%31}"
__device__ __forceinline__ void wgmma_rs64(float* d, const uint32_t* a, uint64_t db) {
  asm volatile("wgmma.mma_async.sync.aligned.m64n64k16.f32.bf16.bf16 " D32 ", {%32,%33,%34,%35}, %36, 1, 1, 1, 0;"
    : R8(d, 0), R8(d, 8), R8(d, 16), R8(d, 24) : "r"(a[0]), "r"(a[1]), "r"(a[2]), "r"(a[3]), "l"(db));
}
__device__ __forceinline__ void wgmma_rs64_z(float* d, const uint32_t* a, uint64_t db) {
  asm volatile("wgmma.mma_async.sync.aligned.m64n64k16.f32.bf16.bf16 " D32 ", {%32,%33,%34,%35}, %36, 0, 1, 1, 0;"
    : W8(d, 0), W8(d, 8), W8(d, 16), W8(d, 24) : "r"(a[0]), "r"(a[1]), "r"(a[2]), "r"(a[3]), "l"(db));
}
__device__ __forceinline__ void issue_qk(float* S, const uint32_t* Q, uint64_t dk) {
  wgmma_rs64_z(S, Q, dk);
#pragma unroll
  for (int kk = 1; kk < 8; kk++) wgmma_rs64(S, Q + 4 * kk, dk + (kk >> 2) * 512 + (kk & 3) * 2);
}
__device__ __forceinline__ void issue_pv(float* O, const uint32_t* P, uint64_t dv, int acc) {
#pragma unroll
  for (int kk = 0; kk < 4; kk++) wgmma_rs128<1>(O, P + 4 * kk, dv + kk * 128, kk ? 1 : acc);
}

#define TS(i)
#define TSC(i)
#define TSX(i)
#define TSY(k) do { if ((tid & 127) == 0) TS((k) + 40 * wg); } while (0)
#define TT(k)
#define TR(k)
#define TH(k)
#define TA(k)
#define TAFLUSH()

struct SoftmaxState { float c0, c1, l0, l1; bool shifted; };
constexpr float SM_SCALE = 0.08838834764831845f * 1.4426950408889634f;
__device__ __forceinline__ void softmax_start(SoftmaxState& z) { z.c0 = z.c1 = z.l0 = z.l1 = 0.f; z.shifted = false; }
__device__ __forceinline__ void softmax_half(float* S, uint32_t* P, float* O, SoftmaxState& z, bool first, uint32_t tag) {
  const float lo0 = z.l0, lo1 = z.l1;
  float lim = 1.2676506002282294e30f;
  const float low = first ? 8.673617379884035e-19f : 0.f;
  if (z.shifted) {
#pragma unroll
    for (int j = 0; j < 32; j++) S[j] += (j & 2) ? z.c1 : z.c0;
  }
#pragma unroll 1
  while (true) {
    bb_fence(tag);
#pragma unroll
    for (int j = 0; j < 8; j++) {
      const float p0 = ex2(S[4 * j]), p1 = ex2(S[4 * j + 1]), p2 = ex2(S[4 * j + 2]), p3 = ex2(S[4 * j + 3]);
      z.l0 += p0; z.l1 += p2; z.l0 += p1; z.l1 += p3;
      P[2 * j] = pack2(p0, p1); P[2 * j + 1] = pack2(p2, p3);
    }
    if (!__any_sync(0xffffffffu, !(z.l0 < lim && z.l1 < lim && fminf(z.l0, z.l1) >= low) && lim > 0.f)) break;
    float d0 = fmaxf(S[0], S[1]), d1 = fmaxf(S[2], S[3]);
#pragma unroll
    for (int j = 1; j < 8; j++) { d0 = fmaxf(d0, fmaxf(S[4 * j], S[4 * j + 1])); d1 = fmaxf(d1, fmaxf(S[4 * j + 2], S[4 * j + 3])); }
    d0 = fmaxf(d0, __shfl_xor_sync(0xffffffffu, d0, 1)); d1 = fmaxf(d1, __shfl_xor_sync(0xffffffffu, d1, 1));
    d0 = fmaxf(d0, __shfl_xor_sync(0xffffffffu, d0, 2)); d1 = fmaxf(d1, __shfl_xor_sync(0xffffffffu, d1, 2));
    if (!first) { d0 = fmaxf(d0, 0.f); d1 = fmaxf(d1, 0.f); }
    z.shifted = true;
    z.c0 -= d0; z.c1 -= d1;
#pragma unroll
    for (int j = 0; j < 32; j++) S[j] -= (j & 2) ? d1 : d0;
    const float a0 = first ? 1.f : ex2(-d0), a1 = first ? 1.f : ex2(-d1);
    z.l0 = lo0 * a0; z.l1 = lo1 * a1;
    lim = -1.f;
    wg_wait<0>();
    reg_fence<64>(O);
#pragma unroll
    for (int j = 0; j < 16; j++) { O[4 * j] *= a0; O[4 * j + 1] *= a0; O[4 * j + 2] *= a1; O[4 * j + 3] *= a1; }
  }
}

__device__ __forceinline__ void modulate_frags(uint32_t* A, const uint32_t* V, const uint4* R, const uint32_t* ln) {
#pragma unroll
  for (int kk = 0; kk < 4; kk++) {
    const uint4 sa = R[kk >> 1], c1 = R[2 + (kk >> 1)];
#pragma unroll
    for (int j = 0; j < 4; j++) {
      const uint32_t n = hfma2(V[4 * kk + j], ln[(j & 1) * 2 + 1], ln[(j & 1) * 2]);
      A[4 * kk + j] = (kk & 1) ? ((j & 2) ? hfma2(n, c1.w, sa.x) : hfma2(n, c1.z, sa.w)) : ((j & 2) ? hfma2(n, c1.y, sa.z) : hfma2(n, c1.x, sa.y));
    }
  }
}
__device__ __forceinline__ void publish_record(uint4* dst, uint32_t pk, int src, int vec, bool doit) {
  const int r = vec ? 0 : 12;
  const uint32_t x = __shfl_sync(0xffffffffu, pk, src + r), y = __shfl_sync(0xffffffffu, pk, src + ((r + 4) & 12));
  const uint32_t z = __shfl_sync(0xffffffffu, pk, src + ((r + 8) & 12)), w = __shfl_sync(0xffffffffu, pk, src + ((r + 12) & 12));
  if (doit) st_pkt16(dst, ~x, y, z, w);
}
__device__ __forceinline__ void put_record(uint32_t sb, int idx, const uint4& v) {
  sts128(sb + SM_STASH + idx * 16, ~v.x, v.y, v.z, v.w);
  sts128(sb + SM_STASH + 16384 + idx * 16, ~v.x, v.y, v.z, v.w);
}
__device__ __forceinline__ float mod_value(float v, int vec) {
  v = rbf(v);
  return (vec ? rbf(1.f + v) : v) * SM_SCALE;
}

__device__ __forceinline__ void row_rcp(float& l0, float& l1) {
  l0 += __shfl_xor_sync(0xffffffffu, l0, 1); l1 += __shfl_xor_sync(0xffffffffu, l1, 1);
  l0 += __shfl_xor_sync(0xffffffffu, l0, 2); l1 += __shfl_xor_sync(0xffffffffu, l1, 2);
  l0 = rcp_f(l0); l1 = rcp_f(l1);
}
__device__ __forceinline__ void stage_o(const float* O, float r0, float r1, uint32_t stsm_addr) {
#pragma unroll
  for (int kk = 0; kk < 8; kk++) {
    stsm4((stsm_addr + (kk >> 2) * 8192) ^ ((kk & 3) * 32),
          pack2(O[8 * kk + 0] * r0, O[8 * kk + 1] * r0), pack2(O[8 * kk + 2] * r1, O[8 * kk + 3] * r1),
          pack2(O[8 * kk + 4] * r0, O[8 * kk + 5] * r0), pack2(O[8 * kk + 6] * r1, O[8 * kk + 7] * r1));
  }
}

__global__ void __cluster_dims__(2, 1, 1) __launch_bounds__(NTHREADS, 1)
fused_kernel(const Params p, const __grid_constant__ CUtensorMap mH, const __grid_constant__ CUtensorMap mWq,
             const __grid_constant__ CUtensorMap mK, const __grid_constant__ CUtensorMap mV,
             const __grid_constant__ CUtensorMap mO, const __grid_constant__ CUtensorMap mWo,
             const __grid_constant__ CUtensorMap mX, const __grid_constant__ CUtensorMap mOut,
             const __grid_constant__ CUtensorMap mWg, const __grid_constant__ CUtensorMap mWu,
             const __grid_constant__ CUtensorMap mWd, const __grid_constant__ CUtensorMap mWm,
             const __grid_constant__ CUtensorMap mWs) {
  extern __shared__ __align__(1024) uint8_t smem_raw[];
  TH(0);
  const uint32_t sb = smem_u32(smem_raw);
  const int tid = threadIdx.x;
  const int b0 = blockIdx.x;
  const int lane = tid & 31;
  const int role = __shfl_sync(0xffffffffu, tid >> 8, 0);

  if (b0 >= NMAIN) {
    const uint32_t tag = ld_relaxed(&g_epoch) + 1;
    const int sp = b0 - NMAIN, vec = 2 + sp;
    const int warp = __shfl_sync(0xffffffffu, tid >> 5, 0);
    float* sc = reinterpret_cast<float*>(smem_raw + SM_STASH);
    float* red = reinterpret_cast<float*>(smem_raw + SM_STASH + 4096);
    const int ridx = (lane >> 3) * 2 * RV + (sp & 1) * RV + 16 * RS + (sp >> 1) * 16 + (warp & 1) * 8 + (lane & 7);
    if (warp < 8) st_pkt16(&g_rec[warp >> 2][0][ridx + (warp & 2) * 16], 0, 0, 0, 0);
#pragma unroll 1
    for (int i = tid; i < 1024; i += NTHREADS) sc[i] = rbf(silu_f(__bfloat162float(p.c[i])));
    if (tid == 0) {
      tma_prefetch_desc(&mWs);
      for (int s = 0; s < NST2; s++) { mbar_init(sb + BAR_FULL2 + 8 * s, 1); mbar_init(sb + BAR_EMPTY2 + 8 * s, 8); }
      fence_async_smem();
      int it = 0;
      do { __nanosleep(100); spin_guard(it); } while (ld_pkt16(&g_lnst[8 * 32 + 16 * sp]).w != tag);
      if (SPD) __nanosleep(SPD);
    }
    __syncthreads();
    int s = 0; uint32_t ph = 0;
    if (tid == 0) TS(0);
    if (warp == 8) {
      const uint64_t pol = policy_evict_first();
#pragma unroll 1
      for (int n = 0; n < 80; n++) {
        mbar_wait_g(sb + BAR_EMPTY2 + 8 * s, ph ^ 1);
        if (elect_one()) {
          mbar_expect_tx(sb + BAR_FULL2 + 8 * s, 32768);
          if (n < 16) {
            tma_ld_hint(sb + s * ST2, &mWs, (sp & 1) * 1024 + 512 + (n >> 3) * 256 + (sp >> 1) * 128, (n & 7) * 128, sb + BAR_FULL2 + 8 * s, pol);
          } else {
#pragma unroll
            for (int j = 0; j < 4; j++) tma_ld_hint(sb + s * ST2 + j * 8192, &mWm, vec * 1024 + j * 256, (n - 16) * 16, sb + BAR_FULL2 + 8 * s, pol);
          }
        }
        __syncwarp();
        if (++s == NST2) { s = 0; ph ^= 1; }
      }
    } else if (warp < 8) {
      float acc[8];
#pragma unroll
      for (int i = 0; i < 8; i++) acc[i] = 0.f;
      auto stage = [&](uint32_t a0, int da, const float* cp, int dc) {
        mbar_wait_g(sb + BAR_FULL2 + 8 * s, ph);
#pragma unroll
        for (int i = 0; i < 8; i++) {
          const uint4 v = lds128(a0 + s * ST2 + i * da);
          const float c = cp[i * dc];
          acc[0] = fmaf(lo2f(v.x), c, acc[0]); acc[1] = fmaf(hi2f(v.x), c, acc[1]);
          acc[2] = fmaf(lo2f(v.y), c, acc[2]); acc[3] = fmaf(hi2f(v.y), c, acc[3]);
          acc[4] = fmaf(lo2f(v.z), c, acc[4]); acc[5] = fmaf(hi2f(v.z), c, acc[5]);
          acc[6] = fmaf(lo2f(v.w), c, acc[6]); acc[7] = fmaf(hi2f(v.w), c, acc[7]);
        }
        if (__shfl_sync(0xffffffffu, lane, __float_as_uint(acc[7]) & 31) < 32 && lane == 0) mbar_arrive(sb + BAR_EMPTY2 + 8 * s);
        if (++s == NST2) { s = 0; ph ^= 1; }
      };
#pragma unroll 1
      for (int n = 0; n < 16; n++) {
        stage(sb + tid * 16, 4096, sc + (n & 7) * 128 + (tid >> 4), 16);
        if ((n & 7) == 7) {
          float* r2 = red + 2048 + (n & 8) * 256;
#pragma unroll
          for (int i = 0; i < 8; i++) { r2[tid * 8 + i] = acc[i]; acc[i] = 0.f; }
          nb_sync(NB_CONS, 256);
          if (warp < 2) {
            float v0 = 0.f, v1 = 0.f;
#pragma unroll 4
            for (int i = 0; i < 16; i++) { const float2 e = reinterpret_cast<const float2*>(r2)[i * 64 + tid]; v0 += e.x; v1 += e.y; }
            publish_record(&g_rec[tag & 1][0][ridx + (n >> 3) * 32], pack2(mod_value(v0, sp & 1), mod_value(v1, sp & 1)),
                           (lane & 4) * 4 + (lane & 3), sp & 1, true);
          }
          if (tid == 0) TS(1 + (n >> 3));
        }
      }
#pragma unroll 1
      for (int n = 0; n < 64; n++) {
        stage(sb + ((tid >> 5) & 3) * 8192 + (tid >> 7) * 4096 + (tid & 31) * 16, 512, sc + n * 16 + (tid >> 7) * 8, 1);
      }
#pragma unroll
      for (int i = 0; i < 8; i++) red[(tid >> 7) * 1024 + (tid & 127) * 8 + i] = acc[i];
    }
    __syncthreads();
    float dot = 0.f;
#pragma unroll 1
    for (int i = tid; i < 512; i += NTHREADS) {
      uint32_t v = pack2(red[2 * i] + red[1024 + 2 * i], red[2 * i + 1] + red[1024 + 2 * i + 1]);
      st_pkt8(&g_mod[vec * 512 + i], v, tag);
      if (vec == 4) v = hadd2(v, ONE2);
      const uint32_t wr = reinterpret_cast<const uint32_t*>(p.w_r)[i];
      dot = fmaf(lo2f(v), lo2f(wr), fmaf(hi2f(v), hi2f(wr), dot));
    }
#pragma unroll
    for (int o = 16; o; o >>= 1) dot += __shfl_xor_sync(0xffffffffu, dot, o);
    if (lane == 0) sc[warp] = dot;
    __syncthreads();
    if (tid == 0) {
      dot = 0.f;
      for (int w = 0; w < 12; w++) dot += sc[w];
      fence_release_gpu();
      st_pkt8(&g_vdone[(vec - 2) * 16], __float_as_uint(dot), tag);
      TS(11);
#pragma unroll 1
      for (int i = 0; i < 128; i++) {
        const int u = i * 4 + (b0 - NMAIN);
        l2_prefetch(p.wo + (size_t)((4 * ((u >> 4) & 7) + (u >> 7)) * 128 + (u & 15) * 8) * 1024, 16384);
        __nanosleep(PFW);
      }
    }
    return;
  }

  const uint32_t rank = b0 & 1;
  const bool slab = !(b0 & 32), late = b0 & 16;
  const uint32_t c0 = clock();
  if (tid == 352) TS(0);
  auto load_slab = [&]() {
    const bf16* wp = p.w_mod + (size_t)(512 * rank + 2 * (tid & ~31) + 2 * (lane & 3) + ((lane >> 2) & 1)) * 6144 + 32 * (b0 >> 1) + 8 * (lane >> 3);
    const uint64_t pef = policy_evict_first();
#pragma unroll
    for (int i = 0; i < 8; i++)
      asm volatile("cp.async.cg.shared.global.L2::cache_hint [%0], [%1], 16, %2;"
        :: "r"(sb + SM_WSLAB + tid * 16 + i * 4096), "l"(wp + (size_t)i * 8 * 6144), "l"(pef) : "memory");
  };
  if (tid == 256) {
    mbar_init(sb + BAR_XH, 1);
    fence_async_smem();
    mbar_expect_tx(sb + BAR_XH, 32768);
    if (XD) while ((uint32_t)clock() - c0 < XD) {}
#pragma unroll
    for (int i = 0; i < 2; i++)
      asm volatile("cp.async.bulk.shared::cluster.global.mbarrier::complete_tx::bytes [%0], [%1], 16384, [%2];"
        :: "r"(sb + SM_XROW + i * ST1), "l"(p.x + (size_t)b0 * 16384 + i * 8192), "r"(sb + BAR_XH) : "memory");
  }
  __syncwarp();
  uint32_t cw[8];
#pragma unroll
  for (int i = 0; i < 8; i++) cw[i] = 0;
  if (!role && slab) {
#pragma unroll
    for (int i = 0; i < 8; i++) cw[i] = ld_relaxed(reinterpret_cast<const uint32_t*>(p.c) + 256 * rank + (tid & ~28) + 4 * i);
  }
  uint32_t epoch = 0;
  if (!role) epoch = ld_relaxed(&p.sc->epoch[lane]);
  if (!role && slab && !late) load_slab();
#define TILE_ROLES() \
  mbar_wait(sb + BAR_ROLE, 0); \
  const int b = 2 * __shfl_sync(0xffffffffu, lds32(sb + SM_ROLE), 0) + rank; \
  const int rt = b >> 3;     \
  const int ct = b & 7;

  if (role) {
    asm volatile("setmaxnreg.dec.sync.aligned.u32 24;");
    const int warp = __shfl_sync(0xffffffffu, tid >> 5, 0);
    if (tid == 256) {
      mbar_init(sb + BAR_RED, 1);
      for (int s = 0; s < 2; s++) mbar_init(sb + BAR_OF + 8 * s, 1);
      mbar_init(sb + BAR_ROLE, 1);
      for (int s = 0; s < 5; s++) { mbar_init(sb + BAR_FULL1 + 8 * s, 1); mbar_init(sb + BAR_EMPTY1 + 8 * s, 4); }
      for (int s = 0; s < 2; s++) { mbar_init(sb + BAR_STASH + 8 * s, 1); mbar_init(sb + BAR_X + 8 * s, 1); }
      for (int s = 0; s < 4; s++) mbar_init(sb + BAR_HS + 8 * s, 1);
      mbar_init(sb + BAR_G, 16); mbar_init(sb + BAR_T1, 1); mbar_init(sb + BAR_HF, 1);
      mbar_init(sb + BAR_SFREE, 4); mbar_init(sb + BAR_TFREE, 8);
      mbar_init(sb + BAR_FFN, 4); mbar_init(sb + BAR_FFN + 8, 2);
      mbar_init(sb + BAR_CAND, 1); mbar_init(sb + BAR_VEC, 32); for (int s = 0; s < 3; s++) mbar_init(sb + BAR_TAB + 8 * s, 32);
      mbar_expect_tx(sb + BAR_RED, 1024);
      mbar_expect_tx(sb + BAR_ROLE, 4);
      asm volatile("fence.mbarrier_init.release.cluster;" ::: "memory");
    }
    __syncwarp();
    asm volatile("barrier.cluster.arrive.relaxed.aligned;" ::: "memory");
    const int ridx = ((lane >> 1) & 3) * 2 * RV + (b0 >> 6) * RV + ((b0 >> 1) & 31) * RS + 2 * rank + (lane & 1) + (lane >> 3) * 4;
    if (warp == 11 && slab && lane < 2 * RS) { st_pkt16(&g_rec[0][0][ridx], 0, 0, 0, 0); st_pkt16(&g_rec[1][0][ridx], 0, 0, 0, 0); }
    if (tid == 256) {
      tma_prefetch_desc(&mWq); tma_prefetch_desc(&mX); tma_prefetch_desc(&mH); tma_prefetch_desc(&mK); tma_prefetch_desc(&mV); tma_prefetch_desc(&mO);
    }
    uint32_t pairid = 0;
    if (tid == 320 && rank == 0) {
      uint32_t t;
      asm("mov.u32 %0, %%smid;" : "=r"(t));
      t >>= 1;
      uint32_t grp = ((0x73216540u >> (4 * ((t < 32 ? t : t < 60 ? 1 + (t - 32) % 7 : t < 62 ? t - 54 : 0) & 7))) & 7) - 1, slot;
      int it = 0;
      do {
        grp = (grp + 1) & 7;
        asm volatile("atom.relaxed.gpu.global.add.u32 %0, [%1], 1;" : "=r"(slot) : "l"(&p.sc->ticket[grp * 32]) : "memory");
        spin_guard(it);
      } while (slot >= 8);
      pairid = slot * 8 + grp;
    }
    __syncwarp();
    asm volatile("barrier.cluster.wait.aligned;" ::: "memory");
    if (tid == 320 && rank == 0) {
#pragma unroll
      for (int r = 0; r < 2; r++)
        asm volatile("st.async.weak.shared::cluster.mbarrier::complete_tx::bytes.b32 [%0], %1, [%2];"
          :: "r"(mapa(sb + SM_ROLE, r)), "r"(pairid), "r"(mapa(sb + BAR_ROLE, r)) : "memory");
    }
    __syncwarp();
    const uint32_t tag = ld_relaxed(&g_epoch) + 1;
    if (warp == 8) {
      TILE_ROLES();
      const int kvrow = (ct >> 1) * 2048 + 1536, arow = rt * 128 + rank * 64;
      const uint64_t pef = policy_evict_first();
#pragma unroll 1
      for (int pair = 0; pair < 2; pair++) {
        const int wblk = (4 * ct + 2 * pair) * 2;
        if (pair) { mbar_wait_g(sb + BAR_HF, 0); fence_async_global(); }
#pragma unroll 1
        for (int n = 0; n < 16; n++) {
          const uint32_t s = n & 3, st = sb + SM_RING + s * ST1, fb = sb + BAR_FULL1 + 8 * s;
          if (n == 2 && pair == 0) mbar_wait_g(sb + BAR_G, 0);
          mbar_wait_g(fb + (BAR_EMPTY1 - BAR_FULL1), ((n >> 2) & 1) ^ 1);
          if (elect_one()) {
            mbar_expect_tx(fb, 49152);
            tma_ld_mc(st + rank * 8192, pair ? &mH : &mX, n * 64, arow, fb);
            tma_ld3_hint(st + 16384, &mWq, n * 64, wblk, fb, pef);
          }
          __syncwarp();
        }
#pragma unroll 1
        for (int n = 0; n < 16; n++) {
          const uint32_t s = n & 3, st = sb + SM_RING + s * ST1 + rank * 8192, fb = sb + BAR_FULL1 + 8 * s;
          const int h0 = n == 0 ? 0 : n == 15 ? 14 : n + 1, h1 = n == 0 ? 1 : n == 15 ? 15 : n - 1;
          mbar_wait_g(fb + (BAR_EMPTY1 - BAR_FULL1), ((n >> 2) & 1) ^ 1);
          if (elect_one()) {
            mbar_expect_tx(fb, 32768);
            tma_ld_mc(st, n == 15 ? &mV : &mK, rank * 64, kvrow + (h0 & 7) * 64, fb);
            tma_ld_mc(st + 16384, n == 0 ? &mK : &mV, rank * 64, kvrow + (h1 & 7) * 64, fb);
            if (n == 3 && pair == 1) mbar_arrive(sb + BAR_T1);
          }
          __syncwarp();
        }
      }
      {
        uint32_t s = 0, ph = 1;
#pragma unroll 1
        for (int half = 0; half < 2; half++) {
          mbar_wait_g(sb + BAR_OF + 8 * half, 0);
          fence_async_global();
#pragma unroll 1
          for (int n = 32 * half; n < 32 * half + 32; n++) {
            const uint32_t st = sb + SM_RING + s * ST1, fb = sb + BAR_FULL1 + 8 * s;
            const int k0 = ((n & 14) * 2 + (n >> 4)) * 128 + (n & 1) * 64;
            mbar_wait_g(n == 8 ? sb + BAR_SFREE : fb + (BAR_EMPTY1 - BAR_FULL1), n == 8 ? 0 : ph ^ (s >> 2));
            if (elect_one()) {
              mbar_expect_tx(fb, 32768);
              tma_ld_mc_hint(st + rank * 8192, &mO, k0, arow, fb, pef);
              tma_ld3_hint(st + 16384, &mWo, k0, 2 * ct, fb, pef);
            }
            __syncwarp();
            if (++s == 5 || n == 3) { s = 0; ph ^= 1; }
          }
        }
        if (b < NFFN) {
#pragma unroll 1
          for (s = 0; s < 2; s++) {
            mbar_wait_g(sb + BAR_EMPTY1 + 8 * s, 0);
            if (elect_one()) {
              mbar_expect_tx(sb + BAR_FFN + 8, 32768);
              tma_ld3_hint(sb + SM_RING + s * ST1, &mWd, b * 32, s * 8, sb + BAR_FFN + 8, pef);
            }
            __syncwarp();
          }
        }
      }
    } else if (warp <= 10) {
      const int w = warp - 9;
      TILE_ROLES();
      const uint32_t st = sb + SM_STASH + w * 16384;
#pragma unroll 1
      for (int j = 0; j < 2; j++) {
        nb_sync(NB_OST + w, 160);
        if (elect_one()) {
          fence_async_smem();
          tma_st(&mH, (2 * ct + j) * 64, rt * 128 + w * 64, st + 4096);
          bulk_commit();
          bulk_wait_read();
          mbar_arrive(sb + BAR_HS + 16 * w + 8 * j);
          if (j) {
            bulk_wait_all();
            fence_async_global();
            fence_release_gpu();
            red_add_relaxed(&g_hflag[rt * 32], 1);
          }
        }
        __syncwarp();
      }
#pragma unroll 1
      for (int r = 0; r < 4; r++) {
        nb_sync(NB_OST + w, 160);
        if (elect_one()) {
          fence_async_smem();
          if (r == 3) __nanosleep(OD0 + w * OD1);
          const int hcol = (4 * ct + r) * 128;
          tma_st(&mO, hcol, rt * 128 + w * 64, st);
          if (r == 3) __nanosleep(2 * OD1);
          tma_st(&mO, hcol + 64, rt * 128 + w * 64, st + 8192);
          bulk_commit();
          bulk_wait_read();
          if (r < 2) {
            mbar_arrive(sb + BAR_STASH + 8 * w);
          } else if (r == 2) {
            mbar_expect_tx(sb + BAR_X + 8 * w, 16384);
            tma_ld(st, &mX, ct * 128, rt * 128 + w * 64, sb + BAR_X + 8 * w);
            tma_ld(st + 8192, &mX, ct * 128 + 64, rt * 128 + w * 64, sb + BAR_X + 8 * w);
          } else {
            mbar_arrive_cl(mapa(sb + BAR_SFREE, 0)); mbar_arrive_cl(mapa(sb + BAR_SFREE, 1));
          }
          bulk_wait_all();
          fence_async_global();
          fence_release_gpu();
          red_add_relaxed(&g_oflag[(rt * 4 + r) * 32], 1);
        }
        __syncwarp();
      }
      nb_sync(NB_OST + w, 160);
      int skip = -1;
      mbar_wait_g(sb + BAR_CAND, 0);
      const bool has_cand = (lds32(sb + SM_CAND) >> 6) == w;
      if (has_cand) {
        nb_sync(NB_WIN + w, 160);
        skip = (int)lds32(sb + SM_WROW + 4 * w) - (rt * 128 + w * 64);
      }
      if ((unsigned)skip >= 64u) {
        if (elect_one()) {
          fence_async_smem();
          tma_st(&mOut, ct * 128, rt * 128 + w * 64, sb + SM_OUT + w * 16384);
          tma_st(&mOut, ct * 128 + 64, rt * 128 + w * 64, sb + SM_OUT + w * 16384 + 8192);
          bulk_commit();
          bulk_wait_read();
        }
        __syncwarp();
      } else {
        uint4* dst = reinterpret_cast<uint4*>(p.out + (size_t)(rt * 128 + w * 64 + (lane >> 4)) * 1024 + ct * 128) + (lane & 15);
#pragma unroll 2
        for (int r = lane >> 4; r < 64; r += 2) {
          const uint4 v = lds128(sb + SM_OUT + w * 16384 + ((lane >> 3) & 1) * 8192 + r * 128 + (((lane ^ r) & 7) * 16));
          if (r != skip) *dst = v;
          dst += 256;
        }
      }
      if (!has_cand) nb_sync(NB_WIN + w, 160);
    } else {
      if (slab) {
        mbar_wait_g(sb + BAR_RED, 0);
        float v = 0.f;
#pragma unroll
        for (int w = 0; w < 8; w++) v += lds_f32(sb + SM_RED + w * 128 + lane * 4);
        v += __shfl_xor_sync(0xffffffffu, v, 16);
        v = mod_value(v, b0 >> 6);
        publish_record(&g_rec[tag & 1][0][ridx], pack2(v, __shfl_down_sync(0xffffffffu, v, 1)), 2 * (lane & 1), b0 >> 6, lane < 8);
        if (lane == 0) TS(1);
      }
      mbar_wait_g(sb + BAR_G, 0);
#pragma unroll 1
      for (int i = 1; i < 4; i++) {
        const uint4* mp = &g_rec[tag & 1][(b0 >> 1) & (NREP - 1)][i == 1 ? (8 + (lane >> 2)) * RS + (lane & 3) : 16 * RS - 64 + 32 * i + lane];
        uint4 v0, v1; int it = 0;
        while (true) {
          v0 = ld_pkt16(mp); v1 = ld_pkt16(mp + RV);
          if (v0.x != 0 && v1.x != 0) break;
          spin_guard(it); __nanosleep(PLD);
        }
        put_record(sb, 32 * i + lane, v0);
        put_record(sb, 128 + 32 * i + lane, v1);
        mbar_arrive(sb + BAR_TAB - 8 + 8 * i);
        if (lane == 0) {
          TS(3 + i + (i > 2));
          if (i == 1) l2_prefetch(((b0 & 64) ? p.vc : p.kc) + (size_t)(((b0 >> 4) & 3) * 2048 + 1536) * 128 + (b0 & 15) * 4096, 8192);
        }
        __syncwarp();
      }
      TILE_ROLES();
      if (lane == 0) {
        int it = 0;
        do { __nanosleep(500); spin_guard(it); } while (ld_relaxed(&g_hflag[rt * 32]) != tag * 16u);
        fence_acquire_gpu();
        mbar_arrive(sb + BAR_HF);
      }
      __syncwarp();
      {
        uint2 v; int it = 0;
        do { __nanosleep(1000); v = ld_pkt8(&g_vdone[(lane & 3) * 16]); spin_guard(it); }
        while (!(v.y == tag));
        __syncwarp();
        fence_acquire_gpu();
        if (lane == 1 || lane == 2) sts32(sb + SM_SCAL + (2 - lane) * 4, v.x);
      }
#pragma unroll 1
      for (int i = 0; i < 2; i++) {
        const int q = i * 32 + lane, pi = ct * 64 + q;
        const uint32_t vga = g_mod[2 * 512 + pi].x, vsb = g_mod[3 * 512 + pi].x, vcb = g_mod[4 * 512 + pi].x, vgb = g_mod[5 * 512 + pi].x;
        const uint32_t wr = reinterpret_cast<const uint32_t*>(p.w_r)[pi];
        const uint32_t c1 = hadd2(vcb, ONE2);
        const float al = lo2f(c1) * lo2f(wr), ah = hi2f(c1) * hi2f(wr);
        const uint32_t o8 = (q & 3) * 8 + ((q >> 2) & 1) * 4;
        sts32(sb + SM_GA + (q >> 3) * 32 + o8, vga);
        sts128(sb + SM_REC + q * 16, c1, vsb, vgb, 0);
        const uint32_t ahi = pack2(al, ah), alo = pack2(al - lo2f(ahi), ah - hi2f(ahi));
        const uint32_t ba = sb + SM_B1 + (q >> 3) * 128 + o8;
        sts32(ba, ONE2); sts32(ba + 32, ahi); sts32(ba + 64, alo); sts32(ba + 96, 0);
      }
      if (lane == 0) TS(28);
      if (lane == 0) {
        tma_prefetch_desc(&mWo); tma_prefetch_desc(&mOut); tma_prefetch_desc(&mWd); tma_prefetch_desc(&mWg); tma_prefetch_desc(&mWu);
#pragma unroll 1
        for (int r = 0; r < 4; r++) {
          int it = 0;
          do { __nanosleep(200); spin_guard(it); } while (ld_relaxed(&g_oflag[(rt * 4 + r) * 32]) != tag * 16u);
          if (r & 1) { fence_acquire_gpu(); mbar_arrive(sb + BAR_OF + 8 * (r >> 1)); }
          if (r == 1 && b < NFFN) {
            const uint64_t pef = policy_evict_first();
            mbar_wait_g(sb + BAR_T1, 0);
#pragma unroll 1
            for (int i = 0; i < 4; i++) {
              mbar_expect_tx(sb + BAR_FFN, 16384);
              tma_ld_hint(sb + SM_RING + i * ST1 + 32768, &mWg, b * 32, i * 256, sb + BAR_FFN, pef);
              __nanosleep(GATED);
            }
          }
        }
      }
      __syncwarp();
      if (b < NFFN) {
        mbar_wait_g(sb + BAR_TFREE, 0);
        const uint64_t pef = policy_evict_first();
#pragma unroll 1
        for (int i = 0; i < 5; i++) {
          if (i > 0 && lane == 0) {
            mbar_expect_tx(sb + BAR_FFN, 16384);
            tma_ld_hint(sb + SM_RING + (i - 1) * ST1 + 32768, &mWu, b * 32, (i - 1) * 256, sb + BAR_FFN, pef);
          }
          if (i < 4) {
#pragma unroll 1
            for (int j = 0; j < 8; j++) {
              asm volatile("prefetch.global.L2 [%0];" :: "l"(p.wu + (size_t)(i * 256 + j * 32 + lane) * 3584 + b * 32) : "memory");
              __nanosleep(UPD);
            }
            __nanosleep(500);
          }
        }
      }
      if (lane == 0) TS(29);
#pragma unroll 1
      for (int i = lane; i < 128; i += 32) st_pkt16(&g_stats[b * 128 + i], 0, 0, 0, 0);
      st_pkt16(&g_cand[b * 32 + lane], 0, 0, 0, 0);
      if (lane < ESTR) st_pkt16(&g_entry[(ct * 16 + rt) * ESTR + lane], 0, 0, 0, 0);
#pragma unroll 1
      for (int i = lane; i < (b < NFFN ? 512 : 0); i += 32) st_pkt16(&g_ypart[((i >> 2) * NFFN + b) * 4 + (i & 3)], 0, 0, 0, 0);
      mbar_arrive(sb + BAR_VEC);
      uint4* const cp = &g_cand[b * 32 + lane];
      uint4* const ep = &g_entry[(ct * 16 + rt) * ESTR];
      nb_sync(NB_AMAX, 288);
      const uint4 e = lds128(sb + SM_AMAX + (lane & 7) * 16);
      const int tmax = __reduce_max_sync(0xffffffffu, (int)e.x);
      const int wl = __ffs(__ballot_sync(0xffffffffu, (int)e.x == tmax)) - 1;
      const uint32_t row = __shfl_sync(0xffffffffu, e.y, wl);
      const uint32_t xa = sb + SM_X2 + (row >> 6) * 16384 + (lane >> 4) * 8192 + (row & 63) * 128 + (lane & 3) * 4
                        + ((((lane >> 1) & 6) ^ (row & 7)) * 16);
      const uint32_t v0 = lds32(xa), v1 = lds32(xa ^ 16);
      if (lane == wl) st_pkt16(ep, e.w, rt * 128 + row, e.z, tag);
      st_pkt16(cp, v0, v1, tag, 0);
      if (lane == 0) { sts32(sb + SM_CAND, row); mbar_arrive(sb + BAR_CAND); }
      if (lane == 0) TS(15);
    }
  } else {
    const int warp = tid >> 5;
    const int wg = warp >> 2, wq = warp & 3;
    const int g = lane >> 2, t = lane & 3;
    uint32_t tag;
    uint32_t ln[4];
    float acc[128];
    uint32_t bf[16];
    auto gemv = [&]() {
          asm volatile("cp.async.wait_all;" ::: "memory");
          float d0[4] = {0.f, 0.f, 0.f, 0.f}, d1[4] = {0.f, 0.f, 0.f, 0.f};
#pragma unroll
          for (int i = 0; i < 8; i++) {
            const uint4 wv = lds128(sb + SM_WSLAB + tid * 16 + i * 4096);
            const uint32_t a[4] = {wv.x, wv.y, wv.z, wv.w};
            mma16816((i & 1) ? d1 : d0, a, bf[2 * i], bf[2 * i + 1]);
          }
#pragma unroll
          for (int i = 0; i < 4; i++) { d0[i] += d1[i]; d0[i] += __shfl_xor_sync(0xffffffffu, d0[i], 6); }
          const uint32_t dst = mapa(sb + SM_MISC, t & 1) - SM_MISC;
          if (!(lane & 6)) st_async_f32x4(dst + SM_RED + warp * 128 + rank * 64 + g * 8, d0, dst + BAR_RED);
          TH(4);
    };
    {
      asm volatile("barrier.cluster.arrive.relaxed.aligned;" ::: "memory");
      if (lane == 0) st_pkt16(&g_lnst[8 * b0 + warp], 0, 0, 0, 0);
      TH(1);
      asm volatile("setmaxnreg.inc.sync.aligned.u32 240;");
      TH(2);
#pragma unroll
      for (int i = 0; i < 8; i++) {
        const float sv = silu_f((g & 4) ? hi2f(cw[i]) : lo2f(cw[i]));
        const uint32_t sp = (g & 1) ? pack2(0.f, sv) : pack2(sv, 0.f);
        bf[2 * i] = (g & 2) ? 0 : sp; bf[2 * i + 1] = (g & 2) ? sp : 0;
      }
      asm volatile("barrier.cluster.wait.aligned;" ::: "memory");
#pragma unroll
      for (int i = 0; i < 128; i++) acc[i] = 0.f;
      reg_fence<128>(acc);
      tag = __shfl_sync(0xffffffffu, epoch, 0) + 1;
      if (slab && late) { while ((uint32_t)clock() - c0 < WL) {} load_slab(); }
      TH(3);
      if (slab && !late) gemv();
      {
        {
          mbar_wait(sb + BAR_XH, 0);
          TH(5);
          float ds[4] = {0.f, 0.f, 0.f, 0.f}, dq[4][4];
#pragma unroll
          for (int i = 0; i < 4; i++) { dq[i][0] = dq[i][1] = dq[i][2] = dq[i][3] = 0.f; }
#pragma unroll
          for (int i = 0; i < 8; i++) {
            uint32_t a[4];
            ldsm4(sb + SM_XROW + wg * ST1 + wq * 4096 + ((lane >> 3) & 1) * 2048 + i * 256 + (lane >> 4) * 128 + (lane & 7) * 16, a);
            mma16816(ds, a, ONE2, ONE2);
            mma1688(dq[0], a[0], a[1], a[0]); mma1688(dq[1], a[0], a[1], a[1]);
            mma1688(dq[2], a[2], a[3], a[2]); mma1688(dq[3], a[2], a[3], a[3]);
          }
          const bool dg = t == (g >> 1);
          const float q0 = dg ? ((g & 1) ? dq[0][1] + dq[2][1] : dq[0][0] + dq[2][0]) : 0.f;
          const float q1 = dg ? ((g & 1) ? dq[1][3] + dq[3][3] : dq[1][2] + dq[3][2]) : 0.f;
          float q = ((lane & 1) ? q1 : q0) + __shfl_xor_sync(0xffffffffu, (lane & 1) ? q0 : q1, 1);
          float sm = (lane & 1) ? ds[2] : ds[0];
          q += __shfl_xor_sync(0xffffffffu, q, 2);
#pragma unroll
          for (int o = 4; o <= 16; o <<= 1) { q += __shfl_xor_sync(0xffffffffu, q, o); sm += __shfl_xor_sync(0xffffffffu, sm, o); }
          const float mean = sm * (1.f / 1024.f);
          const float rd = rcp_f(rbf(sqrt_f(rbf(rbf(fmaxf(fmaf(-mean, mean, q * (1.f / 1024.f)), 0.f)) + 1e-5f))));
          const float mean1 = __shfl_sync(0xffffffffu, mean, 1), rd1 = __shfl_sync(0xffffffffu, rd, 1);
          const uint32_t rh = pack2(rd, rd1);
          if (lane == 0) st_pkt16(&g_lnst[8 * b0 + warp], pack2(-rbf(mean) * lo2f(rh), -rbf(mean1) * hi2f(rh)), rh, 0, tag);
          TH(6);
          if (tid == 0) TS(2);
        }
      }
    }
    if (slab && late) gemv();
    TILE_ROLES();
    const uint32_t xa0 = sb + SM_RING + (warp * 16 + (lane & 15)) * 128 + (((lane >> 4) ^ (lane & 7)) * 16);
    uint32_t V[16];
    {
      const uint4* mp = &g_rec[tag & 1][(b0 >> 1) & (NREP - 1)][RV * wg + (lane >> 2) * RS + (lane & 3)];
      const uint4* lp = &g_lnst[(8 * rt + warp) * 8 + (g >> 1)];
      mbar_wait(sb + BAR_FULL1, 0);
#pragma unroll
      for (int kk = 0; kk < 4; kk++) ldsm4(xa0 ^ (kk * 32), V + 4 * kk);
      uint4 v0 = make_uint4(1, 0, 0, 0), l0, l1;
      int it = 0;
      do { if (wq == 0) v0 = ld_pkt16(mp);
           l0 = ld_pkt16(lp); l1 = ld_pkt16(lp + 4); spin_guard(it); }
        while (!(__all_sync(0xffffffffu, v0.x != 0 && l0.w == tag && l1.w == tag)));
      TH(7);
      if (wq == 0) put_record(sb, 128 * wg + lane, v0);
      const uint32_t sel = (g & 1) ? 0x3232 : 0x1010;
      ln[0] = __byte_perm(l0.x, 0, sel); ln[1] = __byte_perm(l0.y, 0, sel);
      ln[2] = __byte_perm(l1.x, 0, sel); ln[3] = __byte_perm(l1.y, 0, sel);
      __syncwarp();
      if (lane < 2) mbar_arrive_cl(mapa(sb + BAR_G, lane));
      nb_sync(NB_CONS, 256);
      if (tid == 0) TS(3);
      TH(13);
    }

    const uint32_t rel = mapa(sb + SM_MISC, lane & 1) - SM_MISC;
    const uint32_t stsm_addr = sb + SM_STASH + wg * 16384 + (wq * 16 + (lane & 15)) * 128 + (((lane >> 4) ^ (lane & 7)) * 16);

    uint32_t ph = 0;
    uint32_t X[32];
    {
      const uint32_t tab0 = sb + SM_STASH + wg * 16384 + t * 16;
      const uint64_t db0 = mk_desc(sb + SM_RING + 16384, 8192);
      uint32_t A[2][16];
      uint32_t xa[4];
#pragma unroll
      for (int kk = 0; kk < 4; kk++) xa[kk] = xa0 ^ (kk * 32);
      uint32_t tab = tab0;
      reg_fence<4>(xa);
      asm volatile("{\n.reg .pred p;\nsetp.eq.u32 p, %4, 0;\n@p ld.shared.v4.u32 {%0,%1,%2,%3}, [%5];\n}"
        : "+r"(ln[2]), "+r"(ln[0]), "+r"(ln[3]), "+r"(ln[1]) : "r"(tag), "r"(sb));
      int hs = 2 * ct;
      uint4 R[4];
#pragma unroll
      for (int kk = 0; kk < 4; kk++) R[kk] = lds128(tab + (kk >> 1) * 2048 + (kk & 1) * 64);
#pragma unroll 1
      for (int k4 = 0; k4 < 4; k4++) {
#pragma unroll
        for (int s = 0; s < 4; s++) {
          uint32_t* a = A[s & 1];
          const int sn = (s + 1) & 3;
          const uint32_t pn = (k4 + (s == 3)) & 1;
          modulate_frags(a, V, R, ln);
          if (hs == (s & 2)) {
            if (s & 1) mbar_wait(sb + BAR_HS + 16 * wg, 0);
#pragma unroll
            for (int kk = 0; kk < 4; kk++) stsm4((stsm_addr + 4096) ^ (kk * 32), a[4 * kk], a[4 * kk + 1], a[4 * kk + 2], a[4 * kk + 3]);
            nb_arrive(NB_OST + wg, 160);
          }
          if (s == 0 && k4 == 0) TH(8);
          if (s == 0 && k4 == 0 && tid == 0) { TS(6); TSC(61); }
          wg_fence();
#pragma unroll
          for (int kk = 0; kk < 4; kk++) wgmma_rs256<1>(acc, a + 4 * kk, db0 + s * (ST1 >> 4) + kk * 128);
          wg_commit();
          if (s == 3 && k4 < 3) mbar_wait(sb + BAR_TAB + 8 * k4, 0);
#pragma unroll
          for (int kk = 0; kk < 4; kk++) R[kk] = lds128(tab + (s + 1) * 128 + (kk >> 1) * 2048 + (kk & 1) * 64);
          wg_wait<1>();
          if (k4 == 0) TH(9 + s);
          reg_fence<16>(A[(s & 1) ^ 1]);
          if ((tid & 127) < 2 && (s | k4)) mbar_arrive_cl(rel + BAR_EMPTY1 + 8 * ((s + 3) & 3));
          if (s < 3 || k4 < 3) {
            mbar_wait(sb + BAR_FULL1 + 8 * sn, pn);
#pragma unroll
            for (int kk = 0; kk < 4; kk++) ldsm4(xa[kk] + sn * ST1, V + 4 * kk);
          }
        }
        tab += 512; hs -= 4;
      }
      mbar_wait(sb + BAR_HS + 16 * wg + 8, 0);
      wg_wait<0>();
      reg_fence<128>(acc);
    }
#pragma unroll 1
    for (int pair = 0; pair < 2; pair++) {
      uint32_t Q[32];
      TR(0);
      {
        if ((tid & 127) < 2) mbar_arrive_cl(rel + BAR_EMPTY1 + 8 * 3);
        if (pair == 1) mbar_wait(sb + BAR_STASH + 8 * wg, 1);
#pragma unroll
        for (int i = 0; i < 32; i++) Q[i] = pack2(acc[2 * i], acc[2 * i + 1]);
        const uint32_t qs = sb + SM_STASH + wg * 16384 + wq * 2048 + lane * 16;
#pragma unroll
        for (int i = 0; i < 8; i++)
          sts128(qs + (i & 3) * 512 + (i >> 2) * 8192, pack2(acc[64 + 8 * i], acc[65 + 8 * i]), pack2(acc[66 + 8 * i], acc[67 + 8 * i]),
                 pack2(acc[68 + 8 * i], acc[69 + 8 * i]), pack2(acc[70 + 8 * i], acc[71 + 8 * i]));
      }
      if (tid == 0) TS(8 + pair * 2);
      TR(1);
      float O[64], SL[32], SH[32];
      uint32_t PL[16], PH[16];
      SoftmaxState z;
      const uint64_t d0 = mk_desc(sb + SM_RING, 8192);
      {
        mbar_wait(sb + BAR_FULL1, ph);
        wg_fence();
        issue_qk(SL, Q, d0);
        wg_commit();
        issue_qk(SH, Q, d0 + 1024);
        wg_commit();
#pragma unroll
        for (int i = 0; i < 64; i++) O[i] = 0.f;
        reg_fence<64>(O);
        wg_wait<1>();
        reg_fence<32>(SL);
        softmax_start(z);
        softmax_half(SL, PL, O, z, true, tag);
        wg_wait<0>();
        reg_fence<32>(SH);
        if ((tid & 127) < 2) mbar_arrive_cl(rel + BAR_EMPTY1);
      }
      float lp0 = 0.f, lp1 = 0.f;
      uint32_t dB = (uint32_t)d0 + 1 * (ST1 >> 4), dA = (uint32_t)d0 + 2 * (ST1 >> 4);
      const uint32_t dBx = dB ^ ((uint32_t)d0 + 3 * (ST1 >> 4)), dAx = dA ^ (uint32_t)d0;
      uint32_t so = 0;
      bool ready = false;
#pragma unroll 1
      for (int i = 0; i < 7; i++) {
        TA(0);
        TR(2 + i);
        if (!ready) mbar_wait(sb + BAR_FULL1 + 8 + so, ph);
        TA(1);
        TA(2);
        wg_fence();
        issue_qk(SL, Q, (d0 & 0xffffffff00000000ull) | dB);
        if (i == 4) {
          __syncwarp();
          stage_o(O, lp0, lp1, stsm_addr);
        }
        wg_fence();
        issue_pv(O, PL, ((d0 & 0xffffffff00000000ull) | dB) + 1024, i != 4);
        wg_commit();
        if (i == 4) {
          nb_arrive(NB_OST + wg, 160);
        }
        TA(3);
        ph ^= i & 1;
        ready = mbar_test(sb + BAR_FULL1 + 16 - so, ph);
        softmax_half(SH, PH, O, z, false, tag);
        TA(4);
        wg_wait<0>();
        TA(5);
        reg_fence<32>(SL); reg_fence<16>(PL);
        if ((tid & 127) < 2) mbar_arrive_cl(rel + BAR_EMPTY1 + 8 + so);
        if (!ready) mbar_wait(sb + BAR_FULL1 + 16 - so, ph);
        TA(6);
        wg_fence();
        issue_qk(SH, Q, (d0 & 0xffffffff00000000ull) | dA);
        wg_commit();
        issue_pv(O, PH, ((d0 & 0xffffffff00000000ull) | dA) + 1024, 1);
        wg_commit();
        if (i == 2) {
          wg_wait<1>();
          reg_fence<32>(Q);
          const uint32_t qs = sb + SM_STASH + wg * 16384 + wq * 2048 + lane * 16;
#pragma unroll
          for (int j = 0; j < 8; j++) { const uint4 v = lds128(qs + (j & 3) * 512 + (j >> 2) * 8192); Q[4 * j] = v.x; Q[4 * j + 1] = v.y; Q[4 * j + 2] = v.z; Q[4 * j + 3] = v.w; }
        }
        TA(10);
        if (i == 3) { lp0 = z.l0; lp1 = z.l1; row_rcp(lp0, lp1); softmax_start(z); }
        TA(7);
        so ^= 16; dB ^= dBx; dA ^= dAx;
        ready = mbar_test(sb + BAR_FULL1 + 8 + so, ph);
        softmax_half(SL, PL, O, z, i == 3, tag);
        TA(8);
        wg_wait<0>();
        TA(9);
        reg_fence<32>(SH); reg_fence<16>(PH); reg_fence<64>(O); reg_fence<32>(Q);
        if ((tid & 127) < 2) mbar_arrive_cl(rel + BAR_EMPTY1 + so);
      }
      TAFLUSH();
      TR(9);
      {
        if (!ready) mbar_wait(sb + BAR_FULL1 + 8 * 3, ph);
        ph ^= 1;
        const uint64_t dv = d0 + 3 * (ST1 >> 4);
        wg_fence();
        issue_pv(O, PL, dv, 1);
        wg_commit();
        bb_fence(tag);
        softmax_half(SH, PH, O, z, false, tag);
        wg_fence();
        issue_pv(O, PH, dv + 1024, 1);
        wg_commit();
        TR(10);
        row_rcp(z.l0, z.l1);
        mbar_wait(sb + (pair ? BAR_X : BAR_STASH) + 8 * wg, 0);
#pragma unroll
        for (int kk = 0; kk < 8; kk++) ldsm4((stsm_addr + (kk >> 2) * 8192) ^ ((kk & 3) * 32), X + 4 * kk);
        reg_fence<32>(X);
        __syncwarp();
        wg_wait<0>();
        reg_fence<64>(O);
        TR(11);
        if ((tid & 127) < 2) mbar_arrive_cl(rel + BAR_EMPTY1 + 8 * 3);
        stage_o(O, z.l0, z.l1, stsm_addr);
        nb_arrive(NB_OST + wg, 160);
      }
      TR(12);
      if (tid == 0) { TS(9 + pair * 2); TSC(62); }
      if (pair == 1) break;
      {
        mbar_wait(sb + BAR_FULL1, ph);
        const uint64_t da = mk_desc(sb + SM_RING + wg * 8192, 16), db = mk_desc(sb + SM_RING + 16384, 8192);
        wg_fence();
        wgmma_ss256_z<1>(acc, da, db);
#pragma unroll
        for (int kk = 1; kk < 4; kk++) wgmma_ss256<1>(acc, da + kk * 2, db + kk * 128, 1);
        wg_commit();
      }
#pragma unroll 1
      for (int kt = 1; kt < 16; kt++) {
        const uint32_t s = kt & 3;
        if (s == 0) ph ^= 1;
        mbar_wait(sb + BAR_FULL1 + 8 * s, ph);
        const uint32_t st = sb + SM_RING + s * ST1;
        const uint64_t da = mk_desc(st + wg * 8192, 16), db = mk_desc(st + 16384, 8192);
        wg_fence();
#pragma unroll
        for (int kk = 0; kk < 4; kk++) wgmma_ss256<1>(acc, da + kk * 2, db + kk * 128, 1);
        wg_commit();
        wg_wait<1>();
        if ((tid & 127) < 2) mbar_arrive_cl(rel + BAR_EMPTY1 + 8 * ((s + 3) & 3));
      }
      ph ^= 1;
      wg_wait<0>();
      reg_fence<128>(acc);
      TR(13);
    }

    uint4 WG[16], WU[16];
    const int fp = 64 * warp + 8 * g + t;
    uint32_t fsb0, fsb1, fcb0, fcb1, fgb0, fgb1;
    const uint32_t gu_base = sb + SM_RING + (warp >> 1) * ST1 + 32768 + (warp & 1) * 8192;
    const uint32_t gu_addr = gu_base + t * 128 + (g & 1) * 64 + ((g >> 1) ^ t) * 16;
    {
      const uint64_t da0 = mk_desc(sb + SM_RING + __shfl_sync(0xffffffffu, wg, 0) * 8192, 16), db0 = mk_desc(sb + SM_RING + 16384, 8192);
#pragma unroll
      for (int n = 0; n < 4 + 5 * X_PEEL; n++) {
        const int s = n < 4 ? n : (n - 4) % 5;
        mbar_wait(sb + BAR_FULL1 + 8 * s, n < 4 ? 0 : ((n - 4) / 5 + (s < 4)) & 1);
        if (n < 4) TSX(40 + wg * 6 + n);
        const uint64_t da = da0 + s * (ST1 >> 4), db = db0 + s * (ST1 >> 4);
        wg_fence();
        if (n == 0) wgmma_ss128_z<1>(acc, da, db); else wgmma_ss128<1>(acc, da, db, 1);
#pragma unroll
        for (int kk = 1; kk < 4; kk++) wgmma_ss128<1>(acc, da + kk * 2, db + kk * 128, 1);
        wg_commit();
        if (n == 1) {
          mbar_wait(sb + BAR_OF, 0);
          const uint2* mp = &g_mod[3 * 512 + fp];
          fsb0 = ld_pkt8(mp).x; fsb1 = ld_pkt8(mp + 4).x; fcb0 = ld_pkt8(mp + 512).x; fcb1 = ld_pkt8(mp + 516).x;
          fgb0 = ld_pkt8(mp + 1024).x; fgb1 = ld_pkt8(mp + 1028).x;
        }
        if (n == 0 && b < NFFN) mbar_wait(sb + BAR_FFN, 0);
        {
          constexpr int NT = 4 + 5 * X_PEEL, F0 = NT > 16 ? NT - 16 : 0;
#pragma unroll
          for (int i = 0; i < 16; i++) if (F0 + i * (NT - F0) / 16 == n) WG[i] = lds128(gu_addr + i * 512);
        }
        if (n > 0) {
          wg_wait<1>();
          if ((tid & 127) < 2) mbar_arrive_cl(rel + BAR_EMPTY1 + 8 * (n == 4 ? 3 : s ? s - 1 : 4));
        }
      }
      TSX(44 + wg * 6);
      {
        uint32_t dep = 0;
#pragma unroll
        for (int i = 0; i < 16; i++) dep ^= WG[i].x;
        if (__shfl_sync(0xffffffffu, tag, dep & 31) == tag && lane == 2) mbar_arrive(sb + BAR_TFREE);
      }
#pragma unroll 1
      for (int r = X_PEEL; r < 12; r++) {
#pragma unroll
        for (int s = 0; s < 5; s++) {
          mbar_wait(sb + BAR_FULL1 + 8 * s, (r + (s < 4)) & 1);
          const uint64_t da = da0 + s * (ST1 >> 4), db = db0 + s * (ST1 >> 4);
          wg_fence();
#pragma unroll
          for (int kk = 0; kk < 4; kk++) wgmma_ss128<1>(acc, da + kk * 2, db + kk * 128, 1);
          wg_commit();
          wg_wait<1>();
          if ((tid & 127) < 2) mbar_arrive_cl(rel + BAR_EMPTY1 + 8 * (s ? s - 1 : (r == 0 ? 3 : 4)));
        }
      }
    }
    mbar_wait(sb + BAR_VEC, 0);
    const int lrow = warp * 16 + g;
    uint2 ga[8], b1[8];
#pragma unroll
    for (int kk = 0; kk < 8; kk++) { ga[kk] = lds64(sb + SM_GA + kk * 32 + t * 8); b1[kk] = lds64(sb + SM_B1 + min(g, 3) * 32 + t * 8 + kk * 128); }
    uint4* const stp = &g_stats[b * 128 + lrow + 8 * t];
    bb_fence(tag);
    wg_wait<0>();
    reg_fence<64>(acc);
    if (tid == 0) { TS(12); TSC(63); }

    TT(0);
    {
      float d1[4] = {0.f, 0.f, 0.f, 0.f}, d2[4] = {0.f, 0.f, 0.f, 0.f}, d3[4] = {0.f, 0.f, 0.f, 0.f};
      float d4[4] = {0.f, 0.f, 0.f, 0.f}, d5[4] = {0.f, 0.f, 0.f, 0.f};
#pragma unroll
      for (int kk = 0; kk < 8; kk++) {
        uint32_t* x = X + 4 * kk;
        x[0] = hfma2(ga[kk].x, pack2(acc[8 * kk + 0], acc[8 * kk + 1]), x[0]);
        x[1] = hfma2(ga[kk].x, pack2(acc[8 * kk + 2], acc[8 * kk + 3]), x[1]);
        x[2] = hfma2(ga[kk].y, pack2(acc[8 * kk + 4], acc[8 * kk + 5]), x[2]);
        x[3] = hfma2(ga[kk].y, pack2(acc[8 * kk + 6], acc[8 * kk + 7]), x[3]);
        mma16816(d1, x, b1[kk].x, b1[kk].y);
        mma1688(d2, x[0], x[1], x[0]); mma1688(d3, x[0], x[1], x[1]);
        mma1688(d4, x[2], x[3], x[2]); mma1688(d5, x[2], x[3], x[3]);
      }
      const int qb = lane & 28;
      const float q0 = __shfl_sync(0xffffffffu, (g & 1) ? d2[1] + d4[1] : d2[0] + d4[0], qb | (g >> 1));
      const float q1 = __shfl_sync(0xffffffffu, (g & 1) ? d3[3] + d5[3] : d3[2] + d5[2], qb | (g >> 1));
      const float e0 = __shfl_xor_sync(0xffffffffu, t ? d1[0] : d1[3], 1);
      const float e1 = __shfl_sync(0xffffffffu, d1[2], qb);
      if (t < 2) st_pkt16(stp, __float_as_uint(t ? e1 : d1[0]), __float_as_uint(t ? q1 : q0),
                          __float_as_uint((t ? d1[2] : d1[1]) + e0), tag);
    }
    TSY(13);
    TT(1);
    float mb, rd, den, br;
    {
      const uint4* sp = &g_stats[(rt * 8 + 4 * (t & 1)) * 128 + lrow + 4 * (t & 2)];
      mbar_wait(sb + BAR_EMPTY1 + 8 * 3, 0);
#pragma unroll
      for (int kk = 0; kk < 8; kk++) stsm4((stsm_addr - SM_STASH + SM_X2 + (kk >> 2) * 8192) ^ ((kk & 3) * 32), X[4 * kk], X[4 * kk + 1], X[4 * kk + 2], X[4 * kk + 3]);
      if (b < NFFN) mbar_wait(sb + BAR_FFN, 1);
#pragma unroll
      for (int i = 0; i < WU1; i++) WU[i] = lds128(gu_addr + i * 512);
      bb_fence(tag);
      TT(2);
      uint4 v0, v1, v2, v3;
      int it = 0;
      do { v0 = ld_pkt16(sp); v1 = ld_pkt16(sp + 128); v2 = ld_pkt16(sp + 256); v3 = ld_pkt16(sp + 384); spin_guard(it); }
        while (!(__all_sync(0xffffffffu, v0.w == tag && v1.w == tag && v2.w == tag && v3.w == tag)));
      TT(3);
      float sm = (__uint_as_float(v0.x) + __uint_as_float(v1.x)) + (__uint_as_float(v2.x) + __uint_as_float(v3.x));
      float sq = (__uint_as_float(v0.y) + __uint_as_float(v1.y)) + (__uint_as_float(v2.y) + __uint_as_float(v3.y));
      float dt = (__uint_as_float(v0.z) + __uint_as_float(v1.z)) + (__uint_as_float(v2.z) + __uint_as_float(v3.z));
      sm += __shfl_xor_sync(0xffffffffu, sm, 1); sq += __shfl_xor_sync(0xffffffffu, sq, 1); dt += __shfl_xor_sync(0xffffffffu, dt, 1);
      const uint2 scal = lds64(sb + SM_SCAL);
      const float mu = sm * (1.f / 1024.f);
      mb = rbf(mu);
      den = rbf(sqrt_f(rbf(rbf(fmaxf(fmaf(-mu, mu, sq * (1.f / 1024.f)), 0.f)) + 1e-5f)));
      rd = rcp_f(den);
      br = fmaf(fmaf(-mb, __uint_as_float(scal.x), dt), rd, __uint_as_float(scal.y));
    }
    TSY(14);
    TT(4);
    {
      const int rb = __float_as_int(br);
      const int key = rb ^ ((rb >> 31) & 0x7fffffff);
      const int wmax = __reduce_max_sync(0xffffffffu, key);
      if (lane == __ffs(__ballot_sync(0xffffffffu, key == wmax)) - 1)
        sts128(sb + SM_AMAX + warp * 16, (uint32_t)key, lrow + 4 * (t & 2), pack2(mb, den), (uint32_t)rb);
      __syncwarp();
      nb_arrive(NB_AMAX, 288);
    }
    TT(5);
    const uint4* ep = &g_entry[(warp * 16 + (lane & 15)) * ESTR];
    const uint32_t slot = sb + SM_STASH + wg * 8192 + (tid & 127) * 16;
    cp_async16(slot, ep);
    {
      const float rh = rbf(rd);
      const uint32_t u = pack2(-mb * rh, rh);
      const int qb = lane & 28;
      const uint32_t u0 = __shfl_sync(0xffffffffu, u, qb), u1 = __shfl_sync(0xffffffffu, u, qb | 2);
      const uint32_t m0 = __byte_perm(u0, 0, 0x1010), h0 = __byte_perm(u0, 0, 0x3232);
      const uint32_t m1 = __byte_perm(u1, 0, 0x1010), h1 = __byte_perm(u1, 0, 0x3232);
#pragma unroll
      for (int j = 0; j < 16; j++) {
        const uint4 rec = lds128(sb + SM_REC + (4 * j + t) * 16);
        X[2 * j] = hfma2(rec.z, hfma2(hfma2(X[2 * j], h0, m0), rec.x, rec.y), X[2 * j]);
        X[2 * j + 1] = hfma2(rec.z, hfma2(hfma2(X[2 * j + 1], h1, m1), rec.x, rec.y), X[2 * j + 1]);
      }
#pragma unroll
      for (int kk = 0; kk < 8; kk++) stsm4((stsm_addr - SM_STASH + SM_OUT + (kk >> 2) * 8192) ^ ((kk & 3) * 32), X[4 * kk], X[4 * kk + 1], X[4 * kk + 2], X[4 * kk + 3]);
    }
    cp_async_wait();
    uint4 ent = lds128(slot);
    TSY(16);
    TT(6);
    int wrow;
    uint32_t xs0, xs1, hs0, hs1;
    uint32_t WD[64];
    const uint32_t wd_addr = sb + SM_RING + wg * ST1 + wq * 8192 + ((lane & 7) + ((lane >> 4) << 3)) * 128 + ((((lane >> 3) & 1) ^ (lane & 7)) * 16);
    {
      auto leader = [&]() {
        const int key = ent.w == tag ? (int)ent.x ^ (((int)ent.x >> 31) & 0x7fffffff) : (int)0x80000000;
        const int gmax = __reduce_max_sync(0xffffffffu, key);
        return __ffs(__ballot_sync(0xffffffffu, key == gmax)) - 1;
      };
      int wt = leader(), it = 0;
      TT(7);
      nb_arrive(NB_OST + wg, 160);
      TT(8);
      cp_async16(slot + 2048, &g_cand[(wt * 8 + warp) * 32 + lane]);
      if (ent.w != tag) cp_async16(slot, ep);
#pragma unroll
      for (int i = WU1; i < 16; i++) WU[i] = lds128(gu_addr + i * 512);
      if (b < NFFN) mbar_wait(sb + BAR_FFN + 8, 0);
#pragma unroll
      for (int mt = 0; mt < 8; mt++)
#pragma unroll
        for (int s = 0; s < 2; s++) ldsm4t((wd_addr + (mt >> 2) * 4096 + s * 2048) ^ ((mt & 3) * 32), WD + (mt * 2 + s) * 4);
      cp_async_wait();
      uint4 v = lds128(slot + 2048);
      ent = lds128(slot);
      TT(9);
      while (true) {
        const int have = wt;
        wt = leader();
        if (__all_sync(0xffffffffu, ent.w == tag && have == wt && v.z == tag)) break;
        v = ld_pkt16(&g_cand[(wt * 8 + warp) * 32 + lane]);
        if (ent.w != tag) ent = ld_pkt16(ep);
        spin_guard(it);
      }
      TT(10);
      ent.x = __shfl_sync(0xffffffffu, ent.x, wt); wrow = __shfl_sync(0xffffffffu, ent.y, wt); ent.z = __shfl_sync(0xffffffffu, ent.z, wt);
      xs0 = v.x; xs1 = v.y;
      const uint32_t mm = __byte_perm(ent.z, 0, 0x1010);
      const float rs = rcp_f(hi2f(ent.z));
      const uint32_t e0 = hsub2(xs0, mm), e1 = hsub2(xs1, mm);
      hs0 = hfma2(pack2(lo2f(e0) * rs, hi2f(e0) * rs), hadd2(fcb0, ONE2), fsb0);
      hs1 = hfma2(pack2(lo2f(e1) * rs, hi2f(e1) * rs), hadd2(fcb1, ONE2), fsb1);
    }
    if ((tid & 127) == 0) sts32(sb + SM_WROW + 4 * wg, wrow);
    nb_arrive(NB_WIN + wg, 160);
    TSY(17);
    TT(11);
    if (b < NFFN) {
      float da[4][4];
#pragma unroll
      for (int i = 0; i < 4; i++) { da[i][0] = da[i][1] = da[i][2] = da[i][3] = 0.f; }
      const uint32_t selv = ((g & 1) ? 0x1044 : 0x4410) + ((g & 4) ? ((g & 1) ? 0x2200 : 0x0022) : 0);
      const uint32_t sel0 = (g & 2) ? 0x4444 : selv, sel1 = (g & 2) ? selv : 0x4444;
#pragma unroll
      for (int s = 0; s < 16; s++) {
        const uint32_t v = __shfl_sync(0xffffffffu, (s & 1) ? hs1 : hs0, 4 * (s >> 1) + t);
        const uint32_t b0 = __byte_perm(v, 0, sel0), b1 = __byte_perm(v, 0, sel1);
        const uint32_t a0[4] = {WG[s].x, WG[s].y, WG[s].z, WG[s].w};
        const uint32_t a1[4] = {WU[s].x, WU[s].y, WU[s].z, WU[s].w};
        mma16816(da[(s & 1) * 2], a0, b0, b1);
        mma16816(da[(s & 1) * 2 + 1], a1, b0, b1);
      }
      {
        float v[4];
#pragma unroll
        for (int i = 0; i < 4; i++) {
          const float vg = da[0][i] + da[2][i], vu = da[1][i] + da[3][i];
          v[i] = ((g & 1) ? vu : vg) + __shfl_xor_sync(0xffffffffu, (g & 1) ? vg : vu, 6);
        }
        if ((t >> 1) == (g & 1))
          sts128(gu_base + (g & 1) * 128 + (g >> 1) * 32 + (t & 1) * 16, __float_as_uint(v[0]), __float_as_uint(v[1]), __float_as_uint(v[2]), __float_as_uint(v[3]));
      }
      TT(12);
      nb_sync(NB_CONS, 256);
      float gp[8], up[8];
#pragma unroll
      for (int w = 0; w < 8; w++) {
        const uint32_t a = sb + SM_RING + (w >> 1) * ST1 + 32768 + (w & 1) * 8192 + lane * 4;
        gp[w] = lds_f32(a); up[w] = lds_f32(a + 128);
      }
      const float gsum = ((gp[0] + gp[1]) + (gp[2] + gp[3])) + ((gp[4] + gp[5]) + (gp[6] + gp[7]));
      const float usum = ((up[0] + up[1]) + (up[2] + up[3])) + ((up[4] + up[5]) + (up[6] + up[7]));
      const float act = rbf(silu_f(rbf(gsum))) * rbf(usum);
      TT(13);
      const uint32_t ap = pack2(act, __shfl_down_sync(0xffffffffu, act, 1));
      const uint32_t b00 = __shfl_sync(0xffffffffu, ap, 2 * t), b01 = __shfl_sync(0xffffffffu, ap, 2 * t + 8);
      const uint32_t b10 = __shfl_sync(0xffffffffu, ap, 2 * t + 16), b11 = __shfl_sync(0xffffffffu, ap, 2 * t + 24);
      float y[8][4];
#pragma unroll
      for (int mt = 0; mt < 8; mt++) {
        y[mt][0] = y[mt][1] = y[mt][2] = y[mt][3] = 0.f;
        mma16816(y[mt], WD + (mt * 2) * 4, b00, b01);
        mma16816(y[mt], WD + (mt * 2 + 1) * 4, b10, b11);
      }
#pragma unroll
      for (int e = 0; e < 2; e++) {
        const float v0 = t == 0 ? y[e][0] : t == 1 ? y[2 + e][0] : t == 2 ? y[4 + e][0] : y[6 + e][0];
        const float v1 = t == 0 ? y[e][2] : t == 1 ? y[2 + e][2] : t == 2 ? y[4 + e][2] : y[6 + e][2];
        const int f = 16 * warp + 2 * (2 * t + e) + (g >> 2);
        st_pkt16(&g_ypart[(f * NFFN + b) * 4 + (g & 3)], __float_as_uint(v0), __float_as_uint(v1), tag, 0);
      }
    }
    TSY(18);
    TT(14);
    {
      const int pw = warp - (warp > (b >> 4));
      if (warp != (b >> 4)) {
        const uint4* yp = &g_ypart[b * NFFN * 4 + pw * 64 + lane];
        uint4 v0, v1;
        int it = 0;
        do { v0 = ld_pkt16(yp); v1 = ld_pkt16(yp + 32); spin_guard(it); }
        while (!(__all_sync(0xffffffffu, v0.z == tag && v1.z == tag)));
        float y0 = __uint_as_float(v0.x) + __uint_as_float(v1.x), y1 = __uint_as_float(v0.y) + __uint_as_float(v1.y);
#pragma unroll
        for (int o = 4; o <= 16; o <<= 1) { y0 += __shfl_xor_sync(0xffffffffu, y0, o); y1 += __shfl_xor_sync(0xffffffffu, y1, o); }
        if (lane < 4) sts64(sb + SM_YRED + pw * 32 + lane * 8, __float_as_uint(y0), __float_as_uint(y1));
      }
    }
    TT(15);
    if (warp != (b >> 4)) {
      nb_arrive(NB_CONS, 256);
    } else {
      nb_sync(NB_CONS, 256);
      float y0 = 0.f, y1 = 0.f;
      if (lane < 28) { const uint2 e = lds64(sb + SM_YRED + lane * 8); y0 = __uint_as_float(e.x); y1 = __uint_as_float(e.y); }
#pragma unroll
      for (int o = 4; o <= 16; o <<= 1) { y0 += __shfl_xor_sync(0xffffffffu, y0, o); y1 += __shfl_xor_sync(0xffffffffu, y1, o); }
      const int src = 2 * (t & 1);
      const float ya = __shfl_sync(0xffffffffu, y0, src), yb = __shfl_sync(0xffffffffu, y0, src + 1);
      const float yc = __shfl_sync(0xffffffffu, y1, src), yd = __shfl_sync(0xffffffffu, y1, src + 1);
      if (g == ((b >> 1) & 7) && (t >> 1) == (b & 1)) {
        const float rs = rbf(__uint_as_float(ent.x));
        const float sg = sigmoid_f(rs);
        const uint32_t sg2 = pack2(sg, sg);
        const uint32_t o0 = hadd2(xs0, hmul2(fgb0, hadd2(hs0, hmul2(pack2(ya, yb), sg2))));
        const uint32_t o1 = hadd2(xs1, hmul2(fgb1, hadd2(hs1, hmul2(pack2(yc, yd), sg2))));
        uint32_t* op = reinterpret_cast<uint32_t*>(p.out + (size_t)wrow * 1024) + fp;
        op[0] = o0; op[4] = o1;
      }
      if (b == 0) {
        if (lane < 8) st_relaxed(&p.sc->ticket[lane * 32], 0);
        st_relaxed(&p.sc->epoch[lane], tag);
      }
      if (lane == 0) TS(19);
    }
  }
}

typedef CUresult (*EncodeFn)(CUtensorMap*, CUtensorMapDataType, cuuint32_t, void*, const cuuint64_t*, const cuuint64_t*,
                             const cuuint32_t*, const cuuint32_t*, CUtensorMapInterleave, CUtensorMapSwizzle,
                             CUtensorMapL2promotion, CUtensorMapFloatOOBfill);

CUtensorMap make_map(EncodeFn enc, const void* ptr, uint64_t rows, uint64_t cols, uint32_t box_rows, uint32_t box_cols, CUtensorMapSwizzle sw) {
  CUtensorMap m;
  cuuint64_t dims[2] = {cols, rows};
  cuuint64_t strides[1] = {cols * 2};
  cuuint32_t box[2] = {box_cols, box_rows};
  cuuint32_t es[2] = {1, 1};
  enc(&m, CU_TENSOR_MAP_DATA_TYPE_BFLOAT16, 2, const_cast<void*>(ptr), dims, strides, box, es, CU_TENSOR_MAP_INTERLEAVE_NONE, sw,
      CU_TENSOR_MAP_L2_PROMOTION_L2_128B, CU_TENSOR_MAP_FLOAT_OOB_FILL_NONE);
  return m;
}

CUtensorMap make_map3(EncodeFn enc, const void* ptr, uint64_t rows, uint64_t cols, uint32_t box_rows, uint32_t box_blks) {
  CUtensorMap m;
  cuuint64_t dims[3] = {64, rows, cols / 64};
  cuuint64_t strides[2] = {cols * 2, 128};
  cuuint32_t box[3] = {64, box_rows, box_blks};
  cuuint32_t es[3] = {1, 1, 1};
  enc(&m, CU_TENSOR_MAP_DATA_TYPE_BFLOAT16, 3, const_cast<void*>(ptr), dims, strides, box, es, CU_TENSOR_MAP_INTERLEAVE_NONE,
      CU_TENSOR_MAP_SWIZZLE_128B, CU_TENSOR_MAP_L2_PROMOTION_L2_128B, CU_TENSOR_MAP_FLOAT_OOB_FILL_NONE);
  return m;
}

}

extern "C" void kernel_launch(void* const* d_in, const int* in_sizes, int n_in, void* d_out, int out_size) {
  (void)in_sizes; (void)n_in; (void)out_size;
  Params p;
  p.x = (const bf16*)d_in[0]; p.kc = (const bf16*)d_in[1]; p.vc = (const bf16*)d_in[2];
  p.wq = (const bf16*)d_in[3]; p.wo = (const bf16*)d_in[4]; p.w_r = (const bf16*)d_in[6];
  p.wg = (const bf16*)d_in[7]; p.wu = (const bf16*)d_in[8]; p.wd = (const bf16*)d_in[9];
  p.c = (const bf16*)d_in[10]; p.w_mod = (const bf16*)d_in[11]; p.out = (bf16*)d_out;

  void* fn = nullptr;
  cudaDriverEntryPointQueryResult st;
  cudaGetDriverEntryPoint("cuTensorMapEncodeTiled", &fn, cudaEnableDefault, &st);
  EncodeFn enc = (EncodeFn)fn;
  void* scp = nullptr;
  cudaGetSymbolAddress(&scp, g_scratch);
  p.sc = (Scratch*)scp;
  void *hp = p.sc->h, *op = p.sc->o;
  const CUtensorMapSwizzle S128 = CU_TENSOR_MAP_SWIZZLE_128B;
  CUtensorMap mH = make_map(enc, hp, 2048, 1024, 64, 64, S128);
  CUtensorMap mWq = make_map3(enc, p.wq, 1024, 4096, 64, 4);
  CUtensorMap mK = make_map(enc, p.kc, 8192, 128, 64, 64, S128);
  CUtensorMap mV = make_map(enc, p.vc, 8192, 128, 64, 64, S128);
  CUtensorMap mO = make_map(enc, op, 2048, 4096, 64, 64, S128);
  CUtensorMap mWo = make_map3(enc, p.wo, 4096, 1024, 64, 2);
  CUtensorMap mX = make_map(enc, p.x, 2048, 1024, 64, 64, S128);
  CUtensorMap mOut = make_map(enc, p.out, 2048, 1024, 64, 64, S128);
  CUtensorMap mWg = make_map(enc, p.wg, 1024, 3584, 256, 32, CU_TENSOR_MAP_SWIZZLE_64B);
  CUtensorMap mWu = make_map(enc, p.wu, 1024, 3584, 256, 32, CU_TENSOR_MAP_SWIZZLE_64B);
  CUtensorMap mWd = make_map3(enc, p.wd, 3584, 1024, 32, 8);
  CUtensorMap mWm = make_map(enc, p.w_mod, 1024, 6144, 16, 256, CU_TENSOR_MAP_SWIZZLE_NONE);
  CUtensorMap mWs = make_map(enc, p.w_mod, 1024, 6144, 128, 128, CU_TENSOR_MAP_SWIZZLE_NONE);
  cudaFuncSetAttribute(fused_kernel, cudaFuncAttributeMaxDynamicSharedMemorySize, SMEM_BYTES);
  fused_kernel<<<NCTA, NTHREADS, SMEM_BYTES>>>(p, mH, mWq, mK, mV, mO, mWo, mX, mOut, mWg, mWu, mWd, mWm, mWs);
}
```

```cpp
#include <cuda_runtime.h>
#include <cuda_bf16.h>
#include <cuda.h>
#include <stdint.h>
#include <stddef.h>

#define UPD 200
#define GATED 1500
#define WL 3000
#define XD 0
#define PLD 200
#define ESTR 8
#define SPD 0
#define PFW 100
#define X_PEEL 1
#define WU1 12

namespace {

typedef __nv_bfloat16 bf16;

constexpr int NTHREADS = 384;
constexpr int NMAIN = 128;
constexpr int NCTA = 132;
#define RS 8
constexpr int RV = 16 * RS + 64;
constexpr int NREP = 4;
constexpr int NFFN = 112;

constexpr uint32_t SM_RING = 0;
constexpr uint32_t ST1 = 49152;
constexpr uint32_t ST2 = 32768;
constexpr int NST2 = 6;
constexpr uint32_t SM_STASH = 196608;
constexpr uint32_t SM_MISC = 229376;
constexpr uint32_t BAR_FULL1 = SM_MISC + 0;
constexpr uint32_t BAR_EMPTY1 = SM_MISC + 40;
constexpr uint32_t BAR_FULL2 = SM_MISC + 0;
constexpr uint32_t BAR_EMPTY2 = SM_MISC + 48;
constexpr uint32_t BAR_STASH = SM_MISC + 160;
constexpr uint32_t BAR_SFREE = SM_MISC + 176;
constexpr uint32_t BAR_TFREE = SM_MISC + 184;
constexpr uint32_t BAR_FFN = SM_MISC + 192;
constexpr uint32_t BAR_VEC = SM_MISC + 208;
constexpr uint32_t BAR_RED = SM_MISC + 216;
constexpr uint32_t BAR_XH = SM_MISC + 152;
constexpr uint32_t BAR_HS = SM_MISC + 80;
constexpr uint32_t BAR_G = SM_MISC + 112;
constexpr uint32_t BAR_T1 = SM_MISC + 120;
constexpr uint32_t BAR_HF = SM_MISC + 128;
constexpr uint32_t BAR_X = SM_MISC + 136;
constexpr uint32_t BAR_OF = SM_MISC + 224;
constexpr uint32_t BAR_ROLE = SM_MISC + 240;
constexpr uint32_t SM_ROLE = SM_MISC + 248;
constexpr uint32_t SM_GA = SM_MISC + 256;
constexpr uint32_t SM_SCAL = SM_MISC + 512;
constexpr uint32_t SM_WROW = SM_MISC + 520;
constexpr uint32_t SM_AMAX = SM_MISC + 528;
constexpr uint32_t SM_YRED = SM_MISC + 656;
constexpr uint32_t SM_X2 = 2 * ST1, SM_OUT = 3 * ST1;
constexpr uint32_t SM_REC = SM_MISC + 1024;
constexpr uint32_t BAR_TAB = SM_MISC + 1000;
constexpr uint32_t BAR_CAND = SM_MISC + 880;
constexpr uint32_t SM_CAND = SM_MISC + 888;
constexpr uint32_t SM_WSLAB = 2 * 49152 + 16384;
constexpr uint32_t SM_XROW = 2 * 49152;
constexpr uint32_t SM_RED = SM_MISC + 2048;
constexpr uint32_t SM_B1 = SM_MISC + 2048;
constexpr uint32_t SMEM_BYTES = 232448;

constexpr int NB_CONS = 1, NB_WIN = 2  , NB_OST = 4  , NB_AMAX = 6;

struct __align__(1024) Scratch {
  uint32_t epoch[32];
  uint32_t hflag[16 * 32];
  uint32_t oflag[64 * 32];
  uint2 vdone[4 * 16];
  uint32_t pad[96 + 512];
  uint32_t ticket[8 * 32];
  uint2 mod[3072];
  uint4 rec[2][NREP][2 * RV];
  uint4 lnst[1024];
  uint4 entry[8 * 16 * 8];
  uint4 cand[16 * 8 * 32];
  uint4 stats[16 * 8 * 128];
  uint4 ypart[128 * NFFN * 4];
  unsigned long long ts[NCTA * 64];
  uint16_t h[2048 * 1024];
  uint16_t o[2048 * 4096];
};
__device__ Scratch g_scratch;
#define g_epoch (p.sc->epoch[0])
#define g_hflag (p.sc->hflag)
#define g_oflag (p.sc->oflag)
#define g_mod (p.sc->mod)
#define g_entry (p.sc->entry)
#define g_cand (p.sc->cand)
#define g_stats (p.sc->stats)
#define g_ypart (p.sc->ypart)
#define g_vdone (p.sc->vdone)
#define g_lnst (p.sc->lnst)
#define g_rec (p.sc->rec)
#define g_ts (p.sc->ts)
#define g_h (p.sc->h)

struct Params {
  const bf16* w_mod; const bf16* c; Scratch* sc; const bf16* x; const bf16* w_r; bf16* out;
  const bf16* wq; const bf16* wo; const bf16* wg; const bf16* wu; const bf16* wd; const bf16* kc; const bf16* vc;
};

__device__ __forceinline__ uint32_t smem_u32(const void* p) { return (uint32_t)__cvta_generic_to_shared(p); }
__device__ __forceinline__ void mbar_init(uint32_t bar, uint32_t cnt) { asm volatile("mbarrier.init.shared::cta.b64 [%0], %1;" :: "r"(bar), "r"(cnt) : "memory"); }
__device__ __forceinline__ void mbar_expect_tx(uint32_t bar, uint32_t bytes) { asm volatile("mbarrier.arrive.expect_tx.shared::cta.b64 _, [%0], %1;" :: "r"(bar), "r"(bytes) : "memory"); }
__device__ __forceinline__ void mbar_arrive(uint32_t bar) { asm volatile("mbarrier.arrive.shared::cta.b64 _, [%0];" :: "r"(bar) : "memory"); }
__device__ __forceinline__ void mbar_arrive_cl(uint32_t cluster_addr) { asm volatile("mbarrier.arrive.shared::cluster.b64 _, [%0];" :: "r"(cluster_addr) : "memory"); }
__device__ __forceinline__ uint32_t mapa(uint32_t addr, uint32_t cta) { uint32_t r; asm("mapa.shared::cluster.u32 %0, %1, %2;" : "=r"(r) : "r"(addr), "r"(cta)); return r; }
__device__ __forceinline__ bool mbar_test(uint32_t bar, uint32_t parity) {
  uint32_t ok;
  asm volatile("{\n.reg .pred p;\nmbarrier.test_wait.parity.shared::cta.b64 p, [%1], %2;\nselp.u32 %0, 1, 0, p;\n}" : "=r"(ok) : "r"(bar), "r"(parity) : "memory");
  return ok;
}
constexpr int SPIN_LIMIT = 300000;
__device__ __forceinline__ void spin_guard(int& it) {
  asm volatile("{\n.reg .pred p;\n.reg .b64 z;\nadd.s32 %0, %0, 1;\nsetp.gt.s32 p, %0, %1;\nmov.b64 z, 0;\n@p st.volatile.global.u32 [z], %0;\n}" : "+r"(it) : "n"(SPIN_LIMIT));
}
__device__ __forceinline__ void mbar_wait_g(uint32_t bar, uint32_t parity) {
  asm volatile("{\n.reg .pred p, q;\n.reg .b32 c;\n.reg .b64 z;\nmov.b32 c, 0;\nmov.b64 z, 0;\nMW_LOOP:\n"
               "mbarrier.try_wait.parity.shared::cta.b64 p, [%0], %1;\nadd.s32 c, c, 1;\nsetp.gt.s32 q, c, %2;\n"
               "@q st.volatile.global.u32 [z], c;\n@!p bra MW_LOOP;\n}" :: "r"(bar), "r"(parity), "n"(SPIN_LIMIT) : "memory");
}
__device__ __forceinline__ void mbar_wait(uint32_t bar, uint32_t parity) {
  asm volatile("{\n.reg .pred p;\nMW_LOOP:\nmbarrier.try_wait.parity.shared::cta.b64 p, [%0], %1;\n@!p bra MW_LOOP;\n}" :: "r"(bar), "r"(parity) : "memory");
}
__device__ __forceinline__ void bb_fence(uint32_t v) {
  asm volatile("{\n.reg .pred p;\n.reg .u32 c;\nsetp.ne.u32 p, %0, 0;\n@p bra.uni BF_DONE;\nBF_LOOP:\nnanosleep.u32 1;\nmov.u32 c, %%clock;\nsetp.eq.u32 p, c, 0;\n@p bra.uni BF_LOOP;\nBF_DONE:\n}" :: "r"(v) : "memory");
}
__device__ __forceinline__ bool elect_one() {
  uint32_t pred;
  asm volatile("{\n.reg .pred P;\nelect.sync _|P, 0xffffffff;\nselp.u32 %0, 1, 0, P;\n}" : "=r"(pred));
  return pred;
}
__device__ __forceinline__ void tma_ld(uint32_t dst, const CUtensorMap* m, int c0, int c1, uint32_t bar) {
  asm volatile("cp.async.bulk.tensor.2d.shared::cluster.global.mbarrier::complete_tx::bytes [%0], [%1, {%3, %4}], [%2];"
    :: "r"(dst), "l"(m), "r"(bar), "r"(c0), "r"(c1) : "memory");
}
__device__ __forceinline__ void tma_ld_hint(uint32_t dst, const CUtensorMap* m, int c0, int c1, uint32_t bar, uint64_t pol) {
  asm volatile("cp.async.bulk.tensor.2d.shared::cluster.global.mbarrier::complete_tx::bytes.L2::cache_hint [%0], [%1, {%3, %4}], [%2], %5;"
    :: "r"(dst), "l"(m), "r"(bar), "r"(c0), "r"(c1), "l"(pol) : "memory");
}
__device__ __forceinline__ void tma_ld_mc(uint32_t dst, const CUtensorMap* m, int c0, int c1, uint32_t bar) {
  asm volatile("cp.async.bulk.tensor.2d.shared::cluster.global.mbarrier::complete_tx::bytes.multicast::cluster [%0], [%1, {%3, %4}], [%2], %5;"
    :: "r"(dst), "l"(m), "r"(bar), "r"(c0), "r"(c1), "h"((uint16_t)3) : "memory");
}
__device__ __forceinline__ void tma_ld_mc_hint(uint32_t dst, const CUtensorMap* m, int c0, int c1, uint32_t bar, uint64_t pol) {
  asm volatile("cp.async.bulk.tensor.2d.shared::cluster.global.mbarrier::complete_tx::bytes.multicast::cluster.L2::cache_hint [%0], [%1, {%3, %4}], [%2], %5, %6;"
    :: "r"(dst), "l"(m), "r"(bar), "r"(c0), "r"(c1), "h"((uint16_t)3), "l"(pol) : "memory");
}
__device__ __forceinline__ void tma_ld3_hint(uint32_t dst, const CUtensorMap* m, int row, int blk, uint32_t bar, uint64_t pol) {
  asm volatile("cp.async.bulk.tensor.3d.shared::cluster.global.mbarrier::complete_tx::bytes.L2::cache_hint [%0], [%1, {0, %3, %4}], [%2], %5;"
    :: "r"(dst), "l"(m), "r"(bar), "r"(row), "r"(blk), "l"(pol) : "memory");
}
__device__ __forceinline__ void tma_st(const CUtensorMap* m, int c0, int c1, uint32_t src) {
  asm volatile("cp.async.bulk.tensor.2d.global.shared::cta.bulk_group [%0, {%2, %3}], [%1];" :: "l"(m), "r"(src), "r"(c0), "r"(c1) : "memory");
}
__device__ __forceinline__ void tma_prefetch_desc(const CUtensorMap* m) { asm volatile("prefetch.tensormap [%0];" :: "l"(m) : "memory"); }
__device__ __forceinline__ void l2_prefetch(const void* p, uint32_t bytes) { asm volatile("cp.async.bulk.prefetch.L2.global [%0], %1;" :: "l"(p), "r"(bytes) : "memory"); }
__device__ __forceinline__ void bulk_commit() { asm volatile("cp.async.bulk.commit_group;" ::: "memory"); }
__device__ __forceinline__ void bulk_wait_read() { asm volatile("cp.async.bulk.wait_group.read 0;" ::: "memory"); }
__device__ __forceinline__ void bulk_wait_all() { asm volatile("cp.async.bulk.wait_group 0;" ::: "memory"); }
__device__ __forceinline__ void fence_async_smem() { asm volatile("fence.proxy.async.shared::cta;" ::: "memory"); }
__device__ __forceinline__ void fence_async_global() { asm volatile("fence.proxy.async.global;" ::: "memory"); }
__device__ __forceinline__ void fence_acquire_gpu() { asm volatile("fence.acquire.gpu;" ::: "memory"); }
__device__ __forceinline__ void fence_release_gpu() { asm volatile("fence.release.gpu;" ::: "memory"); }
__device__ __forceinline__ void st_async_f32x4(uint32_t cluster_addr, const float* v, uint32_t cluster_bar) {
  asm volatile("st.async.weak.shared::cluster.mbarrier::complete_tx::bytes.v4.f32 [%0], {%1,%2,%3,%4}, [%5];"
    :: "r"(cluster_addr), "f"(v[0]), "f"(v[1]), "f"(v[2]), "f"(v[3]), "r"(cluster_bar) : "memory");
}
__device__ __forceinline__ void nb_sync(int id, int n) { asm volatile("bar.sync %0, %1;" :: "r"(id), "r"(n) : "memory"); }
__device__ __forceinline__ void nb_arrive(int id, int n) { asm volatile("bar.arrive %0, %1;" :: "r"(id), "r"(n) : "memory"); }
__device__ __forceinline__ void wg_fence() { asm volatile("wgmma.fence.sync.aligned;" ::: "memory"); }
__device__ __forceinline__ void wg_commit() { asm volatile("wgmma.commit_group.sync.aligned;" ::: "memory"); }
template <int N> __device__ __forceinline__ void wg_wait() { asm volatile("wgmma.wait_group.sync.aligned %0;" :: "n"(N) : "memory"); }
template <int N> __device__ __forceinline__ void reg_fence(float* a) {
#pragma unroll
  for (int i = 0; i < N; i++) asm volatile("" : "+f"(a[i]) :: "memory");
}
template <int N> __device__ __forceinline__ void reg_fence(uint32_t* a) {
#pragma unroll
  for (int i = 0; i < N; i++) asm volatile("" : "+r"(a[i]) :: "memory");
}
__device__ __forceinline__ uint64_t mk_desc(uint32_t addr, uint32_t lbo) {
  return (uint64_t)((addr & 0x3FFFF) >> 4) | ((uint64_t)(lbo >> 4) << 16) | ((uint64_t)(1024 >> 4) << 32) | (1ull << 62);
}

__device__ __forceinline__ uint64_t policy_evict_first() { uint64_t pol; asm("createpolicy.fractional.L2::evict_first.b64 %0, 1.0;" : "=l"(pol)); return pol; }
__device__ __forceinline__ uint32_t ld_relaxed(const uint32_t* p) { uint32_t v; asm volatile("ld.relaxed.gpu.global.u32 %0, [%1];" : "=r"(v) : "l"(p) : "memory"); return v; }
__device__ __forceinline__ void st_relaxed(uint32_t* p, uint32_t v) { asm volatile("st.relaxed.gpu.global.u32 [%0], %1;" :: "l"(p), "r"(v) : "memory"); }
__device__ __forceinline__ void red_add_relaxed(uint32_t* p, uint32_t v) { asm volatile("red.relaxed.gpu.global.add.u32 [%0], %1;" :: "l"(p), "r"(v) : "memory"); }
__device__ __forceinline__ uint2 ld_pkt8(const uint2* p) {
  uint2 v; asm volatile("{\n.reg .b64 t;\nld.relaxed.gpu.global.b64 t, [%2];\nmov.b64 {%0,%1}, t;\n}" : "=r"(v.x), "=r"(v.y) : "l"(p) : "memory"); return v;
}
__device__ __forceinline__ void st_pkt8(uint2* p, uint32_t a, uint32_t b) {
  asm volatile("{\n.reg .b64 t;\nmov.b64 t, {%1,%2};\nst.relaxed.gpu.global.b64 [%0], t;\n}" :: "l"(p), "r"(a), "r"(b) : "memory");
}
__device__ __forceinline__ uint4 ld_pkt16(const uint4* p) {
  uint4 v; asm volatile("{\n.reg .b128 t;\n.reg .b64 a, b;\nld.relaxed.gpu.global.b128 t, [%4];\nmov.b128 {a, b}, t;\nmov.b64 {%0,%1}, a;\nmov.b64 {%2,%3}, b;\n}"
    : "=r"(v.x), "=r"(v.y), "=r"(v.z), "=r"(v.w) : "l"(p) : "memory"); return v;
}
__device__ __forceinline__ void st_pkt16(uint4* p, uint32_t x, uint32_t y, uint32_t z, uint32_t w) {
  asm volatile("{\n.reg .b128 t;\n.reg .b64 a, b;\nmov.b64 a, {%1,%2};\nmov.b64 b, {%3,%4};\nmov.b128 t, {a, b};\nst.relaxed.gpu.global.b128 [%0], t;\n}"
    :: "l"(p), "r"(x), "r"(y), "r"(z), "r"(w) : "memory");
}
__device__ __forceinline__ void cp_async16(uint32_t dst, const void* src) { asm volatile("cp.async.cg.shared.global [%0], [%1], 16;" :: "r"(dst), "l"(src) : "memory"); }
__device__ __forceinline__ void cp_async_wait() { asm volatile("cp.async.wait_all;" ::: "memory"); }
__device__ __forceinline__ uint32_t lds32(uint32_t a) { uint32_t v; asm volatile("ld.shared.u32 %0, [%1];" : "=r"(v) : "r"(a) : "memory"); return v; }
__device__ __forceinline__ float lds_f32(uint32_t a) { float v; asm volatile("ld.shared.f32 %0, [%1];" : "=f"(v) : "r"(a) : "memory"); return v; }
__device__ __forceinline__ uint2 lds64(uint32_t a) { uint2 v; asm volatile("ld.shared.v2.u32 {%0,%1}, [%2];" : "=r"(v.x), "=r"(v.y) : "r"(a) : "memory"); return v; }
__device__ __forceinline__ uint4 lds128(uint32_t a) { uint4 v; asm volatile("ld.shared.v4.u32 {%0,%1,%2,%3}, [%4];" : "=r"(v.x), "=r"(v.y), "=r"(v.z), "=r"(v.w) : "r"(a) : "memory"); return v; }
__device__ __forceinline__ void sts32(uint32_t a, uint32_t v) { asm volatile("st.shared.u32 [%0], %1;" :: "r"(a), "r"(v) : "memory"); }
__device__ __forceinline__ void sts64(uint32_t a, uint32_t x, uint32_t y) { asm volatile("st.shared.v2.u32 [%0], {%1,%2};" :: "r"(a), "r"(x), "r"(y) : "memory"); }
__device__ __forceinline__ void sts128(uint32_t a, uint32_t x, uint32_t y, uint32_t z, uint32_t w) { asm volatile("st.shared.v4.u32 [%0], {%1,%2,%3,%4};" :: "r"(a), "r"(x), "r"(y), "r"(z), "r"(w) : "memory"); }
__device__ __forceinline__ void stsm4(uint32_t a, uint32_t x, uint32_t y, uint32_t z, uint32_t w) {
  asm volatile("stmatrix.sync.aligned.m8n8.x4.shared.b16 [%0], {%1,%2,%3,%4};" :: "r"(a), "r"(x), "r"(y), "r"(z), "r"(w) : "memory");
}
__device__ __forceinline__ void ldsm4(uint32_t a, uint32_t* r) {
  asm volatile("ldmatrix.sync.aligned.m8n8.x4.shared.b16 {%0,%1,%2,%3}, [%4];" : "=r"(r[0]), "=r"(r[1]), "=r"(r[2]), "=r"(r[3]) : "r"(a) : "memory");
}
__device__ __forceinline__ void ldsm4t(uint32_t a, uint32_t* r) {
  asm volatile("ldmatrix.sync.aligned.m8n8.x4.trans.shared.b16 {%0,%1,%2,%3}, [%4];" : "=r"(r[0]), "=r"(r[1]), "=r"(r[2]), "=r"(r[3]) : "r"(a) : "memory");
}
__device__ __forceinline__ void mma16816(float* d, const uint32_t* a, uint32_t b0, uint32_t b1) {
  asm volatile("mma.sync.aligned.m16n8k16.row.col.f32.bf16.bf16.f32 {%0,%1,%2,%3}, {%4,%5,%6,%7}, {%8,%9}, {%0,%1,%2,%3};"
    : "+f"(d[0]), "+f"(d[1]), "+f"(d[2]), "+f"(d[3]) : "r"(a[0]), "r"(a[1]), "r"(a[2]), "r"(a[3]), "r"(b0), "r"(b1));
}
__device__ __forceinline__ void mma1688(float* d, uint32_t a0, uint32_t a1, uint32_t b0) {
  asm volatile("mma.sync.aligned.m16n8k8.row.col.f32.bf16.bf16.f32 {%0,%1,%2,%3}, {%4,%5}, {%6}, {%0,%1,%2,%3};"
    : "+f"(d[0]), "+f"(d[1]), "+f"(d[2]), "+f"(d[3]) : "r"(a0), "r"(a1), "r"(b0));
}
__device__ __forceinline__ uint32_t pack2(float lo, float hi) { uint32_t r; asm("cvt.rn.bf16x2.f32 %0, %1, %2;" : "=r"(r) : "f"(hi), "f"(lo)); return r; }
__device__ __forceinline__ float lo2f(uint32_t v) { return __uint_as_float(v << 16); }
__device__ __forceinline__ float hi2f(uint32_t v) { return __uint_as_float(v & 0xffff0000u); }
__device__ __forceinline__ uint32_t hmul2(uint32_t a, uint32_t b) { uint32_t r; asm("mul.rn.bf16x2 %0, %1, %2;" : "=r"(r) : "r"(a), "r"(b)); return r; }
__device__ __forceinline__ uint32_t hadd2(uint32_t a, uint32_t b) { uint32_t r; asm("add.rn.bf16x2 %0, %1, %2;" : "=r"(r) : "r"(a), "r"(b)); return r; }
__device__ __forceinline__ uint32_t hsub2(uint32_t a, uint32_t b) { uint32_t r; asm("sub.rn.bf16x2 %0, %1, %2;" : "=r"(r) : "r"(a), "r"(b)); return r; }
__device__ __forceinline__ uint32_t hfma2(uint32_t a, uint32_t b, uint32_t c) { uint32_t r; asm("fma.rn.bf16x2 %0, %1, %2, %3;" : "=r"(r) : "r"(a), "r"(b), "r"(c)); return r; }
__device__ __forceinline__ float rbf(float v) { return lo2f(pack2(v, 0.f)); }
__device__ __forceinline__ float ex2(float v) { float r; asm("ex2.approx.ftz.f32 %0, %1;" : "=f"(r) : "f"(v)); return r; }
__device__ __forceinline__ float rcp_f(float v) { float r; asm("rcp.approx.ftz.f32 %0, %1;" : "=f"(r) : "f"(v)); return r; }
__device__ __forceinline__ float sqrt_f(float v) { float r; asm("sqrt.approx.ftz.f32 %0, %1;" : "=f"(r) : "f"(v)); return r; }
__device__ __forceinline__ float sigmoid_f(float v) { return rcp_f(1.f + ex2(-1.4426950408889634f * v)); }
__device__ __forceinline__ float silu_f(float v) { return v * sigmoid_f(v); }
constexpr uint32_t ONE2 = 0x3f803f80u;

#define R8(a,o) "+f"(a[o+0]), "+f"(a[o+1]), "+f"(a[o+2]), "+f"(a[o+3]), "+f"(a[o+4]), "+f"(a[o+5]), "+f"(a[o+6]), "+f"(a[o+7])
#define R64(a,o) R8(a,o), R8(a,o+8), R8(a,o+16), R8(a,o+24), R8(a,o+32), R8(a,o+40), R8(a,o+48), R8(a,o+56)
#define D64 "{%0,%1,%2,%3,%4,%5,%6,%7,%8,%9,%10,%11,%12,%13,%14,%15,%16,%17,%18,%19,%20,%21,%22,%23,%24,%25,%26,%27,%28,%29,%30,%31," \
            "%32,%33,%34,%35,%36,%37,%38,%39,%40,%41,%42,%43,%44,%45,%46,%47,%48,%49,%50,%51,%52,%53,%54,%55,%56,%57,%58,%59,%60,%61,%62,%63"
#define D128 D64 ",%64,%65,%66,%67,%68,%69,%70,%71,%72,%73,%74,%75,%76,%77,%78,%79,%80,%81,%82,%83,%84,%85,%86,%87,%88,%89,%90,%91,%92,%93,%94,%95," \
            "%96,%97,%98,%99,%100,%101,%102,%103,%104,%105,%106,%107,%108,%109,%110,%111,%112,%113,%114,%115,%116,%117,%118,%119,%120,%121,%122,%123,%124,%125,%126,%127"

template <int TB> __device__ __forceinline__ void wgmma_ss128(float* d, uint64_t da, uint64_t db, int acc) {
  asm volatile("{\n.reg .pred p;\nsetp.ne.b32 p, %66, 0;\nwgmma.mma_async.sync.aligned.m64n128k16.f32.bf16.bf16 " D64 "}, %64, %65, p, 1, 1, 0, %67;\n}"
    : R64(d, 0) : "l"(da), "l"(db), "r"(acc), "n"(TB));
}
template <int TB> __device__ __forceinline__ void wgmma_rs128(float* d, const uint32_t* a, uint64_t db, int acc) {
  asm volatile("{\n.reg .pred p;\nsetp.ne.b32 p, %69, 0;\nwgmma.mma_async.sync.aligned.m64n128k16.f32.bf16.bf16 " D64 "}, {%64,%65,%66,%67}, %68, p, 1, 1, %70;\n}"
    : R64(d, 0) : "r"(a[0]), "r"(a[1]), "r"(a[2]), "r"(a[3]), "l"(db), "r"(acc), "n"(TB));
}
template <int TB> __device__ __forceinline__ void wgmma_ss256(float* d, uint64_t da, uint64_t db, int acc) {
  asm volatile("{\n.reg .pred p;\nsetp.ne.b32 p, %130, 0;\nwgmma.mma_async.sync.aligned.m64n256k16.f32.bf16.bf16 " D128 "}, %128, %129, p, 1, 1, 0, %131;\n}"
    : R64(d, 0), R64(d, 64) : "l"(da), "l"(db), "r"(acc), "n"(TB));
}

#define W8(a,o) "=f"(a[o+0]), "=f"(a[o+1]), "=f"(a[o+2]), "=f"(a[o+3]), "=f"(a[o+4]), "=f"(a[o+5]), "=f"(a[o+6]), "=f"(a[o+7])
#define W64(a,o) W8(a,o), W8(a,o+8), W8(a,o+16), W8(a,o+24), W8(a,o+32), W8(a,o+40), W8(a,o+48), W8(a,o+56)
template <int TB> __device__ __forceinline__ void wgmma_ss128_z(float* d, uint64_t da, uint64_t db) {
  asm volatile("wgmma.mma_async.sync.aligned.m64n128k16.f32.bf16.bf16 " D64 "}, %64, %65, 0, 1, 1, 0, %66;"
    : W64(d, 0) : "l"(da), "l"(db), "n"(TB));
}
template <int TB> __device__ __forceinline__ void wgmma_rs128_z(float* d, const uint32_t* a, uint64_t db) {
  asm volatile("wgmma.mma_async.sync.aligned.m64n128k16.f32.bf16.bf16 " D64 "}, {%64,%65,%66,%67}, %68, 0, 1, 1, %69;"
    : W64(d, 0) : "r"(a[0]), "r"(a[1]), "r"(a[2]), "r"(a[3]), "l"(db), "n"(TB));
}
template <int TB> __device__ __forceinline__ void wgmma_ss256_z(float* d, uint64_t da, uint64_t db) {
  asm volatile("wgmma.mma_async.sync.aligned.m64n256k16.f32.bf16.bf16 " D128 "}, %128, %129, 0, 1, 1, 0, %130;"
    : W64(d, 0), W64(d, 64) : "l"(da), "l"(db), "n"(TB));
}

template <int TB> __device__ __forceinline__ void wgmma_rs256(float* d, const uint32_t* a, uint64_t db) {
  asm volatile("wgmma.mma_async.sync.aligned.m64n256k16.f32.bf16.bf16 " D128 "}, {%128,%129,%130,%131}, %132, 1, 1, 1, %133;"
    : R64(d, 0), R64(d, 64) : "r"(a[0]), "r"(a[1]), "r"(a[2]), "r"(a[3]), "l"(db), "n"(TB));
}
template <int TB> __device__ __forceinline__ void wgmma_rs256_z(float* d, const uint32_t* a, uint64_t db) {
  asm volatile("wgmma.mma_async.sync.aligned.m64n256k16.f32.bf16.bf16 " D128 "}, {%128,%129,%130,%131}, %132, 0, 1, 1, %133;"
    : W64(d, 0), W64(d, 64) : "r"(a[0]), "r"(a[1]), "r"(a[2]), "r"(a[3]), "l"(db), "n"(TB));
}
#define D32 "{%0,%1,%2,%3,%4,%5,%6,%7,%8,%9,%10,%11,%12,%13,%14,%15,%16,%17,%18,%19,%20,%21,%22,%23,%24,%25,%26,%27,%28,%29,%30,%31}"
__device__ __forceinline__ void wgmma_rs64(float* d, const uint32_t* a, uint64_t db) {
  asm volatile("wgmma.mma_async.sync.aligned.m64n64k16.f32.bf16.bf16 " D32 ", {%32,%33,%34,%35}, %36, 1, 1, 1, 0;"
    : R8(d, 0), R8(d, 8), R8(d, 16), R8(d, 24) : "r"(a[0]), "r"(a[1]), "r"(a[2]), "r"(a[3]), "l"(db));
}
__device__ __forceinline__ void wgmma_rs64_z(float* d, const uint32_t* a, uint64_t db) {
  asm volatile("wgmma.mma_async.sync.aligned.m64n64k16.f32.bf16.bf16 " D32 ", {%32,%33,%34,%35}, %36, 0, 1, 1, 0;"
    : W8(d, 0), W8(d, 8), W8(d, 16), W8(d, 24) : "r"(a[0]), "r"(a[1]), "r"(a[2]), "r"(a[3]), "l"(db));
}
__device__ __forceinline__ void issue_qk(float* S, const uint32_t* Q, uint64_t dk) {
  wgmma_rs64_z(S, Q, dk);
#pragma unroll
  for (int kk = 1; kk < 8; kk++) wgmma_rs64(S, Q + 4 * kk, dk + (kk >> 2) * 512 + (kk & 3) * 2);
}
__device__ __forceinline__ void issue_pv(float* O, const uint32_t* P, uint64_t dv, int acc) {
#pragma unroll
  for (int kk = 0; kk < 4; kk++) wgmma_rs128<1>(O, P + 4 * kk, dv + kk * 128, kk ? 1 : acc);
}

#define TS(i)
#define TSC(i)
#define TSX(i)
#define TSY(k) do { if ((tid & 127) == 0) TS((k) + 40 * wg); } while (0)
#define TT(k)
#define TR(k)
#define TH(k)
#define TA(k)
#define TAFLUSH()

struct SoftmaxState { float c0, c1, l0, l1; bool shifted; };
constexpr float SM_SCALE = 0.08838834764831845f * 1.4426950408889634f;
__device__ __forceinline__ void softmax_start(SoftmaxState& z) { z.c0 = z.c1 = z.l0 = z.l1 = 0.f; z.shifted = false; }
__device__ __forceinline__ void softmax_half(float* S, uint32_t* P, float* O, SoftmaxState& z, bool first, uint32_t tag) {
  const float lo0 = z.l0, lo1 = z.l1;
  float lim = 1.2676506002282294e30f;
  const float low = first ? 8.673617379884035e-19f : 0.f;
  if (z.shifted) {
#pragma unroll
    for (int j = 0; j < 32; j++) S[j] += (j & 2) ? z.c1 : z.c0;
  }
#pragma unroll 1
  while (true) {
    bb_fence(tag);
#pragma unroll
    for (int j = 0; j < 8; j++) {
      const float p0 = ex2(S[4 * j]), p1 = ex2(S[4 * j + 1]), p2 = ex2(S[4 * j + 2]), p3 = ex2(S[4 * j + 3]);
      z.l0 += p0; z.l1 += p2; z.l0 += p1; z.l1 += p3;
      P[2 * j] = pack2(p0, p1); P[2 * j + 1] = pack2(p2, p3);
    }
    if (!__any_sync(0xffffffffu, !(z.l0 < lim && z.l1 < lim && fminf(z.l0, z.l1) >= low) && lim > 0.f)) break;
    float d0 = fmaxf(S[0], S[1]), d1 = fmaxf(S[2], S[3]);
#pragma unroll
    for (int j = 1; j < 8; j++) { d0 = fmaxf(d0, fmaxf(S[4 * j], S[4 * j + 1])); d1 = fmaxf(d1, fmaxf(S[4 * j + 2], S[4 * j + 3])); }
    d0 = fmaxf(d0, __shfl_xor_sync(0xffffffffu, d0, 1)); d1 = fmaxf(d1, __shfl_xor_sync(0xffffffffu, d1, 1));
    d0 = fmaxf(d0, __shfl_xor_sync(0xffffffffu, d0, 2)); d1 = fmaxf(d1, __shfl_xor_sync(0xffffffffu, d1, 2));
    if (!first) { d0 = fmaxf(d0, 0.f); d1 = fmaxf(d1, 0.f); }
    z.shifted = true;
    z.c0 -= d0; z.c1 -= d1;
#pragma unroll
    for (int j = 0; j < 32; j++) S[j] -= (j & 2) ? d1 : d0;
    const float a0 = first ? 1.f : ex2(-d0), a1 = first ? 1.f : ex2(-d1);
    z.l0 = lo0 * a0; z.l1 = lo1 * a1;
    lim = -1.f;
    wg_wait<0>();
    reg_fence<64>(O);
#pragma unroll
    for (int j = 0; j < 16; j++) { O[4 * j] *= a0; O[4 * j + 1] *= a0; O[4 * j + 2] *= a1; O[4 * j + 3] *= a1; }
  }
}

__device__ __forceinline__ void modulate_frags(uint32_t* A, const uint32_t* V, const uint4* R, const uint32_t* ln) {
#pragma unroll
  for (int kk = 0; kk < 4; kk++) {
    const uint4 sa = R[kk >> 1], c1 = R[2 + (kk >> 1)];
#pragma unroll
    for (int j = 0; j < 4; j++) {
      const uint32_t n = hfma2(V[4 * kk + j], ln[(j & 1) * 2 + 1], ln[(j & 1) * 2]);
      A[4 * kk + j] = (kk & 1) ? ((j & 2) ? hfma2(n, c1.w, sa.x) : hfma2(n, c1.z, sa.w)) : ((j & 2) ? hfma2(n, c1.y, sa.z) : hfma2(n, c1.x, sa.y));
    }
  }
}
__device__ __forceinline__ void publish_record(uint4* dst, uint32_t pk, int src, int vec, bool doit) {
  const int r = vec ? 0 : 12;
  const uint32_t x = __shfl_sync(0xffffffffu, pk, src + r), y = __shfl_sync(0xffffffffu, pk, src + ((r + 4) & 12));
  const uint32_t z = __shfl_sync(0xffffffffu, pk, src + ((r + 8) & 12)), w = __shfl_sync(0xffffffffu, pk, src + ((r + 12) & 12));
  if (doit) st_pkt16(dst, ~x, y, z, w);
}
__device__ __forceinline__ void put_record(uint32_t sb, int idx, const uint4& v) {
  sts128(sb + SM_STASH + idx * 16, ~v.x, v.y, v.z, v.w);
  sts128(sb + SM_STASH + 16384 + idx * 16, ~v.x, v.y, v.z, v.w);
}
__device__ __forceinline__ float mod_value(float v, int vec) {
  v = rbf(v);
  return (vec ? rbf(1.f + v) : v) * SM_SCALE;
}

__device__ __forceinline__ void row_rcp(float& l0, float& l1) {
  l0 += __shfl_xor_sync(0xffffffffu, l0, 1); l1 += __shfl_xor_sync(0xffffffffu, l1, 1);
  l0 += __shfl_xor_sync(0xffffffffu, l0, 2); l1 += __shfl_xor_sync(0xffffffffu, l1, 2);
  l0 = rcp_f(l0); l1 = rcp_f(l1);
}
__device__ __forceinline__ void stage_o(const float* O, float r0, float r1, uint32_t stsm_addr) {
#pragma unroll
  for (int kk = 0; kk < 8; kk++) {
    stsm4((stsm_addr + (kk >> 2) * 8192) ^ ((kk & 3) * 32),
          pack2(O[8 * kk + 0] * r0, O[8 * kk + 1] * r0), pack2(O[8 * kk + 2] * r1, O[8 * kk + 3] * r1),
          pack2(O[8 * kk + 4] * r0, O[8 * kk + 5] * r0), pack2(O[8 * kk + 6] * r1, O[8 * kk + 7] * r1));
  }
}

__global__ void __cluster_dims__(2, 1, 1) __launch_bounds__(NTHREADS, 1)
fused_kernel(const Params p, const __grid_constant__ CUtensorMap mH, const __grid_constant__ CUtensorMap mWq,
             const __grid_constant__ CUtensorMap mK, const __grid_constant__ CUtensorMap mV,
             const __grid_constant__ CUtensorMap mO, const __grid_constant__ CUtensorMap mWo,
             const __grid_constant__ CUtensorMap mX, const __grid_constant__ CUtensorMap mOut,
             const __grid_constant__ CUtensorMap mWg, const __grid_constant__ CUtensorMap mWu,
             const __grid_constant__ CUtensorMap mWd, const __grid_constant__ CUtensorMap mWm,
             const __grid_constant__ CUtensorMap mWs) {
  extern __shared__ __align__(1024) uint8_t smem_raw[];
  TH(0);
  const uint32_t sb = smem_u32(smem_raw);
  const int tid = threadIdx.x;
  const int b0 = blockIdx.x;
  const int lane = tid & 31;
  const int role = __shfl_sync(0xffffffffu, tid >> 8, 0);

  if (b0 >= NMAIN) {
    const uint32_t tag = ld_relaxed(&g_epoch) + 1;
    const int sp = b0 - NMAIN, vec = 2 + sp;
    const int warp = __shfl_sync(0xffffffffu, tid >> 5, 0);
    float* sc = reinterpret_cast<float*>(smem_raw + SM_STASH);
    float* red = reinterpret_cast<float*>(smem_raw + SM_STASH + 4096);
    const int ridx = (lane >> 3) * 2 * RV + (sp & 1) * RV + 16 * RS + (sp >> 1) * 16 + (warp & 1) * 8 + (lane & 7);
    if (warp < 8) st_pkt16(&g_rec[warp >> 2][0][ridx + (warp & 2) * 16], 0, 0, 0, 0);
#pragma unroll 1
    for (int i = tid; i < 1024; i += NTHREADS) sc[i] = rbf(silu_f(__bfloat162float(p.c[i])));
    if (tid == 0) {
      tma_prefetch_desc(&mWs);
      for (int s = 0; s < NST2; s++) { mbar_init(sb + BAR_FULL2 + 8 * s, 1); mbar_init(sb + BAR_EMPTY2 + 8 * s, 8); }
      fence_async_smem();
      int it = 0;
      do { __nanosleep(100); spin_guard(it); } while (ld_pkt16(&g_lnst[8 * 32 + 16 * sp]).w != tag);
      if (SPD) __nanosleep(SPD);
    }
    __syncthreads();
    int s = 0; uint32_t ph = 0;
    if (tid == 0) TS(0);
    if (warp == 8) {
      const uint64_t pol = policy_evict_first();
#pragma unroll 1
      for (int n = 0; n < 80; n++) {
        mbar_wait_g(sb + BAR_EMPTY2 + 8 * s, ph ^ 1);
        if (elect_one()) {
          mbar_expect_tx(sb + BAR_FULL2 + 8 * s, 32768);
          if (n < 16) {
            tma_ld_hint(sb + s * ST2, &mWs, (sp & 1) * 1024 + 512 + (n >> 3) * 256 + (sp >> 1) * 128, (n & 7) * 128, sb + BAR_FULL2 + 8 * s, pol);
          } else {
#pragma unroll
            for (int j = 0; j < 4; j++) tma_ld_hint(sb + s * ST2 + j * 8192, &mWm, vec * 1024 + j * 256, (n - 16) * 16, sb + BAR_FULL2 + 8 * s, pol);
          }
        }
        __syncwarp();
        if (++s == NST2) { s = 0; ph ^= 1; }
      }
    } else if (warp < 8) {
      float acc[8];
#pragma unroll
      for (int i = 0; i < 8; i++) acc[i] = 0.f;
      auto stage = [&](uint32_t a0, int da, const float* cp, int dc) {
        mbar_wait_g(sb + BAR_FULL2 + 8 * s, ph);
#pragma unroll
        for (int i = 0; i < 8; i++) {
          const uint4 v = lds128(a0 + s * ST2 + i * da);
          const float c = cp[i * dc];
          acc[0] = fmaf(lo2f(v.x), c, acc[0]); acc[1] = fmaf(hi2f(v.x), c, acc[1]);
          acc[2] = fmaf(lo2f(v.y), c, acc[2]); acc[3] = fmaf(hi2f(v.y), c, acc[3]);
          acc[4] = fmaf(lo2f(v.z), c, acc[4]); acc[5] = fmaf(hi2f(v.z), c, acc[5]);
          acc[6] = fmaf(lo2f(v.w), c, acc[6]); acc[7] = fmaf(hi2f(v.w), c, acc[7]);
        }
        if (__shfl_sync(0xffffffffu, lane, __float_as_uint(acc[7]) & 31) < 32 && lane == 0) mbar_arrive(sb + BAR_EMPTY2 + 8 * s);
        if (++s == NST2) { s = 0; ph ^= 1; }
      };
#pragma unroll 1
      for (int n = 0; n < 16; n++) {
        stage(sb + tid * 16, 4096, sc + (n & 7) * 128 + (tid >> 4), 16);
        if ((n & 7) == 7) {
          float* r2 = red + 2048 + (n & 8) * 256;
#pragma unroll
          for (int i = 0; i < 8; i++) { r2[tid * 8 + i] = acc[i]; acc[i] = 0.f; }
          nb_sync(NB_CONS, 256);
          if (warp < 2) {
            float v0 = 0.f, v1 = 0.f;
#pragma unroll 4
            for (int i = 0; i < 16; i++) { const float2 e = reinterpret_cast<const float2*>(r2)[i * 64 + tid]; v0 += e.x; v1 += e.y; }
            publish_record(&g_rec[tag & 1][0][ridx + (n >> 3) * 32], pack2(mod_value(v0, sp & 1), mod_value(v1, sp & 1)),
                           (lane & 4) * 4 + (lane & 3), sp & 1, true);
          }
          if (tid == 0) TS(1 + (n >> 3));
        }
      }
#pragma unroll 1
      for (int n = 0; n < 64; n++) {
        stage(sb + ((tid >> 5) & 3) * 8192 + (tid >> 7) * 4096 + (tid & 31) * 16, 512, sc + n * 16 + (tid >> 7) * 8, 1);
      }
#pragma unroll
      for (int i = 0; i < 8; i++) red[(tid >> 7) * 1024 + (tid & 127) * 8 + i] = acc[i];
    }
    __syncthreads();
    float dot = 0.f;
#pragma unroll 1
    for (int i = tid; i < 512; i += NTHREADS) {
      uint32_t v = pack2(red[2 * i] + red[1024 + 2 * i], red[2 * i + 1] + red[1024 + 2 * i + 1]);
      st_pkt8(&g_mod[vec * 512 + i], v, tag);
      if (vec == 4) v = hadd2(v, ONE2);
      const uint32_t wr = reinterpret_cast<const uint32_t*>(p.w_r)[i];
      dot = fmaf(lo2f(v), lo2f(wr), fmaf(hi2f(v), hi2f(wr), dot));
    }
#pragma unroll
    for (int o = 16; o; o >>= 1) dot += __shfl_xor_sync(0xffffffffu, dot, o);
    if (lane == 0) sc[warp] = dot;
    __syncthreads();
    if (tid == 0) {
      dot = 0.f;
      for (int w = 0; w < 12; w++) dot += sc[w];
      fence_release_gpu();
      st_pkt8(&g_vdone[(vec - 2) * 16], __float_as_uint(dot), tag);
      TS(11);
#pragma unroll 1
      for (int i = 0; i < 128; i++) {
        const int u = i * 4 + (b0 - NMAIN);
        l2_prefetch(p.wo + (size_t)((4 * ((u >> 4) & 7) + (u >> 7)) * 128 + (u & 15) * 8) * 1024, 16384);
        __nanosleep(PFW);
      }
    }
    return;
  }

  const uint32_t rank = b0 & 1;
  const bool slab = !(b0 & 32), late = b0 & 16;
  const uint32_t c0 = clock();
  if (tid == 352) TS(0);
  auto load_slab = [&]() {
    const bf16* wp = p.w_mod + (size_t)(512 * rank + 2 * (tid & ~31) + 2 * (lane & 3) + ((lane >> 2) & 1)) * 6144 + 32 * (b0 >> 1) + 8 * (lane >> 3);
    const uint64_t pef = policy_evict_first();
#pragma unroll
    for (int i = 0; i < 8; i++)
      asm volatile("cp.async.cg.shared.global.L2::cache_hint [%0], [%1], 16, %2;"
        :: "r"(sb + SM_WSLAB + tid * 16 + i * 4096), "l"(wp + (size_t)i * 8 * 6144), "l"(pef) : "memory");
  };
  if (tid == 256) {
    mbar_init(sb + BAR_XH, 1);
    fence_async_smem();
    mbar_expect_tx(sb + BAR_XH, 32768);
    if (XD) while ((uint32_t)clock() - c0 < XD) {}
#pragma unroll
    for (int i = 0; i < 2; i++)
      asm volatile("cp.async.bulk.shared::cluster.global.mbarrier::complete_tx::bytes [%0], [%1], 16384, [%2];"
        :: "r"(sb + SM_XROW + i * ST1), "l"(p.x + (size_t)b0 * 16384 + i * 8192), "r"(sb + BAR_XH) : "memory");
  }
  __syncwarp();
  uint32_t cw[8];
#pragma unroll
  for (int i = 0; i < 8; i++) cw[i] = 0;
  if (!role && slab) {
#pragma unroll
    for (int i = 0; i < 8; i++) cw[i] = ld_relaxed(reinterpret_cast<const uint32_t*>(p.c) + 256 * rank + (tid & ~28) + 4 * i);
  }
  uint32_t epoch = 0;
  if (!role) epoch = ld_relaxed(&p.sc->epoch[lane]);
  if (!role && slab && !late) load_slab();
#define TILE_ROLES() \
  mbar_wait(sb + BAR_ROLE, 0); \
  const int b = 2 * __shfl_sync(0xffffffffu, lds32(sb + SM_ROLE), 0) + rank; \
  const int rt = b >> 3;     \
  const int ct = b & 7;

  if (role) {
    asm volatile("setmaxnreg.dec.sync.aligned.u32 24;");
    const int warp = __shfl_sync(0xffffffffu, tid >> 5, 0);
    if (tid == 256) {
      mbar_init(sb + BAR_RED, 1);
      for (int s = 0; s < 2; s++) mbar_init(sb + BAR_OF + 8 * s, 1);
      mbar_init(sb + BAR_ROLE, 1);
      for (int s = 0; s < 5; s++) { mbar_init(sb + BAR_FULL1 + 8 * s, 1); mbar_init(sb + BAR_EMPTY1 + 8 * s, 4); }
      for (int s = 0; s < 2; s++) { mbar_init(sb + BAR_STASH + 8 * s, 1); mbar_init(sb + BAR_X + 8 * s, 1); }
      for (int s = 0; s < 4; s++) mbar_init(sb + BAR_HS + 8 * s, 1);
      mbar_init(sb + BAR_G, 16); mbar_init(sb + BAR_T1, 1); mbar_init(sb + BAR_HF, 1);
      mbar_init(sb + BAR_SFREE, 4); mbar_init(sb + BAR_TFREE, 8);
      mbar_init(sb + BAR_FFN, 4); mbar_init(sb + BAR_FFN + 8, 2);
      mbar_init(sb + BAR_CAND, 1); mbar_init(sb + BAR_VEC, 32); for (int s = 0; s < 3; s++) mbar_init(sb + BAR_TAB + 8 * s, 32);
      mbar_expect_tx(sb + BAR_RED, 1024);
      mbar_expect_tx(sb + BAR_ROLE, 4);
      asm volatile("fence.mbarrier_init.release.cluster;" ::: "memory");
    }
    __syncwarp();
    asm volatile("barrier.cluster.arrive.relaxed.aligned;" ::: "memory");
    const int ridx = ((lane >> 1) & 3) * 2 * RV + (b0 >> 6) * RV + ((b0 >> 1) & 31) * RS + 2 * rank + (lane & 1) + (lane >> 3) * 4;
    if (warp == 11 && slab && lane < 2 * RS) { st_pkt16(&g_rec[0][0][ridx], 0, 0, 0, 0); st_pkt16(&g_rec[1][0][ridx], 0, 0, 0, 0); }
    if (tid == 256) {
      tma_prefetch_desc(&mWq); tma_prefetch_desc(&mX); tma_prefetch_desc(&mH); tma_prefetch_desc(&mK); tma_prefetch_desc(&mV); tma_prefetch_desc(&mO);
    }
    uint32_t pairid = 0;
    if (tid == 320 && rank == 0) {
      uint32_t t;
      asm("mov.u32 %0, %%smid;" : "=r"(t));
      t >>= 1;
      uint32_t grp = ((0x73216540u >> (4 * ((t < 32 ? t : t < 60 ? 1 + (t - 32) % 7 : t < 62 ? t - 54 : 0) & 7))) & 7) - 1, slot;
      int it = 0;
      do {
        grp = (grp + 1) & 7;
        asm volatile("atom.relaxed.gpu.global.add.u32 %0, [%1], 1;" : "=r"(slot) : "l"(&p.sc->ticket[grp * 32]) : "memory");
        spin_guard(it);
      } while (slot >= 8);
      pairid = slot * 8 + grp;
    }
    __syncwarp();
    asm volatile("barrier.cluster.wait.aligned;" ::: "memory");
    if (tid == 320 && rank == 0) {
#pragma unroll
      for (int r = 0; r < 2; r++)
        asm volatile("st.async.weak.shared::cluster.mbarrier::complete_tx::bytes.b32 [%0], %1, [%2];"
          :: "r"(mapa(sb + SM_ROLE, r)), "r"(pairid), "r"(mapa(sb + BAR_ROLE, r)) : "memory");
    }
    __syncwarp();
    const uint32_t tag = ld_relaxed(&g_epoch) + 1;
    if (warp == 8) {
      TILE_ROLES();
      const int kvrow = (ct >> 1) * 2048 + 1536, arow = rt * 128 + rank * 64;
      const uint64_t pef = policy_evict_first();
#pragma unroll 1
      for (int pair = 0; pair < 2; pair++) {
        const int wblk = (4 * ct + 2 * pair) * 2;
        if (pair) { mbar_wait_g(sb + BAR_HF, 0); fence_async_global(); }
#pragma unroll 1
        for (int n = 0; n < 16; n++) {
          const uint32_t s = n & 3, st = sb + SM_RING + s * ST1, fb = sb + BAR_FULL1 + 8 * s;
          if (n == 2 && pair == 0) mbar_wait_g(sb + BAR_G, 0);
          mbar_wait_g(fb + (BAR_EMPTY1 - BAR_FULL1), ((n >> 2) & 1) ^ 1);
          if (elect_one()) {
            mbar_expect_tx(fb, 49152);
            if (pair) tma_ld_mc_hint(st + rank * 8192, &mH, n * 64, arow, fb, pef); else
            tma_ld_mc(st + rank * 8192, pair ? &mH : &mX, n * 64, arow, fb);
            tma_ld3_hint(st + 16384, &mWq, n * 64, wblk, fb, pef);
          }
          __syncwarp();
        }
#pragma unroll 1
        for (int n = 0; n < 16; n++) {
          const uint32_t s = n & 3, st = sb + SM_RING + s * ST1 + rank * 8192, fb = sb + BAR_FULL1 + 8 * s;
          const int h0 = n == 0 ? 0 : n == 15 ? 14 : n + 1, h1 = n == 0 ? 1 : n == 15 ? 15 : n - 1;
          mbar_wait_g(fb + (BAR_EMPTY1 - BAR_FULL1), ((n >> 2) & 1) ^ 1);
          if (elect_one()) {
            mbar_expect_tx(fb, 32768);
            tma_ld_mc(st, n == 15 ? &mV : &mK, rank * 64, kvrow + (h0 & 7) * 64, fb);
            tma_ld_mc(st + 16384, n == 0 ? &mK : &mV, rank * 64, kvrow + (h1 & 7) * 64, fb);
            if (n == 3 && pair == 1) mbar_arrive(sb + BAR_T1);
          }
          __syncwarp();
        }
      }
      {
        uint32_t s = 0, ph = 1;
#pragma unroll 1
        for (int half = 0; half < 2; half++) {
          mbar_wait_g(sb + BAR_OF + 8 * half, 0);
          fence_async_global();
#pragma unroll 1
          for (int n = 32 * half; n < 32 * half + 32; n++) {
            const uint32_t st = sb + SM_RING + s * ST1, fb = sb + BAR_FULL1 + 8 * s;
            const int k0 = ((n & 14) * 2 + (n >> 4)) * 128 + (n & 1) * 64;
            mbar_wait_g(n == 8 ? sb + BAR_SFREE : fb + (BAR_EMPTY1 - BAR_FULL1), n == 8 ? 0 : ph ^ (s >> 2));
            if (elect_one()) {
              mbar_expect_tx(fb, 32768);
              tma_ld_mc_hint(st + rank * 8192, &mO, k0, arow, fb, pef);
              tma_ld3_hint(st + 16384, &mWo, k0, 2 * ct, fb, pef);
            }
            __syncwarp();
            if (++s == 5 || n == 3) { s = 0; ph ^= 1; }
          }
        }
        if (b < NFFN) {
#pragma unroll 1
          for (s = 0; s < 2; s++) {
            mbar_wait_g(sb + BAR_EMPTY1 + 8 * s, 0);
            if (elect_one()) {
              mbar_expect_tx(sb + BAR_FFN + 8, 32768);
              tma_ld3_hint(sb + SM_RING + s * ST1, &mWd, b * 32, s * 8, sb + BAR_FFN + 8, pef);
            }
            __syncwarp();
          }
        }
      }
    } else if (warp <= 10) {
      const int w = warp - 9;
      TILE_ROLES();
      const uint32_t st = sb + SM_STASH + w * 16384;
#pragma unroll 1
      for (int j = 0; j < 2; j++) {
        nb_sync(NB_OST + w, 160);
        if (elect_one()) {
          fence_async_smem();
          tma_st(&mH, (2 * ct + j) * 64, rt * 128 + w * 64, st + 4096);
          bulk_commit();
          bulk_wait_read();
          mbar_arrive(sb + BAR_HS + 16 * w + 8 * j);
          if (j) {
            bulk_wait_all();
            fence_async_global();
            fence_release_gpu();
            red_add_relaxed(&g_hflag[rt * 32], 1);
          }
        }
        __syncwarp();
      }
#pragma unroll 1
      for (int r = 0; r < 4; r++) {
        nb_sync(NB_OST + w, 160);
        if (elect_one()) {
          fence_async_smem();
          const int hcol = (4 * ct + r) * 128;
          tma_st(&mO, hcol, rt * 128 + w * 64, st);
          tma_st(&mO, hcol + 64, rt * 128 + w * 64, st + 8192);
          bulk_commit();
          bulk_wait_read();
          if (r < 2) {
            mbar_arrive(sb + BAR_STASH + 8 * w);
          } else if (r == 2) {
            mbar_expect_tx(sb + BAR_X + 8 * w, 16384);
            tma_ld_hint(st, &mX, ct * 128, rt * 128 + w * 64, sb + BAR_X + 8 * w, policy_evict_first());
            tma_ld_hint(st + 8192, &mX, ct * 128 + 64, rt * 128 + w * 64, sb + BAR_X + 8 * w, policy_evict_first());
          } else {
            mbar_arrive_cl(mapa(sb + BAR_SFREE, 0)); mbar_arrive_cl(mapa(sb + BAR_SFREE, 1));
          }
          bulk_wait_all();
          fence_async_global();
          fence_release_gpu();
          red_add_relaxed(&g_oflag[(rt * 4 + r) * 32], 1);
        }
        __syncwarp();
      }
      nb_sync(NB_OST + w, 160);
      int skip = -1;
      mbar_wait_g(sb + BAR_CAND, 0);
      const bool has_cand = (lds32(sb + SM_CAND) >> 6) == w;
      if (has_cand) {
        nb_sync(NB_WIN + w, 160);
        skip = (int)lds32(sb + SM_WROW + 4 * w) - (rt * 128 + w * 64);
      }
      if ((unsigned)skip >= 64u) {
        if (elect_one()) {
          fence_async_smem();
          tma_st(&mOut, ct * 128, rt * 128 + w * 64, sb + SM_OUT + w * 16384);
          tma_st(&mOut, ct * 128 + 64, rt * 128 + w * 64, sb + SM_OUT + w * 16384 + 8192);
          bulk_commit();
          bulk_wait_read();
        }
        __syncwarp();
      } else {
        uint4* dst = reinterpret_cast<uint4*>(p.out + (size_t)(rt * 128 + w * 64 + (lane >> 4)) * 1024 + ct * 128) + (lane & 15);
#pragma unroll 2
        for (int r = lane >> 4; r < 64; r += 2) {
          const uint4 v = lds128(sb + SM_OUT + w * 16384 + ((lane >> 3) & 1) * 8192 + r * 128 + (((lane ^ r) & 7) * 16));
          if (r != skip) *dst = v;
          dst += 256;
        }
      }
      if (!has_cand) nb_sync(NB_WIN + w, 160);
    } else {
      if (slab) {
        mbar_wait_g(sb + BAR_RED, 0);
        float v = 0.f;
#pragma unroll
        for (int w = 0; w < 8; w++) v += lds_f32(sb + SM_RED + w * 128 + lane * 4);
        v += __shfl_xor_sync(0xffffffffu, v, 16);
        v = mod_value(v, b0 >> 6);
        publish_record(&g_rec[tag & 1][0][ridx], pack2(v, __shfl_down_sync(0xffffffffu, v, 1)), 2 * (lane & 1), b0 >> 6, lane < 8);
        if (lane == 0) TS(1);
      }
      mbar_wait_g(sb + BAR_G, 0);
#pragma unroll 1
      for (int i = 1; i < 4; i++) {
        const uint4* mp = &g_rec[tag & 1][(b0 >> 1) & (NREP - 1)][i == 1 ? (8 + (lane >> 2)) * RS + (lane & 3) : 16 * RS - 64 + 32 * i + lane];
        uint4 v0, v1; int it = 0;
        while (true) {
          v0 = ld_pkt16(mp); v1 = ld_pkt16(mp + RV);
          if (v0.x != 0 && v1.x != 0) break;
          spin_guard(it); __nanosleep(PLD);
        }
        put_record(sb, 32 * i + lane, v0);
        put_record(sb, 128 + 32 * i + lane, v1);
        mbar_arrive(sb + BAR_TAB - 8 + 8 * i);
        if (lane == 0) {
          TS(3 + i + (i > 2));
          if (i == 1) l2_prefetch(((b0 & 64) ? p.vc : p.kc) + (size_t)(((b0 >> 4) & 3) * 2048 + 1536) * 128 + (b0 & 15) * 4096, 8192);
        }
        __syncwarp();
      }
      TILE_ROLES();
      if (lane == 0) {
        int it = 0;
        do { __nanosleep(500); spin_guard(it); } while (ld_relaxed(&g_hflag[rt * 32]) != tag * 16u);
        fence_acquire_gpu();
        mbar_arrive(sb + BAR_HF);
        if (b < NFFN) for (int i = 0; i < 8; i++) { __nanosleep(800); l2_prefetch(p.wd + (size_t)(b * 32 + i * 4) * 1024, 8192); }
      }
      __syncwarp();
      {
        uint2 v; int it = 0;
        do { __nanosleep(1000); v = ld_pkt8(&g_vdone[(lane & 3) * 16]); spin_guard(it); }
        while (!(v.y == tag));
        __syncwarp();
        fence_acquire_gpu();
        if (lane == 1 || lane == 2) sts32(sb + SM_SCAL + (2 - lane) * 4, v.x);
      }
#pragma unroll 1
      for (int i = 0; i < 2; i++) {
        const int q = i * 32 + lane, pi = ct * 64 + q;
        const uint32_t vga = g_mod[2 * 512 + pi].x, vsb = g_mod[3 * 512 + pi].x, vcb = g_mod[4 * 512 + pi].x, vgb = g_mod[5 * 512 + pi].x;
        const uint32_t wr = reinterpret_cast<const uint32_t*>(p.w_r)[pi];
        const uint32_t c1 = hadd2(vcb, ONE2);
        const float al = lo2f(c1) * lo2f(wr), ah = hi2f(c1) * hi2f(wr);
        const uint32_t o8 = (q & 3) * 8 + ((q >> 2) & 1) * 4;
        sts32(sb + SM_GA + (q >> 3) * 32 + o8, vga);
        sts128(sb + SM_REC + q * 16, c1, vsb, vgb, 0);
        const uint32_t ahi = pack2(al, ah), alo = pack2(al - lo2f(ahi), ah - hi2f(ahi));
        const uint32_t ba = sb + SM_B1 + (q >> 3) * 128 + o8;
        sts32(ba, ONE2); sts32(ba + 32, ahi); sts32(ba + 64, alo); sts32(ba + 96, 0);
      }
      if (lane == 0) TS(28);
      if (lane == 0) {
        tma_prefetch_desc(&mWo); tma_prefetch_desc(&mOut); tma_prefetch_desc(&mWd); tma_prefetch_desc(&mWg); tma_prefetch_desc(&mWu);
#pragma unroll 1
        for (int r = 0; r < 4; r++) {
          int it = 0;
          do { __nanosleep(200); spin_guard(it); } while (ld_relaxed(&g_oflag[(rt * 4 + r) * 32]) != tag * 16u);
          if (r & 1) { fence_acquire_gpu(); mbar_arrive(sb + BAR_OF + 8 * (r >> 1)); }
          if (r == 1 && b < NFFN) {
            const uint64_t pef = policy_evict_first();
            mbar_wait_g(sb + BAR_T1, 0);
#pragma unroll 1
            for (int i = 0; i < 4; i++) {
              mbar_expect_tx(sb + BAR_FFN, 16384);
              tma_ld_hint(sb + SM_RING + i * ST1 + 32768, &mWg, b * 32, i * 256, sb + BAR_FFN, pef);
              __nanosleep(GATED);
            }
          }
        }
      }
      __syncwarp();
      if (b < NFFN) {
        mbar_wait_g(sb + BAR_TFREE, 0);
        const uint64_t pef = policy_evict_first();
#pragma unroll 1
        for (int i = 0; i < 5; i++) {
          if (i > 0 && lane == 0) {
            mbar_expect_tx(sb + BAR_FFN, 16384);
            tma_ld_hint(sb + SM_RING + (i - 1) * ST1 + 32768, &mWu, b * 32, (i - 1) * 256, sb + BAR_FFN, pef);
          }
          if (i < 4) {
#pragma unroll 1
            for (int j = 0; j < 8; j++) {
              asm volatile("prefetch.global.L2 [%0];" :: "l"(p.wu + (size_t)(i * 256 + j * 32 + lane) * 3584 + b * 32) : "memory");
              __nanosleep(UPD);
            }
            __nanosleep(500);
          }
        }
      }
      if (lane == 0) TS(29);
#pragma unroll 1
      for (int i = lane; i < 128; i += 32) st_pkt16(&g_stats[b * 128 + i], 0, 0, 0, 0);
      st_pkt16(&g_cand[b * 32 + lane], 0, 0, 0, 0);
      if (lane < ESTR) st_pkt16(&g_entry[(ct * 16 + rt) * ESTR + lane], 0, 0, 0, 0);
#pragma unroll 1
      for (int i = lane; i < (b < NFFN ? 512 : 0); i += 32) st_pkt16(&g_ypart[((i >> 2) * NFFN + b) * 4 + (i & 3)], 0, 0, 0, 0);
      mbar_arrive(sb + BAR_VEC);
      uint4* const cp = &g_cand[b * 32 + lane];
      uint4* const ep = &g_entry[(ct * 16 + rt) * ESTR];
      nb_sync(NB_AMAX, 288);
      const uint4 e = lds128(sb + SM_AMAX + (lane & 7) * 16);
      const int tmax = __reduce_max_sync(0xffffffffu, (int)e.x);
      const int wl = __ffs(__ballot_sync(0xffffffffu, (int)e.x == tmax)) - 1;
      const uint32_t row = __shfl_sync(0xffffffffu, e.y, wl);
      const uint32_t xa = sb + SM_X2 + (row >> 6) * 16384 + (lane >> 4) * 8192 + (row & 63) * 128 + (lane & 3) * 4
                        + ((((lane >> 1) & 6) ^ (row & 7)) * 16);
      const uint32_t v0 = lds32(xa), v1 = lds32(xa ^ 16);
      if (lane == wl) st_pkt16(ep, e.w, rt * 128 + row, e.z, tag);
      st_pkt16(cp, v0, v1, tag, 0);
      if (lane == 0) { sts32(sb + SM_CAND, row); mbar_arrive(sb + BAR_CAND); }
      if (lane == 0) TS(15);
    }
  } else {
    const int warp = tid >> 5;
    const int wg = warp >> 2, wq = warp & 3;
    const int g = lane >> 2, t = lane & 3;
    uint32_t tag;
    uint32_t ln[4];
    float acc[128];
    uint32_t bf[16];
    auto gemv = [&]() {
          asm volatile("cp.async.wait_all;" ::: "memory");
          float d0[4] = {0.f, 0.f, 0.f, 0.f}, d1[4] = {0.f, 0.f, 0.f, 0.f};
#pragma unroll
          for (int i = 0; i < 8; i++) {
            const uint4 wv = lds128(sb + SM_WSLAB + tid * 16 + i * 4096);
            const uint32_t a[4] = {wv.x, wv.y, wv.z, wv.w};
            mma16816((i & 1) ? d1 : d0, a, bf[2 * i], bf[2 * i + 1]);
          }
#pragma unroll
          for (int i = 0; i < 4; i++) { d0[i] += d1[i]; d0[i] += __shfl_xor_sync(0xffffffffu, d0[i], 6); }
          const uint32_t dst = mapa(sb + SM_MISC, t & 1) - SM_MISC;
          if (!(lane & 6)) st_async_f32x4(dst + SM_RED + warp * 128 + rank * 64 + g * 8, d0, dst + BAR_RED);
          TH(4);
    };
    {
      asm volatile("barrier.cluster.arrive.relaxed.aligned;" ::: "memory");
      if (lane == 0) st_pkt16(&g_lnst[8 * b0 + warp], 0, 0, 0, 0);
      TH(1);
      asm volatile("setmaxnreg.inc.sync.aligned.u32 240;");
      TH(2);
#pragma unroll
      for (int i = 0; i < 8; i++) {
        const float sv = silu_f((g & 4) ? hi2f(cw[i]) : lo2f(cw[i]));
        const uint32_t sp = (g & 1) ? pack2(0.f, sv) : pack2(sv, 0.f);
        bf[2 * i] = (g & 2) ? 0 : sp; bf[2 * i + 1] = (g & 2) ? sp : 0;
      }
      asm volatile("barrier.cluster.wait.aligned;" ::: "memory");
#pragma unroll
      for (int i = 0; i < 128; i++) acc[i] = 0.f;
      reg_fence<128>(acc);
      tag = __shfl_sync(0xffffffffu, epoch, 0) + 1;
      if (slab && late) { while ((uint32_t)clock() - c0 < WL) {} load_slab(); }
      TH(3);
      if (slab && !late) gemv();
      {
        {
          mbar_wait(sb + BAR_XH, 0);
          TH(5);
          float ds[4] = {0.f, 0.f, 0.f, 0.f}, dq[4][4];
#pragma unroll
          for (int i = 0; i < 4; i++) { dq[i][0] = dq[i][1] = dq[i][2] = dq[i][3] = 0.f; }
#pragma unroll
          for (int i = 0; i < 8; i++) {
            uint32_t a[4];
            ldsm4(sb + SM_XROW + wg * ST1 + wq * 4096 + ((lane >> 3) & 1) * 2048 + i * 256 + (lane >> 4) * 128 + (lane & 7) * 16, a);
            mma16816(ds, a, ONE2, ONE2);
            mma1688(dq[0], a[0], a[1], a[0]); mma1688(dq[1], a[0], a[1], a[1]);
            mma1688(dq[2], a[2], a[3], a[2]); mma1688(dq[3], a[2], a[3], a[3]);
          }
          const bool dg = t == (g >> 1);
          const float q0 = dg ? ((g & 1) ? dq[0][1] + dq[2][1] : dq[0][0] + dq[2][0]) : 0.f;
          const float q1 = dg ? ((g & 1) ? dq[1][3] + dq[3][3] : dq[1][2] + dq[3][2]) : 0.f;
          float q = ((lane & 1) ? q1 : q0) + __shfl_xor_sync(0xffffffffu, (lane & 1) ? q0 : q1, 1);
          float sm = (lane & 1) ? ds[2] : ds[0];
          q += __shfl_xor_sync(0xffffffffu, q, 2);
#pragma unroll
          for (int o = 4; o <= 16; o <<= 1) { q += __shfl_xor_sync(0xffffffffu, q, o); sm += __shfl_xor_sync(0xffffffffu, sm, o); }
          const float mean = sm * (1.f / 1024.f);
          const float rd = rcp_f(rbf(sqrt_f(rbf(rbf(fmaxf(fmaf(-mean, mean, q * (1.f / 1024.f)), 0.f)) + 1e-5f))));
          const float mean1 = __shfl_sync(0xffffffffu, mean, 1), rd1 = __shfl_sync(0xffffffffu, rd, 1);
          const uint32_t rh = pack2(rd, rd1);
          if (lane == 0) st_pkt16(&g_lnst[8 * b0 + warp], pack2(-rbf(mean) * lo2f(rh), -rbf(mean1) * hi2f(rh)), rh, 0, tag);
          TH(6);
          if (tid == 0) TS(2);
        }
      }
    }
    if (slab && late) gemv();
    TILE_ROLES();
    const uint32_t xa0 = sb + SM_RING + (warp * 16 + (lane & 15)) * 128 + (((lane >> 4) ^ (lane & 7)) * 16);
    uint32_t V[16];
    {
      const uint4* mp = &g_rec[tag & 1][(b0 >> 1) & (NREP - 1)][RV * wg + (lane >> 2) * RS + (lane & 3)];
      const uint4* lp = &g_lnst[(8 * rt + warp) * 8 + (g >> 1)];
      mbar_wait(sb + BAR_FULL1, 0);
#pragma unroll
      for (int kk = 0; kk < 4; kk++) ldsm4(xa0 ^ (kk * 32), V + 4 * kk);
      uint4 v0 = make_uint4(1, 0, 0, 0), l0, l1;
      int it = 0;
      do { if (wq == 0) v0 = ld_pkt16(mp);
           l0 = ld_pkt16(lp); l1 = ld_pkt16(lp + 4); spin_guard(it); }
        while (!(__all_sync(0xffffffffu, v0.x != 0 && l0.w == tag && l1.w == tag)));
      TH(7);
      if (wq == 0) put_record(sb, 128 * wg + lane, v0);
      const uint32_t sel = (g & 1) ? 0x3232 : 0x1010;
      ln[0] = __byte_perm(l0.x, 0, sel); ln[1] = __byte_perm(l0.y, 0, sel);
      ln[2] = __byte_perm(l1.x, 0, sel); ln[3] = __byte_perm(l1.y, 0, sel);
      __syncwarp();
      if (lane < 2) mbar_arrive_cl(mapa(sb + BAR_G, lane));
      nb_sync(NB_CONS, 256);
      if (tid == 0) TS(3);
      TH(13);
    }

    const uint32_t rel = mapa(sb + SM_MISC, lane & 1) - SM_MISC;
    const uint32_t stsm_addr = sb + SM_STASH + wg * 16384 + (wq * 16 + (lane & 15)) * 128 + (((lane >> 4) ^ (lane & 7)) * 16);

    uint32_t ph = 0;
    uint32_t X[32];
    {
      const uint32_t tab0 = sb + SM_STASH + wg * 16384 + t * 16;
      const uint64_t db0 = mk_desc(sb + SM_RING + 16384, 8192);
      uint32_t A[2][16];
      uint32_t xa[4];
#pragma unroll
      for (int kk = 0; kk < 4; kk++) xa[kk] = xa0 ^ (kk * 32);
      uint32_t tab = tab0;
      reg_fence<4>(xa);
      asm volatile("{\n.reg .pred p;\nsetp.eq.u32 p, %4, 0;\n@p ld.shared.v4.u32 {%0,%1,%2,%3}, [%5];\n}"
        : "+r"(ln[2]), "+r"(ln[0]), "+r"(ln[3]), "+r"(ln[1]) : "r"(tag), "r"(sb));
      int hs = 2 * ct;
      uint4 R[4];
#pragma unroll
      for (int kk = 0; kk < 4; kk++) R[kk] = lds128(tab + (kk >> 1) * 2048 + (kk & 1) * 64);
#pragma unroll 1
      for (int k4 = 0; k4 < 4; k4++) {
#pragma unroll
        for (int s = 0; s < 4; s++) {
          uint32_t* a = A[s & 1];
          const int sn = (s + 1) & 3;
          const uint32_t pn = (k4 + (s == 3)) & 1;
          modulate_frags(a, V, R, ln);
          if (hs == (s & 2)) {
            if (s & 1) mbar_wait(sb + BAR_HS + 16 * wg, 0);
#pragma unroll
            for (int kk = 0; kk < 4; kk++) stsm4((stsm_addr + 4096) ^ (kk * 32), a[4 * kk], a[4 * kk + 1], a[4 * kk + 2], a[4 * kk + 3]);
            nb_arrive(NB_OST + wg, 160);
          }
          if (s == 0 && k4 == 0) TH(8);
          if (s == 0 && k4 == 0 && tid == 0) { TS(6); TSC(61); }
          wg_fence();
#pragma unroll
          for (int kk = 0; kk < 4; kk++) wgmma_rs256<1>(acc, a + 4 * kk, db0 + s * (ST1 >> 4) + kk * 128);
          wg_commit();
          if (s == 3 && k4 < 3) mbar_wait(sb + BAR_TAB + 8 * k4, 0);
#pragma unroll
          for (int kk = 0; kk < 4; kk++) R[kk] = lds128(tab + (s + 1) * 128 + (kk >> 1) * 2048 + (kk & 1) * 64);
          wg_wait<1>();
          if (k4 == 0) TH(9 + s);
          reg_fence<16>(A[(s & 1) ^ 1]);
          if ((tid & 127) < 2 && (s | k4)) mbar_arrive_cl(rel + BAR_EMPTY1 + 8 * ((s + 3) & 3));
          if (s < 3 || k4 < 3) {
            mbar_wait(sb + BAR_FULL1 + 8 * sn, pn);
#pragma unroll
            for (int kk = 0; kk < 4; kk++) ldsm4(xa[kk] + sn * ST1, V + 4 * kk);
          }
        }
        tab += 512; hs -= 4;
      }
      mbar_wait(sb + BAR_HS + 16 * wg + 8, 0);
      wg_wait<0>();
      reg_fence<128>(acc);
    }
#pragma unroll 1
    for (int pair = 0; pair < 2; pair++) {
      uint32_t Q[32];
      TR(0);
      {
        if ((tid & 127) < 2) mbar_arrive_cl(rel + BAR_EMPTY1 + 8 * 3);
        if (pair == 1) mbar_wait(sb + BAR_STASH + 8 * wg, 1);
#pragma unroll
        for (int i = 0; i < 32; i++) Q[i] = pack2(acc[2 * i], acc[2 * i + 1]);
        const uint32_t qs = sb + SM_STASH + wg * 16384 + wq * 2048 + lane * 16;
#pragma unroll
        for (int i = 0; i < 8; i++)
          sts128(qs + (i & 3) * 512 + (i >> 2) * 8192, pack2(acc[64 + 8 * i], acc[65 + 8 * i]), pack2(acc[66 + 8 * i], acc[67 + 8 * i]),
                 pack2(acc[68 + 8 * i], acc[69 + 8 * i]), pack2(acc[70 + 8 * i], acc[71 + 8 * i]));
      }
      if (tid == 0) TS(8 + pair * 2);
      TR(1);
      float O[64], SL[32], SH[32];
      uint32_t PL[16], PH[16];
      SoftmaxState z;
      const uint64_t d0 = mk_desc(sb + SM_RING, 8192);
      {
        mbar_wait(sb + BAR_FULL1, ph);
        wg_fence();
        issue_qk(SL, Q, d0);
        wg_commit();
        issue_qk(SH, Q, d0 + 1024);
        wg_commit();
#pragma unroll
        for (int i = 0; i < 64; i++) O[i] = 0.f;
        reg_fence<64>(O);
        wg_wait<1>();
        reg_fence<32>(SL);
        softmax_start(z);
        softmax_half(SL, PL, O, z, true, tag);
        wg_wait<0>();
        reg_fence<32>(SH);
        if ((tid & 127) < 2) mbar_arrive_cl(rel + BAR_EMPTY1);
      }
      float lp0 = 0.f, lp1 = 0.f;
      uint32_t dB = (uint32_t)d0 + 1 * (ST1 >> 4), dA = (uint32_t)d0 + 2 * (ST1 >> 4);
      const uint32_t dBx = dB ^ ((uint32_t)d0 + 3 * (ST1 >> 4)), dAx = dA ^ (uint32_t)d0;
      uint32_t so = 0;
      bool ready = false;
#pragma unroll 1
      for (int i = 0; i < 7; i++) {
        TA(0);
        TR(2 + i);
        if (!ready) mbar_wait(sb + BAR_FULL1 + 8 + so, ph);
        TA(1);
        TA(2);
        wg_fence();
        issue_qk(SL, Q, (d0 & 0xffffffff00000000ull) | dB);
        if (i == 4) {
          __syncwarp();
          stage_o(O, lp0, lp1, stsm_addr);
        }
        wg_fence();
        issue_pv(O, PL, ((d0 & 0xffffffff00000000ull) | dB) + 1024, i != 4);
        wg_commit();
        if (i == 4) {
          nb_arrive(NB_OST + wg, 160);
        }
        TA(3);
        ph ^= i & 1;
        ready = mbar_test(sb + BAR_FULL1 + 16 - so, ph);
        softmax_half(SH, PH, O, z, false, tag);
        TA(4);
        wg_wait<0>();
        TA(5);
        reg_fence<32>(SL); reg_fence<16>(PL);
        if ((tid & 127) < 2) mbar_arrive_cl(rel + BAR_EMPTY1 + 8 + so);
        if (!ready) mbar_wait(sb + BAR_FULL1 + 16 - so, ph);
        TA(6);
        wg_fence();
        issue_qk(SH, Q, (d0 & 0xffffffff00000000ull) | dA);
        wg_commit();
        issue_pv(O, PH, ((d0 & 0xffffffff00000000ull) | dA) + 1024, 1);
        wg_commit();
        if (i == 2) {
          wg_wait<1>();
          reg_fence<32>(Q);
          const uint32_t qs = sb + SM_STASH + wg * 16384 + wq * 2048 + lane * 16;
#pragma unroll
          for (int j = 0; j < 8; j++) { const uint4 v = lds128(qs + (j & 3) * 512 + (j >> 2) * 8192); Q[4 * j] = v.x; Q[4 * j + 1] = v.y; Q[4 * j + 2] = v.z; Q[4 * j + 3] = v.w; }
        }
        TA(10);
        if (i == 3) { lp0 = z.l0; lp1 = z.l1; row_rcp(lp0, lp1); softmax_start(z); }
        TA(7);
        so ^= 16; dB ^= dBx; dA ^= dAx;
        ready = mbar_test(sb + BAR_FULL1 + 8 + so, ph);
        softmax_half(SL, PL, O, z, i == 3, tag);
        TA(8);
        wg_wait<0>();
        TA(9);
        reg_fence<32>(SH); reg_fence<16>(PH); reg_fence<64>(O); reg_fence<32>(Q);
        if ((tid & 127) < 2) mbar_arrive_cl(rel + BAR_EMPTY1 + so);
      }
      TAFLUSH();
      TR(9);
      {
        if (!ready) mbar_wait(sb + BAR_FULL1 + 8 * 3, ph);
        ph ^= 1;
        const uint64_t dv = d0 + 3 * (ST1 >> 4);
        wg_fence();
        issue_pv(O, PL, dv, 1);
        wg_commit();
        bb_fence(tag);
        softmax_half(SH, PH, O, z, false, tag);
        wg_fence();
        issue_pv(O, PH, dv + 1024, 1);
        wg_commit();
        TR(10);
        row_rcp(z.l0, z.l1);
        mbar_wait(sb + (pair ? BAR_X : BAR_STASH) + 8 * wg, 0);
#pragma unroll
        for (int kk = 0; kk < 8; kk++) ldsm4((stsm_addr + (kk >> 2) * 8192) ^ ((kk & 3) * 32), X + 4 * kk);
        reg_fence<32>(X);
        __syncwarp();
        wg_wait<0>();
        reg_fence<64>(O);
        TR(11);
        if ((tid & 127) < 2) mbar_arrive_cl(rel + BAR_EMPTY1 + 8 * 3);
        stage_o(O, z.l0, z.l1, stsm_addr);
        nb_arrive(NB_OST + wg, 160);
      }
      TR(12);
      if (tid == 0) { TS(9 + pair * 2); TSC(62); }
      if (pair == 1) break;
      {
        mbar_wait(sb + BAR_FULL1, ph);
        const uint64_t da = mk_desc(sb + SM_RING + wg * 8192, 16), db = mk_desc(sb + SM_RING + 16384, 8192);
        wg_fence();
        wgmma_ss256_z<1>(acc, da, db);
#pragma unroll
        for (int kk = 1; kk < 4; kk++) wgmma_ss256<1>(acc, da + kk * 2, db + kk * 128, 1);
        wg_commit();
      }
#pragma unroll 1
      for (int kt = 1; kt < 16; kt++) {
        const uint32_t s = kt & 3;
        if (s == 0) ph ^= 1;
        mbar_wait(sb + BAR_FULL1 + 8 * s, ph);
        const uint32_t st = sb + SM_RING + s * ST1;
        const uint64_t da = mk_desc(st + wg * 8192, 16), db = mk_desc(st + 16384, 8192);
        wg_fence();
#pragma unroll
        for (int kk = 0; kk < 4; kk++) wgmma_ss256<1>(acc, da + kk * 2, db + kk * 128, 1);
        wg_commit();
        wg_wait<1>();
        if ((tid & 127) < 2) mbar_arrive_cl(rel + BAR_EMPTY1 + 8 * ((s + 3) & 3));
      }
      ph ^= 1;
      wg_wait<0>();
      reg_fence<128>(acc);
      TR(13);
    }

    uint4 WG[16], WU[16];
    const int fp = 64 * warp + 8 * g + t;
    uint32_t fsb0, fsb1, fcb0, fcb1, fgb0, fgb1;
    const uint32_t gu_base = sb + SM_RING + (warp >> 1) * ST1 + 32768 + (warp & 1) * 8192;
    const uint32_t gu_addr = gu_base + t * 128 + (g & 1) * 64 + ((g >> 1) ^ t) * 16;
    {
      const uint64_t da0 = mk_desc(sb + SM_RING + __shfl_sync(0xffffffffu, wg, 0) * 8192, 16), db0 = mk_desc(sb + SM_RING + 16384, 8192);
#pragma unroll
      for (int n = 0; n < 4 + 5 * X_PEEL; n++) {
        const int s = n < 4 ? n : (n - 4) % 5;
        mbar_wait(sb + BAR_FULL1 + 8 * s, n < 4 ? 0 : ((n - 4) / 5 + (s < 4)) & 1);
        if (n < 4) TSX(40 + wg * 6 + n);
        const uint64_t da = da0 + s * (ST1 >> 4), db = db0 + s * (ST1 >> 4);
        wg_fence();
        if (n == 0) wgmma_ss128_z<1>(acc, da, db); else wgmma_ss128<1>(acc, da, db, 1);
#pragma unroll
        for (int kk = 1; kk < 4; kk++) wgmma_ss128<1>(acc, da + kk * 2, db + kk * 128, 1);
        wg_commit();
        if (n == 1) {
          mbar_wait(sb + BAR_OF, 0);
          const uint2* mp = &g_mod[3 * 512 + fp];
          fsb0 = ld_pkt8(mp).x; fsb1 = ld_pkt8(mp + 4).x; fcb0 = ld_pkt8(mp + 512).x; fcb1 = ld_pkt8(mp + 516).x;
          fgb0 = ld_pkt8(mp + 1024).x; fgb1 = ld_pkt8(mp + 1028).x;
        }
        if (n == 0 && b < NFFN) mbar_wait(sb + BAR_FFN, 0);
        {
          constexpr int NT = 4 + 5 * X_PEEL, F0 = NT > 16 ? NT - 16 : 0;
#pragma unroll
          for (int i = 0; i < 16; i++) if (F0 + i * (NT - F0) / 16 == n) WG[i] = lds128(gu_addr + i * 512);
        }
        if (n > 0) {
          wg_wait<1>();
          if ((tid & 127) < 2) mbar_arrive_cl(rel + BAR_EMPTY1 + 8 * (n == 4 ? 3 : s ? s - 1 : 4));
        }
      }
      TSX(44 + wg * 6);
      {
        uint32_t dep = 0;
#pragma unroll
        for (int i = 0; i < 16; i++) dep ^= WG[i].x;
        if (__shfl_sync(0xffffffffu, tag, dep & 31) == tag && lane == 2) mbar_arrive(sb + BAR_TFREE);
      }
#pragma unroll 1
      for (int r = X_PEEL; r < 12; r++) {
#pragma unroll
        for (int s = 0; s < 5; s++) {
          mbar_wait(sb + BAR_FULL1 + 8 * s, (r + (s < 4)) & 1);
          const uint64_t da = da0 + s * (ST1 >> 4), db = db0 + s * (ST1 >> 4);
          wg_fence();
#pragma unroll
          for (int kk = 0; kk < 4; kk++) wgmma_ss128<1>(acc, da + kk * 2, db + kk * 128, 1);
          wg_commit();
          wg_wait<1>();
          if ((tid & 127) < 2) mbar_arrive_cl(rel + BAR_EMPTY1 + 8 * (s ? s - 1 : (r == 0 ? 3 : 4)));
        }
      }
    }
    mbar_wait(sb + BAR_VEC, 0);
    const int lrow = warp * 16 + g;
    uint2 ga[8], b1[8];
#pragma unroll
    for (int kk = 0; kk < 8; kk++) { ga[kk] = lds64(sb + SM_GA + kk * 32 + t * 8); b1[kk] = lds64(sb + SM_B1 + min(g, 3) * 32 + t * 8 + kk * 128); }
    uint4* const stp = &g_stats[b * 128 + lrow + 8 * t];
    bb_fence(tag);
    wg_wait<0>();
    reg_fence<64>(acc);
    if (tid == 0) { TS(12); TSC(63); }

    TT(0);
    {
      float d1[4] = {0.f, 0.f, 0.f, 0.f}, d2[4] = {0.f, 0.f, 0.f, 0.f}, d3[4] = {0.f, 0.f, 0.f, 0.f};
      float d4[4] = {0.f, 0.f, 0.f, 0.f}, d5[4] = {0.f, 0.f, 0.f, 0.f};
#pragma unroll
      for (int kk = 0; kk < 8; kk++) {
        uint32_t* x = X + 4 * kk;
        x[0] = hfma2(ga[kk].x, pack2(acc[8 * kk + 0], acc[8 * kk + 1]), x[0]);
        x[1] = hfma2(ga[kk].x, pack2(acc[8 * kk + 2], acc[8 * kk + 3]), x[1]);
        x[2] = hfma2(ga[kk].y, pack2(acc[8 * kk + 4], acc[8 * kk + 5]), x[2]);
        x[3] = hfma2(ga[kk].y, pack2(acc[8 * kk + 6], acc[8 * kk + 7]), x[3]);
        mma16816(d1, x, b1[kk].x, b1[kk].y);
        mma1688(d2, x[0], x[1], x[0]); mma1688(d3, x[0], x[1], x[1]);
        mma1688(d4, x[2], x[3], x[2]); mma1688(d5, x[2], x[3], x[3]);
      }
      const int qb = lane & 28;
      const float q0 = __shfl_sync(0xffffffffu, (g & 1) ? d2[1] + d4[1] : d2[0] + d4[0], qb | (g >> 1));
      const float q1 = __shfl_sync(0xffffffffu, (g & 1) ? d3[3] + d5[3] : d3[2] + d5[2], qb | (g >> 1));
      const float e0 = __shfl_xor_sync(0xffffffffu, t ? d1[0] : d1[3], 1);
      const float e1 = __shfl_sync(0xffffffffu, d1[2], qb);
      if (t < 2) st_pkt16(stp, __float_as_uint(t ? e1 : d1[0]), __float_as_uint(t ? q1 : q0),
                          __float_as_uint((t ? d1[2] : d1[1]) + e0), tag);
    }
    TSY(13);
    TT(1);
    float mb, rd, den, br;
    {
      const uint4* sp = &g_stats[(rt * 8 + 4 * (t & 1)) * 128 + lrow + 4 * (t & 2)];
      mbar_wait(sb + BAR_EMPTY1 + 8 * 3, 0);
#pragma unroll
      for (int kk = 0; kk < 8; kk++) stsm4((stsm_addr - SM_STASH + SM_X2 + (kk >> 2) * 8192) ^ ((kk & 3) * 32), X[4 * kk], X[4 * kk + 1], X[4 * kk + 2], X[4 * kk + 3]);
      if (b < NFFN) mbar_wait(sb + BAR_FFN, 1);
#pragma unroll
      for (int i = 0; i < WU1; i++) WU[i] = lds128(gu_addr + i * 512);
      bb_fence(tag);
      TT(2);
      uint4 v0, v1, v2, v3;
      int it = 0;
      do { v0 = ld_pkt16(sp); v1 = ld_pkt16(sp + 128); v2 = ld_pkt16(sp + 256); v3 = ld_pkt16(sp + 384); spin_guard(it); }
        while (!(__all_sync(0xffffffffu, v0.w == tag && v1.w == tag && v2.w == tag && v3.w == tag)));
      TT(3);
      float sm = (__uint_as_float(v0.x) + __uint_as_float(v1.x)) + (__uint_as_float(v2.x) + __uint_as_float(v3.x));
      float sq = (__uint_as_float(v0.y) + __uint_as_float(v1.y)) + (__uint_as_float(v2.y) + __uint_as_float(v3.y));
      float dt = (__uint_as_float(v0.z) + __uint_as_float(v1.z)) + (__uint_as_float(v2.z) + __uint_as_float(v3.z));
      sm += __shfl_xor_sync(0xffffffffu, sm, 1); sq += __shfl_xor_sync(0xffffffffu, sq, 1); dt += __shfl_xor_sync(0xffffffffu, dt, 1);
      const uint2 scal = lds64(sb + SM_SCAL);
      const float mu = sm * (1.f / 1024.f);
      mb = rbf(mu);
      den = rbf(sqrt_f(rbf(rbf(fmaxf(fmaf(-mu, mu, sq * (1.f / 1024.f)), 0.f)) + 1e-5f)));
      rd = rcp_f(den);
      br = fmaf(fmaf(-mb, __uint_as_float(scal.x), dt), rd, __uint_as_float(scal.y));
    }
    TSY(14);
    TT(4);
    {
      const int rb = __float_as_int(br);
      const int key = rb ^ ((rb >> 31) & 0x7fffffff);
      const int wmax = __reduce_max_sync(0xffffffffu, key);
      if (lane == __ffs(__ballot_sync(0xffffffffu, key == wmax)) - 1)
        sts128(sb + SM_AMAX + warp * 16, (uint32_t)key, lrow + 4 * (t & 2), pack2(mb, den), (uint32_t)rb);
      __syncwarp();
      nb_arrive(NB_AMAX, 288);
    }
    TT(5);
    const uint4* ep = &g_entry[(warp * 16 + (lane & 15)) * ESTR];
    const uint32_t slot = sb + SM_STASH + wg * 8192 + (tid & 127) * 16;
    cp_async16(slot, ep);
    {
      const float rh = rbf(rd);
      const uint32_t u = pack2(-mb * rh, rh);
      const int qb = lane & 28;
      const uint32_t u0 = __shfl_sync(0xffffffffu, u, qb), u1 = __shfl_sync(0xffffffffu, u, qb | 2);
      const uint32_t m0 = __byte_perm(u0, 0, 0x1010), h0 = __byte_perm(u0, 0, 0x3232);
      const uint32_t m1 = __byte_perm(u1, 0, 0x1010), h1 = __byte_perm(u1, 0, 0x3232);
#pragma unroll
      for (int j = 0; j < 16; j++) {
        const uint4 rec = lds128(sb + SM_REC + (4 * j + t) * 16);
        X[2 * j] = hfma2(rec.z, hfma2(hfma2(X[2 * j], h0, m0), rec.x, rec.y), X[2 * j]);
        X[2 * j + 1] = hfma2(rec.z, hfma2(hfma2(X[2 * j + 1], h1, m1), rec.x, rec.y), X[2 * j + 1]);
      }
#pragma unroll
      for (int kk = 0; kk < 8; kk++) stsm4((stsm_addr - SM_STASH + SM_OUT + (kk >> 2) * 8192) ^ ((kk & 3) * 32), X[4 * kk], X[4 * kk + 1], X[4 * kk + 2], X[4 * kk + 3]);
    }
    cp_async_wait();
    uint4 ent = lds128(slot);
    TSY(16);
    TT(6);
    int wrow;
    uint32_t xs0, xs1, hs0, hs1;
    uint32_t WD[64];
    const uint32_t wd_addr = sb + SM_RING + wg * ST1 + wq * 8192 + ((lane & 7) + ((lane >> 4) << 3)) * 128 + ((((lane >> 3) & 1) ^ (lane & 7)) * 16);
    {
      auto leader = [&]() {
        const int key = ent.w == tag ? (int)ent.x ^ (((int)ent.x >> 31) & 0x7fffffff) : (int)0x80000000;
        const int gmax = __reduce_max_sync(0xffffffffu, key);
        return __ffs(__ballot_sync(0xffffffffu, key == gmax)) - 1;
      };
      int wt = leader(), it = 0;
      TT(7);
      nb_arrive(NB_OST + wg, 160);
      TT(8);
      cp_async16(slot + 2048, &g_cand[(wt * 8 + warp) * 32 + lane]);
      if (ent.w != tag) cp_async16(slot, ep);
#pragma unroll
      for (int i = WU1; i < 16; i++) WU[i] = lds128(gu_addr + i * 512);
      if (b < NFFN) mbar_wait(sb + BAR_FFN + 8, 0);
#pragma unroll
      for (int mt = 0; mt < 8; mt++)
#pragma unroll
        for (int s = 0; s < 2; s++) ldsm4t((wd_addr + (mt >> 2) * 4096 + s * 2048) ^ ((mt & 3) * 32), WD + (mt * 2 + s) * 4);
      cp_async_wait();
      uint4 v = lds128(slot + 2048);
      ent = lds128(slot);
      TT(9);
      while (true) {
        const int have = wt;
        wt = leader();
        if (__all_sync(0xffffffffu, ent.w == tag && have == wt && v.z == tag)) break;
        v = ld_pkt16(&g_cand[(wt * 8 + warp) * 32 + lane]);
        if (ent.w != tag) ent = ld_pkt16(ep);
        spin_guard(it);
      }
      TT(10);
      ent.x = __shfl_sync(0xffffffffu, ent.x, wt); wrow = __shfl_sync(0xffffffffu, ent.y, wt); ent.z = __shfl_sync(0xffffffffu, ent.z, wt);
      xs0 = v.x; xs1 = v.y;
      const uint32_t mm = __byte_perm(ent.z, 0, 0x1010);
      const float rs = rcp_f(hi2f(ent.z));
      const uint32_t e0 = hsub2(xs0, mm), e1 = hsub2(xs1, mm);
      hs0 = hfma2(pack2(lo2f(e0) * rs, hi2f(e0) * rs), hadd2(fcb0, ONE2), fsb0);
      hs1 = hfma2(pack2(lo2f(e1) * rs, hi2f(e1) * rs), hadd2(fcb1, ONE2), fsb1);
    }
    if ((tid & 127) == 0) sts32(sb + SM_WROW + 4 * wg, wrow);
    nb_arrive(NB_WIN + wg, 160);
    TSY(17);
    TT(11);
    if (b < NFFN) {
      float da[4][4];
#pragma unroll
      for (int i = 0; i < 4; i++) { da[i][0] = da[i][1] = da[i][2] = da[i][3] = 0.f; }
      const uint32_t selv = ((g & 1) ? 0x1044 : 0x4410) + ((g & 4) ? ((g & 1) ? 0x2200 : 0x0022) : 0);
      const uint32_t sel0 = (g & 2) ? 0x4444 : selv, sel1 = (g & 2) ? selv : 0x4444;
#pragma unroll
      for (int s = 0; s < 16; s++) {
        const uint32_t v = __shfl_sync(0xffffffffu, (s & 1) ? hs1 : hs0, 4 * (s >> 1) + t);
        const uint32_t b0 = __byte_perm(v, 0, sel0), b1 = __byte_perm(v, 0, sel1);
        const uint32_t a0[4] = {WG[s].x, WG[s].y, WG[s].z, WG[s].w};
        const uint32_t a1[4] = {WU[s].x, WU[s].y, WU[s].z, WU[s].w};
        mma16816(da[(s & 1) * 2], a0, b0, b1);
        mma16816(da[(s & 1) * 2 + 1], a1, b0, b1);
      }
      {
        float v[4];
#pragma unroll
        for (int i = 0; i < 4; i++) {
          const float vg = da[0][i] + da[2][i], vu = da[1][i] + da[3][i];
          v[i] = ((g & 1) ? vu : vg) + __shfl_xor_sync(0xffffffffu, (g & 1) ? vg : vu, 6);
        }
        if ((t >> 1) == (g & 1))
          sts128(gu_base + (g & 1) * 128 + (g >> 1) * 32 + (t & 1) * 16, __float_as_uint(v[0]), __float_as_uint(v[1]), __float_as_uint(v[2]), __float_as_uint(v[3]));
      }
      TT(12);
      nb_sync(NB_CONS, 256);
      float gp[8], up[8];
#pragma unroll
      for (int w = 0; w < 8; w++) {
        const uint32_t a = sb + SM_RING + (w >> 1) * ST1 + 32768 + (w & 1) * 8192 + lane * 4;
        gp[w] = lds_f32(a); up[w] = lds_f32(a + 128);
      }
      const float gsum = ((gp[0] + gp[1]) + (gp[2] + gp[3])) + ((gp[4] + gp[5]) + (gp[6] + gp[7]));
      const float usum = ((up[0] + up[1]) + (up[2] + up[3])) + ((up[4] + up[5]) + (up[6] + up[7]));
      const float act = rbf(silu_f(rbf(gsum))) * rbf(usum);
      TT(13);
      const uint32_t ap = pack2(act, __shfl_down_sync(0xffffffffu, act, 1));
      const uint32_t b00 = __shfl_sync(0xffffffffu, ap, 2 * t), b01 = __shfl_sync(0xffffffffu, ap, 2 * t + 8);
      const uint32_t b10 = __shfl_sync(0xffffffffu, ap, 2 * t + 16), b11 = __shfl_sync(0xffffffffu, ap, 2 * t + 24);
      float y[8][4];
#pragma unroll
      for (int mt = 0; mt < 8; mt++) {
        y[mt][0] = y[mt][1] = y[mt][2] = y[mt][3] = 0.f;
        mma16816(y[mt], WD + (mt * 2) * 4, b00, b01);
        mma16816(y[mt], WD + (mt * 2 + 1) * 4, b10, b11);
      }
#pragma unroll
      for (int e = 0; e < 2; e++) {
        const float v0 = t == 0 ? y[e][0] : t == 1 ? y[2 + e][0] : t == 2 ? y[4 + e][0] : y[6 + e][0];
        const float v1 = t == 0 ? y[e][2] : t == 1 ? y[2 + e][2] : t == 2 ? y[4 + e][2] : y[6 + e][2];
        const int f = 16 * warp + 2 * (2 * t + e) + (g >> 2);
        st_pkt16(&g_ypart[(f * NFFN + b) * 4 + (g & 3)], __float_as_uint(v0), __float_as_uint(v1), tag, 0);
      }
    }
    TSY(18);
    TT(14);
    {
      const int pw = warp - (warp > (b >> 4));
      if (warp != (b >> 4)) {
        const uint4* yp = &g_ypart[b * NFFN * 4 + pw * 64 + lane];
        uint4 v0, v1;
        int it = 0;
        do { v0 = ld_pkt16(yp); v1 = ld_pkt16(yp + 32); spin_guard(it); }
        while (!(__all_sync(0xffffffffu, v0.z == tag && v1.z == tag)));
        float y0 = __uint_as_float(v0.x) + __uint_as_float(v1.x), y1 = __uint_as_float(v0.y) + __uint_as_float(v1.y);
#pragma unroll
        for (int o = 4; o <= 16; o <<= 1) { y0 += __shfl_xor_sync(0xffffffffu, y0, o); y1 += __shfl_xor_sync(0xffffffffu, y1, o); }
        if (lane < 4) sts64(sb + SM_YRED + pw * 32 + lane * 8, __float_as_uint(y0), __float_as_uint(y1));
      }
    }
    TT(15);
    if (warp != (b >> 4)) {
      nb_arrive(NB_CONS, 256);
    } else {
      nb_sync(NB_CONS, 256);
      float y0 = 0.f, y1 = 0.f;
      if (lane < 28) { const uint2 e = lds64(sb + SM_YRED + lane * 8); y0 = __uint_as_float(e.x); y1 = __uint_as_float(e.y); }
#pragma unroll
      for (int o = 4; o <= 16; o <<= 1) { y0 += __shfl_xor_sync(0xffffffffu, y0, o); y1 += __shfl_xor_sync(0xffffffffu, y1, o); }
      const int src = 2 * (t & 1);
      const float ya = __shfl_sync(0xffffffffu, y0, src), yb = __shfl_sync(0xffffffffu, y0, src + 1);
      const float yc = __shfl_sync(0xffffffffu, y1, src), yd = __shfl_sync(0xffffffffu, y1, src + 1);
      if (g == ((b >> 1) & 7) && (t >> 1) == (b & 1)) {
        const float rs = rbf(__uint_as_float(ent.x));
        const float sg = sigmoid_f(rs);
        const uint32_t sg2 = pack2(sg, sg);
        const uint32_t o0 = hadd2(xs0, hmul2(fgb0, hadd2(hs0, hmul2(pack2(ya, yb), sg2))));
        const uint32_t o1 = hadd2(xs1, hmul2(fgb1, hadd2(hs1, hmul2(pack2(yc, yd), sg2))));
        uint32_t* op = reinterpret_cast<uint32_t*>(p.out + (size_t)wrow * 1024) + fp;
        op[0] = o0; op[4] = o1;
      }
      if (b == 0) {
        if (lane < 8) st_relaxed(&p.sc->ticket[lane * 32], 0);
        st_relaxed(&p.sc->epoch[lane], tag);
      }
      if (lane == 0) TS(19);
    }
  }
}

typedef CUresult (*EncodeFn)(CUtensorMap*, CUtensorMapDataType, cuuint32_t, void*, const cuuint64_t*, const cuuint64_t*,
                             const cuuint32_t*, const cuuint32_t*, CUtensorMapInterleave, CUtensorMapSwizzle,
                             CUtensorMapL2promotion, CUtensorMapFloatOOBfill);

CUtensorMap make_map(EncodeFn enc, const void* ptr, uint64_t rows, uint64_t cols, uint32_t box_rows, uint32_t box_cols, CUtensorMapSwizzle sw) {
  CUtensorMap m;
  cuuint64_t dims[2] = {cols, rows};
  cuuint64_t strides[1] = {cols * 2};
  cuuint32_t box[2] = {box_cols, box_rows};
  cuuint32_t es[2] = {1, 1};
  enc(&m, CU_TENSOR_MAP_DATA_TYPE_BFLOAT16, 2, const_cast<void*>(ptr), dims, strides, box, es, CU_TENSOR_MAP_INTERLEAVE_NONE, sw,
      CU_TENSOR_MAP_L2_PROMOTION_L2_128B, CU_TENSOR_MAP_FLOAT_OOB_FILL_NONE);
  return m;
}

CUtensorMap make_map3(EncodeFn enc, const void* ptr, uint64_t rows, uint64_t cols, uint32_t box_rows, uint32_t box_blks) {
  CUtensorMap m;
  cuuint64_t dims[3] = {64, rows, cols / 64};
  cuuint64_t strides[2] = {cols * 2, 128};
  cuuint32_t box[3] = {64, box_rows, box_blks};
  cuuint32_t es[3] = {1, 1, 1};
  enc(&m, CU_TENSOR_MAP_DATA_TYPE_BFLOAT16, 3, const_cast<void*>(ptr), dims, strides, box, es, CU_TENSOR_MAP_INTERLEAVE_NONE,
      CU_TENSOR_MAP_SWIZZLE_128B, CU_TENSOR_MAP_L2_PROMOTION_L2_128B, CU_TENSOR_MAP_FLOAT_OOB_FILL_NONE);
  return m;
}

}

extern "C" void kernel_launch(void* const* d_in, const int* in_sizes, int n_in, void* d_out, int out_size) {
  (void)in_sizes; (void)n_in; (void)out_size;
  Params p;
  p.x = (const bf16*)d_in[0]; p.kc = (const bf16*)d_in[1]; p.vc = (const bf16*)d_in[2];
  p.wq = (const bf16*)d_in[3]; p.wo = (const bf16*)d_in[4]; p.w_r = (const bf16*)d_in[6];
  p.wg = (const bf16*)d_in[7]; p.wu = (const bf16*)d_in[8]; p.wd = (const bf16*)d_in[9];
  p.c = (const bf16*)d_in[10]; p.w_mod = (const bf16*)d_in[11]; p.out = (bf16*)d_out;

  void* fn = nullptr;
  cudaDriverEntryPointQueryResult st;
  cudaGetDriverEntryPoint("cuTensorMapEncodeTiled", &fn, cudaEnableDefault, &st);
  EncodeFn enc = (EncodeFn)fn;
  void* scp = nullptr;
  cudaGetSymbolAddress(&scp, g_scratch);
  p.sc = (Scratch*)scp;
  void *hp = p.sc->h, *op = p.sc->o;
  const CUtensorMapSwizzle S128 = CU_TENSOR_MAP_SWIZZLE_128B;
  CUtensorMap mH = make_map(enc, hp, 2048, 1024, 64, 64, S128);
  CUtensorMap mWq = make_map3(enc, p.wq, 1024, 4096, 64, 4);
  CUtensorMap mK = make_map(enc, p.kc, 8192, 128, 64, 64, S128);
  CUtensorMap mV = make_map(enc, p.vc, 8192, 128, 64, 64, S128);
  CUtensorMap mO = make_map(enc, op, 2048, 4096, 64, 64, S128);
  CUtensorMap mWo = make_map3(enc, p.wo, 4096, 1024, 64, 2);
  CUtensorMap mX = make_map(enc, p.x, 2048, 1024, 64, 64, S128);
  CUtensorMap mOut = make_map(enc, p.out, 2048, 1024, 64, 64, S128);
  CUtensorMap mWg = make_map(enc, p.wg, 1024, 3584, 256, 32, CU_TENSOR_MAP_SWIZZLE_64B);
  CUtensorMap mWu = make_map(enc, p.wu, 1024, 3584, 256, 32, CU_TENSOR_MAP_SWIZZLE_64B);
  CUtensorMap mWd = make_map3(enc, p.wd, 3584, 1024, 32, 8);
  CUtensorMap mWm = make_map(enc, p.w_mod, 1024, 6144, 16, 256, CU_TENSOR_MAP_SWIZZLE_NONE);
  CUtensorMap mWs = make_map(enc, p.w_mod, 1024, 6144, 128, 128, CU_TENSOR_MAP_SWIZZLE_NONE);
  cudaFuncSetAttribute(fused_kernel, cudaFuncAttributeMaxDynamicSharedMemorySize, SMEM_BYTES);
  fused_kernel<<<NCTA, NTHREADS, SMEM_BYTES>>>(p, mH, mWq, mK, mV, mO, mWo, mX, mOut, mWg, mWu, mWd, mWm, mWs);
}
```

```cpp
#include <cuda_runtime.h>
#include <cuda_bf16.h>
#include <cuda.h>
#include <stdint.h>
#include <stddef.h>

#define UPD 200
#define GATED 1500
#define WL 3000
#define XD 0
#define PLD 200
#define ESTR 8
#define HD 6000
#define YD 600
#define SPD 0
#define PFW 100
#define X_PEEL 1
#define WU1 12

namespace {

typedef __nv_bfloat16 bf16;

constexpr int NTHREADS = 384;
constexpr int NMAIN = 128;
constexpr int NCTA = 132;
#define RS 8
constexpr int RV = 16 * RS + 64;
constexpr int NREP = 4;
constexpr int NFFN = 112;

constexpr uint32_t SM_RING = 0;
constexpr uint32_t ST1 = 49152;
constexpr uint32_t ST2 = 32768;
constexpr int NST2 = 6;
constexpr uint32_t SM_STASH = 196608;
constexpr uint32_t SM_MISC = 229376;
constexpr uint32_t BAR_FULL1 = SM_MISC + 0;
constexpr uint32_t BAR_EMPTY1 = SM_MISC + 40;
constexpr uint32_t BAR_FULL2 = SM_MISC + 0;
constexpr uint32_t BAR_EMPTY2 = SM_MISC + 48;
constexpr uint32_t BAR_STASH = SM_MISC + 160;
constexpr uint32_t BAR_SFREE = SM_MISC + 176;
constexpr uint32_t BAR_TFREE = SM_MISC + 184;
constexpr uint32_t BAR_FFN = SM_MISC + 192;
constexpr uint32_t BAR_VEC = SM_MISC + 208;
constexpr uint32_t BAR_RED = SM_MISC + 216;
constexpr uint32_t BAR_XH = SM_MISC + 152;
constexpr uint32_t BAR_HS = SM_MISC + 80;
constexpr uint32_t BAR_G = SM_MISC + 112;
constexpr uint32_t BAR_T1 = SM_MISC + 120;
constexpr uint32_t BAR_HF = SM_MISC + 128;
constexpr uint32_t BAR_X = SM_MISC + 136;
constexpr uint32_t BAR_OF = SM_MISC + 224;
constexpr uint32_t BAR_ROLE = SM_MISC + 240;
constexpr uint32_t SM_ROLE = SM_MISC + 248;
constexpr uint32_t SM_GA = SM_MISC + 256;
constexpr uint32_t SM_SCAL = SM_MISC + 512;
constexpr uint32_t SM_WROW = SM_MISC + 520;
constexpr uint32_t SM_AMAX = SM_MISC + 528;
constexpr uint32_t SM_YRED = SM_MISC + 656;
constexpr uint32_t SM_X2 = 2 * ST1, SM_OUT = 3 * ST1;
constexpr uint32_t SM_REC = SM_MISC + 1024;
constexpr uint32_t BAR_TAB = SM_MISC + 1000;
constexpr uint32_t BAR_CAND = SM_MISC + 880;
constexpr uint32_t SM_CAND = SM_MISC + 888;
constexpr uint32_t SM_WSLAB = 2 * 49152 + 16384;
constexpr uint32_t SM_XROW = 2 * 49152;
constexpr uint32_t SM_RED = SM_MISC + 2048;
constexpr uint32_t SM_B1 = SM_MISC + 2048;
constexpr uint32_t SMEM_BYTES = 232448;

constexpr int NB_CONS = 1, NB_WIN = 2  , NB_OST = 4  , NB_AMAX = 6;

struct __align__(1024) Scratch {
  uint32_t epoch[32];
  uint32_t hflag[16 * 32];
  uint32_t oflag[64 * 32];
  uint2 vdone[4 * 16];
  uint32_t pad[96 + 512];
  uint32_t ticket[8 * 32];
  uint2 mod[3072];
  uint4 rec[2][NREP][2 * RV];
  uint4 lnst[1024];
  uint4 entry[8 * 16 * 8];
  uint4 cand[16 * 8 * 32];
  uint4 stats[16 * 8 * 128];
  uint4 ypart[128 * NFFN * 4];
  unsigned long long ts[NCTA * 64];
  uint16_t h[2048 * 1024];
  uint16_t o[2048 * 4096];
};
__device__ Scratch g_scratch;
#define g_epoch (p.sc->epoch[0])
#define g_hflag (p.sc->hflag)
#define g_oflag (p.sc->oflag)
#define g_mod (p.sc->mod)
#define g_entry (p.sc->entry)
#define g_cand (p.sc->cand)
#define g_stats (p.sc->stats)
#define g_ypart (p.sc->ypart)
#define g_vdone (p.sc->vdone)
#define g_lnst (p.sc->lnst)
#define g_rec (p.sc->rec)
#define g_ts (p.sc->ts)
#define g_h (p.sc->h)

struct Params {
  const bf16* w_mod; const bf16* c; Scratch* sc; const bf16* x; const bf16* w_r; bf16* out;
  const bf16* wq; const bf16* wo; const bf16* wg; const bf16* wu; const bf16* wd; const bf16* kc; const bf16* vc;
};

__device__ __forceinline__ uint32_t smem_u32(const void* p) { return (uint32_t)__cvta_generic_to_shared(p); }
__device__ __forceinline__ void mbar_init(uint32_t bar, uint32_t cnt) { asm volatile("mbarrier.init.shared::cta.b64 [%0], %1;" :: "r"(bar), "r"(cnt) : "memory"); }
__device__ __forceinline__ void mbar_expect_tx(uint32_t bar, uint32_t bytes) { asm volatile("mbarrier.arrive.expect_tx.shared::cta.b64 _, [%0], %1;" :: "r"(bar), "r"(bytes) : "memory"); }
__device__ __forceinline__ void mbar_arrive(uint32_t bar) { asm volatile("mbarrier.arrive.shared::cta.b64 _, [%0];" :: "r"(bar) : "memory"); }
__device__ __forceinline__ void mbar_arrive_cl(uint32_t cluster_addr) { asm volatile("mbarrier.arrive.shared::cluster.b64 _, [%0];" :: "r"(cluster_addr) : "memory"); }
__device__ __forceinline__ uint32_t mapa(uint32_t addr, uint32_t cta) { uint32_t r; asm("mapa.shared::cluster.u32 %0, %1, %2;" : "=r"(r) : "r"(addr), "r"(cta)); return r; }
__device__ __forceinline__ bool mbar_test(uint32_t bar, uint32_t parity) {
  uint32_t ok;
  asm volatile("{\n.reg .pred p;\nmbarrier.test_wait.parity.shared::cta.b64 p, [%1], %2;\nselp.u32 %0, 1, 0, p;\n}" : "=r"(ok) : "r"(bar), "r"(parity) : "memory");
  return ok;
}
constexpr int SPIN_LIMIT = 300000;
__device__ __forceinline__ void spin_guard(int& it) {
  asm volatile("{\n.reg .pred p;\n.reg .b64 z;\nadd.s32 %0, %0, 1;\nsetp.gt.s32 p, %0, %1;\nmov.b64 z, 0;\n@p st.volatile.global.u32 [z], %0;\n}" : "+r"(it) : "n"(SPIN_LIMIT));
}
__device__ __forceinline__ void mbar_wait_g(uint32_t bar, uint32_t parity) {
  asm volatile("{\n.reg .pred p, q;\n.reg .b32 c;\n.reg .b64 z;\nmov.b32 c, 0;\nmov.b64 z, 0;\nMW_LOOP:\n"
               "mbarrier.try_wait.parity.shared::cta.b64 p, [%0], %1;\nadd.s32 c, c, 1;\nsetp.gt.s32 q, c, %2;\n"
               "@q st.volatile.global.u32 [z], c;\n@!p bra MW_LOOP;\n}" :: "r"(bar), "r"(parity), "n"(SPIN_LIMIT) : "memory");
}
__device__ __forceinline__ void mbar_wait(uint32_t bar, uint32_t parity) {
  asm volatile("{\n.reg .pred p;\nMW_LOOP:\nmbarrier.try_wait.parity.shared::cta.b64 p, [%0], %1;\n@!p bra MW_LOOP;\n}" :: "r"(bar), "r"(parity) : "memory");
}
__device__ __forceinline__ void bb_fence(uint32_t v) {
  asm volatile("{\n.reg .pred p;\n.reg .u32 c;\nsetp.ne.u32 p, %0, 0;\n@p bra.uni BF_DONE;\nBF_LOOP:\nnanosleep.u32 1;\nmov.u32 c, %%clock;\nsetp.eq.u32 p, c, 0;\n@p bra.uni BF_LOOP;\nBF_DONE:\n}" :: "r"(v) : "memory");
}
__device__ __forceinline__ bool elect_one() {
  uint32_t pred;
  asm volatile("{\n.reg .pred P;\nelect.sync _|P, 0xffffffff;\nselp.u32 %0, 1, 0, P;\n}" : "=r"(pred));
  return pred;
}
__device__ __forceinline__ void tma_ld(uint32_t dst, const CUtensorMap* m, int c0, int c1, uint32_t bar) {
  asm volatile("cp.async.bulk.tensor.2d.shared::cluster.global.mbarrier::complete_tx::bytes [%0], [%1, {%3, %4}], [%2];"
    :: "r"(dst), "l"(m), "r"(bar), "r"(c0), "r"(c1) : "memory");
}
__device__ __forceinline__ void tma_ld_hint(uint32_t dst, const CUtensorMap* m, int c0, int c1, uint32_t bar, uint64_t pol) {
  asm volatile("cp.async.bulk.tensor.2d.shared::cluster.global.mbarrier::complete_tx::bytes.L2::cache_hint [%0], [%1, {%3, %4}], [%2], %5;"
    :: "r"(dst), "l"(m), "r"(bar), "r"(c0), "r"(c1), "l"(pol) : "memory");
}
__device__ __forceinline__ void tma_ld_mc(uint32_t dst, const CUtensorMap* m, int c0, int c1, uint32_t bar) {
  asm volatile("cp.async.bulk.tensor.2d.shared::cluster.global.mbarrier::complete_tx::bytes.multicast::cluster [%0], [%1, {%3, %4}], [%2], %5;"
    :: "r"(dst), "l"(m), "r"(bar), "r"(c0), "r"(c1), "h"((uint16_t)3) : "memory");
}
__device__ __forceinline__ void tma_ld_mc_hint(uint32_t dst, const CUtensorMap* m, int c0, int c1, uint32_t bar, uint64_t pol) {
  asm volatile("cp.async.bulk.tensor.2d.shared::cluster.global.mbarrier::complete_tx::bytes.multicast::cluster.L2::cache_hint [%0], [%1, {%3, %4}], [%2], %5, %6;"
    :: "r"(dst), "l"(m), "r"(bar), "r"(c0), "r"(c1), "h"((uint16_t)3), "l"(pol) : "memory");
}
__device__ __forceinline__ void tma_ld3_hint(uint32_t dst, const CUtensorMap* m, int row, int blk, uint32_t bar, uint64_t pol) {
  asm volatile("cp.async.bulk.tensor.3d.shared::cluster.global.mbarrier::complete_tx::bytes.L2::cache_hint [%0], [%1, {0, %3, %4}], [%2], %5;"
    :: "r"(dst), "l"(m), "r"(bar), "r"(row), "r"(blk), "l"(pol) : "memory");
}
__device__ __forceinline__ void tma_st(const CUtensorMap* m, int c0, int c1, uint32_t src) {
  asm volatile("cp.async.bulk.tensor.2d.global.shared::cta.bulk_group [%0, {%2, %3}], [%1];" :: "l"(m), "r"(src), "r"(c0), "r"(c1) : "memory");
}
__device__ __forceinline__ void tma_prefetch_desc(const CUtensorMap* m) { asm volatile("prefetch.tensormap [%0];" :: "l"(m) : "memory"); }
__device__ __forceinline__ void l2_prefetch(const void* p, uint32_t bytes) { asm volatile("cp.async.bulk.prefetch.L2.global [%0], %1;" :: "l"(p), "r"(bytes) : "memory"); }
__device__ __forceinline__ void bulk_commit() { asm volatile("cp.async.bulk.commit_group;" ::: "memory"); }
__device__ __forceinline__ void bulk_wait_read() { asm volatile("cp.async.bulk.wait_group.read 0;" ::: "memory"); }
__device__ __forceinline__ void bulk_wait_all() { asm volatile("cp.async.bulk.wait_group 0;" ::: "memory"); }
__device__ __forceinline__ void fence_async_smem() { asm volatile("fence.proxy.async.shared::cta;" ::: "memory"); }
__device__ __forceinline__ void fence_async_global() { asm volatile("fence.proxy.async.global;" ::: "memory"); }
__device__ __forceinline__ void fence_acquire_gpu() { asm volatile("fence.acquire.gpu;" ::: "memory"); }
__device__ __forceinline__ void fence_release_gpu() { asm volatile("fence.release.gpu;" ::: "memory"); }
__device__ __forceinline__ void st_async_f32x4(uint32_t cluster_addr, const float* v, uint32_t cluster_bar) {
  asm volatile("st.async.weak.shared::cluster.mbarrier::complete_tx::bytes.v4.f32 [%0], {%1,%2,%3,%4}, [%5];"
    :: "r"(cluster_addr), "f"(v[0]), "f"(v[1]), "f"(v[2]), "f"(v[3]), "r"(cluster_bar) : "memory");
}
__device__ __forceinline__ void nb_sync(int id, int n) { asm volatile("bar.sync %0, %1;" :: "r"(id), "r"(n) : "memory"); }
__device__ __forceinline__ void nb_arrive(int id, int n) { asm volatile("bar.arrive %0, %1;" :: "r"(id), "r"(n) : "memory"); }
__device__ __forceinline__ void wg_fence() { asm volatile("wgmma.fence.sync.aligned;" ::: "memory"); }
__device__ __forceinline__ void wg_commit() { asm volatile("wgmma.commit_group.sync.aligned;" ::: "memory"); }
template <int N> __device__ __forceinline__ void wg_wait() { asm volatile("wgmma.wait_group.sync.aligned %0;" :: "n"(N) : "memory"); }
template <int N> __device__ __forceinline__ void reg_fence(float* a) {
#pragma unroll
  for (int i = 0; i < N; i++) asm volatile("" : "+f"(a[i]) :: "memory");
}
template <int N> __device__ __forceinline__ void reg_fence(uint32_t* a) {
#pragma unroll
  for (int i = 0; i < N; i++) asm volatile("" : "+r"(a[i]) :: "memory");
}
__device__ __forceinline__ uint64_t mk_desc(uint32_t addr, uint32_t lbo) {
  return (uint64_t)((addr & 0x3FFFF) >> 4) | ((uint64_t)(lbo >> 4) << 16) | ((uint64_t)(1024 >> 4) << 32) | (1ull << 62);
}

__device__ __forceinline__ uint64_t policy_evict_first() { uint64_t pol; asm("createpolicy.fractional.L2::evict_first.b64 %0, 1.0;" : "=l"(pol)); return pol; }
__device__ __forceinline__ uint32_t ld_relaxed(const uint32_t* p) { uint32_t v; asm volatile("ld.relaxed.gpu.global.u32 %0, [%1];" : "=r"(v) : "l"(p) : "memory"); return v; }
__device__ __forceinline__ void st_relaxed(uint32_t* p, uint32_t v) { asm volatile("st.relaxed.gpu.global.u32 [%0], %1;" :: "l"(p), "r"(v) : "memory"); }
__device__ __forceinline__ void red_add_relaxed(uint32_t* p, uint32_t v) { asm volatile("red.relaxed.gpu.global.add.u32 [%0], %1;" :: "l"(p), "r"(v) : "memory"); }
__device__ __forceinline__ uint2 ld_pkt8(const uint2* p) {
  uint2 v; asm volatile("{\n.reg .b64 t;\nld.relaxed.gpu.global.b64 t, [%2];\nmov.b64 {%0,%1}, t;\n}" : "=r"(v.x), "=r"(v.y) : "l"(p) : "memory"); return v;
}
__device__ __forceinline__ void st_pkt8(uint2* p, uint32_t a, uint32_t b) {
  asm volatile("{\n.reg .b64 t;\nmov.b64 t, {%1,%2};\nst.relaxed.gpu.global.b64 [%0], t;\n}" :: "l"(p), "r"(a), "r"(b) : "memory");
}
__device__ __forceinline__ uint4 ld_pkt16(const uint4* p) {
  uint4 v; asm volatile("{\n.reg .b128 t;\n.reg .b64 a, b;\nld.relaxed.gpu.global.b128 t, [%4];\nmov.b128 {a, b}, t;\nmov.b64 {%0,%1}, a;\nmov.b64 {%2,%3}, b;\n}"
    : "=r"(v.x), "=r"(v.y), "=r"(v.z), "=r"(v.w) : "l"(p) : "memory"); return v;
}
__device__ __forceinline__ void st_pkt16(uint4* p, uint32_t x, uint32_t y, uint32_t z, uint32_t w) {
  asm volatile("{\n.reg .b128 t;\n.reg .b64 a, b;\nmov.b64 a, {%1,%2};\nmov.b64 b, {%3,%4};\nmov.b128 t, {a, b};\nst.relaxed.gpu.global.b128 [%0], t;\n}"
    :: "l"(p), "r"(x), "r"(y), "r"(z), "r"(w) : "memory");
}
__device__ __forceinline__ void cp_async16(uint32_t dst, const void* src) { asm volatile("cp.async.cg.shared.global [%0], [%1], 16;" :: "r"(dst), "l"(src) : "memory"); }
__device__ __forceinline__ void cp_async_wait() { asm volatile("cp.async.wait_all;" ::: "memory"); }
__device__ __forceinline__ uint32_t lds32(uint32_t a) { uint32_t v; asm volatile("ld.shared.u32 %0, [%1];" : "=r"(v) : "r"(a) : "memory"); return v; }
__device__ __forceinline__ float lds_f32(uint32_t a) { float v; asm volatile("ld.shared.f32 %0, [%1];" : "=f"(v) : "r"(a) : "memory"); return v; }
__device__ __forceinline__ uint2 lds64(uint32_t a) { uint2 v; asm volatile("ld.shared.v2.u32 {%0,%1}, [%2];" : "=r"(v.x), "=r"(v.y) : "r"(a) : "memory"); return v; }
__device__ __forceinline__ uint4 lds128(uint32_t a) { uint4 v; asm volatile("ld.shared.v4.u32 {%0,%1,%2,%3}, [%4];" : "=r"(v.x), "=r"(v.y), "=r"(v.z), "=r"(v.w) : "r"(a) : "memory"); return v; }
__device__ __forceinline__ void sts32(uint32_t a, uint32_t v) { asm volatile("st.shared.u32 [%0], %1;" :: "r"(a), "r"(v) : "memory"); }
__device__ __forceinline__ void sts64(uint32_t a, uint32_t x, uint32_t y) { asm volatile("st.shared.v2.u32 [%0], {%1,%2};" :: "r"(a), "r"(x), "r"(y) : "memory"); }
__device__ __forceinline__ void sts128(uint32_t a, uint32_t x, uint32_t y, uint32_t z, uint32_t w) { asm volatile("st.shared.v4.u32 [%0], {%1,%2,%3,%4};" :: "r"(a), "r"(x), "r"(y), "r"(z), "r"(w) : "memory"); }
__device__ __forceinline__ void stsm4(uint32_t a, uint32_t x, uint32_t y, uint32_t z, uint32_t w) {
  asm volatile("stmatrix.sync.aligned.m8n8.x4.shared.b16 [%0], {%1,%2,%3,%4};" :: "r"(a), "r"(x), "r"(y), "r"(z), "r"(w) : "memory");
}
__device__ __forceinline__ void ldsm4(uint32_t a, uint32_t* r) {
  asm volatile("ldmatrix.sync.aligned.m8n8.x4.shared.b16 {%0,%1,%2,%3}, [%4];" : "=r"(r[0]), "=r"(r[1]), "=r"(r[2]), "=r"(r[3]) : "r"(a) : "memory");
}
__device__ __forceinline__ void ldsm4t(uint32_t a, uint32_t* r) {
  asm volatile("ldmatrix.sync.aligned.m8n8.x4.trans.shared.b16 {%0,%1,%2,%3}, [%4];" : "=r"(r[0]), "=r"(r[1]), "=r"(r[2]), "=r"(r[3]) : "r"(a) : "memory");
}
__device__ __forceinline__ void mma16816(float* d, const uint32_t* a, uint32_t b0, uint32_t b1) {
  asm volatile("mma.sync.aligned.m16n8k16.row.col.f32.bf16.bf16.f32 {%0,%1,%2,%3}, {%4,%5,%6,%7}, {%8,%9}, {%0,%1,%2,%3};"
    : "+f"(d[0]), "+f"(d[1]), "+f"(d[2]), "+f"(d[3]) : "r"(a[0]), "r"(a[1]), "r"(a[2]), "r"(a[3]), "r"(b0), "r"(b1));
}
__device__ __forceinline__ void mma1688(float* d, uint32_t a0, uint32_t a1, uint32_t b0) {
  asm volatile("mma.sync.aligned.m16n8k8.row.col.f32.bf16.bf16.f32 {%0,%1,%2,%3}, {%4,%5}, {%6}, {%0,%1,%2,%3};"
    : "+f"(d[0]), "+f"(d[1]), "+f"(d[2]), "+f"(d[3]) : "r"(a0), "r"(a1), "r"(b0));
}
__device__ __forceinline__ uint32_t pack2(float lo, float hi) { uint32_t r; asm("cvt.rn.bf16x2.f32 %0, %1, %2;" : "=r"(r) : "f"(hi), "f"(lo)); return r; }
__device__ __forceinline__ float lo2f(uint32_t v) { return __uint_as_float(v << 16); }
__device__ __forceinline__ float hi2f(uint32_t v) { return __uint_as_float(v & 0xffff0000u); }
__device__ __forceinline__ uint32_t hmul2(uint32_t a, uint32_t b) { uint32_t r; asm("mul.rn.bf16x2 %0, %1, %2;" : "=r"(r) : "r"(a), "r"(b)); return r; }
__device__ __forceinline__ uint32_t hadd2(uint32_t a, uint32_t b) { uint32_t r; asm("add.rn.bf16x2 %0, %1, %2;" : "=r"(r) : "r"(a), "r"(b)); return r; }
__device__ __forceinline__ uint32_t hsub2(uint32_t a, uint32_t b) { uint32_t r; asm("sub.rn.bf16x2 %0, %1, %2;" : "=r"(r) : "r"(a), "r"(b)); return r; }
__device__ __forceinline__ uint32_t hfma2(uint32_t a, uint32_t b, uint32_t c) { uint32_t r; asm("fma.rn.bf16x2 %0, %1, %2, %3;" : "=r"(r) : "r"(a), "r"(b), "r"(c)); return r; }
__device__ __forceinline__ float rbf(float v) { return lo2f(pack2(v, 0.f)); }
__device__ __forceinline__ float ex2(float v) { float r; asm("ex2.approx.ftz.f32 %0, %1;" : "=f"(r) : "f"(v)); return r; }
__device__ __forceinline__ float rcp_f(float v) { float r; asm("rcp.approx.ftz.f32 %0, %1;" : "=f"(r) : "f"(v)); return r; }
__device__ __forceinline__ float sqrt_f(float v) { float r; asm("sqrt.approx.ftz.f32 %0, %1;" : "=f"(r) : "f"(v)); return r; }
__device__ __forceinline__ float sigmoid_f(float v) { return rcp_f(1.f + ex2(-1.4426950408889634f * v)); }
__device__ __forceinline__ float silu_f(float v) { return v * sigmoid_f(v); }
constexpr uint32_t ONE2 = 0x3f803f80u;

#define R8(a,o) "+f"(a[o+0]), "+f"(a[o+1]), "+f"(a[o+2]), "+f"(a[o+3]), "+f"(a[o+4]), "+f"(a[o+5]), "+f"(a[o+6]), "+f"(a[o+7])
#define R64(a,o) R8(a,o), R8(a,o+8), R8(a,o+16), R8(a,o+24), R8(a,o+32), R8(a,o+40), R8(a,o+48), R8(a,o+56)
#define D64 "{%0,%1,%2,%3,%4,%5,%6,%7,%8,%9,%10,%11,%12,%13,%14,%15,%16,%17,%18,%19,%20,%21,%22,%23,%24,%25,%26,%27,%28,%29,%30,%31," \
            "%32,%33,%34,%35,%36,%37,%38,%39,%40,%41,%42,%43,%44,%45,%46,%47,%48,%49,%50,%51,%52,%53,%54,%55,%56,%57,%58,%59,%60,%61,%62,%63"
#define D128 D64 ",%64,%65,%66,%67,%68,%69,%70,%71,%72,%73,%74,%75,%76,%77,%78,%79,%80,%81,%82,%83,%84,%85,%86,%87,%88,%89,%90,%91,%92,%93,%94,%95," \
            "%96,%97,%98,%99,%100,%101,%102,%103,%104,%105,%106,%107,%108,%109,%110,%111,%112,%113,%114,%115,%116,%117,%118,%119,%120,%121,%122,%123,%124,%125,%126,%127"

template <int TB> __device__ __forceinline__ void wgmma_ss128(float* d, uint64_t da, uint64_t db, int acc) {
  asm volatile("{\n.reg .pred p;\nsetp.ne.b32 p, %66, 0;\nwgmma.mma_async.sync.aligned.m64n128k16.f32.bf16.bf16 " D64 "}, %64, %65, p, 1, 1, 0, %67;\n}"
    : R64(d, 0) : "l"(da), "l"(db), "r"(acc), "n"(TB));
}
template <int TB> __device__ __forceinline__ void wgmma_rs128(float* d, const uint32_t* a, uint64_t db, int acc) {
  asm volatile("{\n.reg .pred p;\nsetp.ne.b32 p, %69, 0;\nwgmma.mma_async.sync.aligned.m64n128k16.f32.bf16.bf16 " D64 "}, {%64,%65,%66,%67}, %68, p, 1, 1, %70;\n}"
    : R64(d, 0) : "r"(a[0]), "r"(a[1]), "r"(a[2]), "r"(a[3]), "l"(db), "r"(acc), "n"(TB));
}
template <int TB> __device__ __forceinline__ void wgmma_ss256(float* d, uint64_t da, uint64_t db, int acc) {
  asm volatile("{\n.reg .pred p;\nsetp.ne.b32 p, %130, 0;\nwgmma.mma_async.sync.aligned.m64n256k16.f32.bf16.bf16 " D128 "}, %128, %129, p, 1, 1, 0, %131;\n}"
    : R64(d, 0), R64(d, 64) : "l"(da), "l"(db), "r"(acc), "n"(TB));
}

#define W8(a,o) "=f"(a[o+0]), "=f"(a[o+1]), "=f"(a[o+2]), "=f"(a[o+3]), "=f"(a[o+4]), "=f"(a[o+5]), "=f"(a[o+6]), "=f"(a[o+7])
#define W64(a,o) W8(a,o), W8(a,o+8), W8(a,o+16), W8(a,o+24), W8(a,o+32), W8(a,o+40), W8(a,o+48), W8(a,o+56)
template <int TB> __device__ __forceinline__ void wgmma_ss128_z(float* d, uint64_t da, uint64_t db) {
  asm volatile("wgmma.mma_async.sync.aligned.m64n128k16.f32.bf16.bf16 " D64 "}, %64, %65, 0, 1, 1, 0, %66;"
    : W64(d, 0) : "l"(da), "l"(db), "n"(TB));
}
template <int TB> __device__ __forceinline__ void wgmma_rs128_z(float* d, const uint32_t* a, uint64_t db) {
  asm volatile("wgmma.mma_async.sync.aligned.m64n128k16.f32.bf16.bf16 " D64 "}, {%64,%65,%66,%67}, %68, 0, 1, 1, %69;"
    : W64(d, 0) : "r"(a[0]), "r"(a[1]), "r"(a[2]), "r"(a[3]), "l"(db), "n"(TB));
}
template <int TB> __device__ __forceinline__ void wgmma_ss256_z(float* d, uint64_t da, uint64_t db) {
  asm volatile("wgmma.mma_async.sync.aligned.m64n256k16.f32.bf16.bf16 " D128 "}, %128, %129, 0, 1, 1, 0, %130;"
    : W64(d, 0), W64(d, 64) : "l"(da), "l"(db), "n"(TB));
}

template <int TB> __device__ __forceinline__ void wgmma_rs256(float* d, const uint32_t* a, uint64_t db) {
  asm volatile("wgmma.mma_async.sync.aligned.m64n256k16.f32.bf16.bf16 " D128 "}, {%128,%129,%130,%131}, %132, 1, 1, 1, %133;"
    : R64(d, 0), R64(d, 64) : "r"(a[0]), "r"(a[1]), "r"(a[2]), "r"(a[3]), "l"(db), "n"(TB));
}
template <int TB> __device__ __forceinline__ void wgmma_rs256_z(float* d, const uint32_t* a, uint64_t db) {
  asm volatile("wgmma.mma_async.sync.aligned.m64n256k16.f32.bf16.bf16 " D128 "}, {%128,%129,%130,%131}, %132, 0, 1, 1, %133;"
    : W64(d, 0), W64(d, 64) : "r"(a[0]), "r"(a[1]), "r"(a[2]), "r"(a[3]), "l"(db), "n"(TB));
}
#define D32 "{%0,%1,%2,%3,%4,%5,%6,%7,%8,%9,%10,%11,%12,%13,%14,%15,%16,%17,%18,%19,%20,%21,%22,%23,%24,%25,%26,%27,%28,%29,%30,%31}"
__device__ __forceinline__ void wgmma_rs64(float* d, const uint32_t* a, uint64_t db) {
  asm volatile("wgmma.mma_async.sync.aligned.m64n64k16.f32.bf16.bf16 " D32 ", {%32,%33,%34,%35}, %36, 1, 1, 1, 0;"
    : R8(d, 0), R8(d, 8), R8(d, 16), R8(d, 24) : "r"(a[0]), "r"(a[1]), "r"(a[2]), "r"(a[3]), "l"(db));
}
__device__ __forceinline__ void wgmma_rs64_z(float* d, const uint32_t* a, uint64_t db) {
  asm volatile("wgmma.mma_async.sync.aligned.m64n64k16.f32.bf16.bf16 " D32 ", {%32,%33,%34,%35}, %36, 0, 1, 1, 0;"
    : W8(d, 0), W8(d, 8), W8(d, 16), W8(d, 24) : "r"(a[0]), "r"(a[1]), "r"(a[2]), "r"(a[3]), "l"(db));
}
__device__ __forceinline__ void issue_qk(float* S, const uint32_t* Q, uint64_t dk) {
  wgmma_rs64_z(S, Q, dk);
#pragma unroll
  for (int kk = 1; kk < 8; kk++) wgmma_rs64(S, Q + 4 * kk, dk + (kk >> 2) * 512 + (kk & 3) * 2);
}
__device__ __forceinline__ void issue_pv(float* O, const uint32_t* P, uint64_t dv, int acc) {
#pragma unroll
  for (int kk = 0; kk < 4; kk++) wgmma_rs128<1>(O, P + 4 * kk, dv + kk * 128, kk ? 1 : acc);
}

#define TS(i)
#define TSC(i)
#define TSX(i)
#define TSY(k) do { if ((tid & 127) == 0) TS((k) + 40 * wg); } while (0)
#define TT(k)
#define TV(k)
#define TR(k)
#define TH(k)
#define TA(k)
#define TAFLUSH()

struct SoftmaxState { float c0, c1, l0, l1; bool shifted; };
constexpr float SM_SCALE = 0.08838834764831845f * 1.4426950408889634f;
__device__ __forceinline__ void softmax_start(SoftmaxState& z) { z.c0 = z.c1 = z.l0 = z.l1 = 0.f; z.shifted = false; }
__device__ __forceinline__ void softmax_half(float* S, uint32_t* P, float* O, SoftmaxState& z, bool first, uint32_t tag) {
  const float lo0 = z.l0, lo1 = z.l1;
  float lim = 1.2676506002282294e30f;
  const float low = first ? 8.673617379884035e-19f : 0.f;
  if (z.shifted) {
#pragma unroll
    for (int j = 0; j < 32; j++) S[j] += (j & 2) ? z.c1 : z.c0;
  }
#pragma unroll 1
  while (true) {
    bb_fence(tag);
#pragma unroll
    for (int j = 0; j < 8; j++) {
      const float p0 = ex2(S[4 * j]), p1 = ex2(S[4 * j + 1]), p2 = ex2(S[4 * j + 2]), p3 = ex2(S[4 * j + 3]);
      z.l0 += p0; z.l1 += p2; z.l0 += p1; z.l1 += p3;
      P[2 * j] = pack2(p0, p1); P[2 * j + 1] = pack2(p2, p3);
    }
    if (!__any_sync(0xffffffffu, !(z.l0 < lim && z.l1 < lim && fminf(z.l0, z.l1) >= low) && lim > 0.f)) break;
    float d0 = fmaxf(S[0], S[1]), d1 = fmaxf(S[2], S[3]);
#pragma unroll
    for (int j = 1; j < 8; j++) { d0 = fmaxf(d0, fmaxf(S[4 * j], S[4 * j + 1])); d1 = fmaxf(d1, fmaxf(S[4 * j + 2], S[4 * j + 3])); }
    d0 = fmaxf(d0, __shfl_xor_sync(0xffffffffu, d0, 1)); d1 = fmaxf(d1, __shfl_xor_sync(0xffffffffu, d1, 1));
    d0 = fmaxf(d0, __shfl_xor_sync(0xffffffffu, d0, 2)); d1 = fmaxf(d1, __shfl_xor_sync(0xffffffffu, d1, 2));
    if (!first) { d0 = fmaxf(d0, 0.f); d1 = fmaxf(d1, 0.f); }
    z.shifted = true;
    z.c0 -= d0; z.c1 -= d1;
#pragma unroll
    for (int j = 0; j < 32; j++) S[j] -= (j & 2) ? d1 : d0;
    const float a0 = first ? 1.f : ex2(-d0), a1 = first ? 1.f : ex2(-d1);
    z.l0 = lo0 * a0; z.l1 = lo1 * a1;
    lim = -1.f;
    wg_wait<0>();
    reg_fence<64>(O);
#pragma unroll
    for (int j = 0; j < 16; j++) { O[4 * j] *= a0; O[4 * j + 1] *= a0; O[4 * j + 2] *= a1; O[4 * j + 3] *= a1; }
  }
}

__device__ __forceinline__ void modulate_frags(uint32_t* A, const uint32_t* V, const uint4* R, const uint32_t* ln) {
#pragma unroll
  for (int kk = 0; kk < 4; kk++) {
    const uint4 sa = R[kk >> 1], c1 = R[2 + (kk >> 1)];
#pragma unroll
    for (int j = 0; j < 4; j++) {
      const uint32_t n = hfma2(V[4 * kk + j], ln[(j & 1) * 2 + 1], ln[(j & 1) * 2]);
      A[4 * kk + j] = (kk & 1) ? ((j & 2) ? hfma2(n, c1.w, sa.x) : hfma2(n, c1.z, sa.w)) : ((j & 2) ? hfma2(n, c1.y, sa.z) : hfma2(n, c1.x, sa.y));
    }
  }
}
__device__ __forceinline__ void publish_record(uint4* dst, uint32_t pk, int src, int vec, bool doit) {
  const int r = vec ? 0 : 12;
  const uint32_t x = __shfl_sync(0xffffffffu, pk, src + r), y = __shfl_sync(0xffffffffu, pk, src + ((r + 4) & 12));
  const uint32_t z = __shfl_sync(0xffffffffu, pk, src + ((r + 8) & 12)), w = __shfl_sync(0xffffffffu, pk, src + ((r + 12) & 12));
  if (doit) st_pkt16(dst, ~x, y, z, w);
}
__device__ __forceinline__ void put_record(uint32_t sb, int idx, const uint4& v) {
  sts128(sb + SM_STASH + idx * 16, ~v.x, v.y, v.z, v.w);
  sts128(sb + SM_STASH + 16384 + idx * 16, ~v.x, v.y, v.z, v.w);
}
__device__ __forceinline__ float mod_value(float v, int vec) {
  v = rbf(v);
  return (vec ? rbf(1.f + v) : v) * SM_SCALE;
}

__device__ __forceinline__ void row_rcp(float& l0, float& l1) {
  l0 += __shfl_xor_sync(0xffffffffu, l0, 1); l1 += __shfl_xor_sync(0xffffffffu, l1, 1);
  l0 += __shfl_xor_sync(0xffffffffu, l0, 2); l1 += __shfl_xor_sync(0xffffffffu, l1, 2);
  l0 = rcp_f(l0); l1 = rcp_f(l1);
}
__device__ __forceinline__ void stage_o(const float* O, float r0, float r1, uint32_t stsm_addr) {
#pragma unroll
  for (int kk = 0; kk < 8; kk++) {
    stsm4((stsm_addr + (kk >> 2) * 8192) ^ ((kk & 3) * 32),
          pack2(O[8 * kk + 0] * r0, O[8 * kk + 1] * r0), pack2(O[8 * kk + 2] * r1, O[8 * kk + 3] * r1),
          pack2(O[8 * kk + 4] * r0, O[8 * kk + 5] * r0), pack2(O[8 * kk + 6] * r1, O[8 * kk + 7] * r1));
  }
}

__global__ void __cluster_dims__(2, 1, 1) __launch_bounds__(NTHREADS, 1)
fused_kernel(const Params p, const __grid_constant__ CUtensorMap mH, const __grid_constant__ CUtensorMap mWq,
             const __grid_constant__ CUtensorMap mK, const __grid_constant__ CUtensorMap mV,
             const __grid_constant__ CUtensorMap mO, const __grid_constant__ CUtensorMap mWo,
             const __grid_constant__ CUtensorMap mX, const __grid_constant__ CUtensorMap mOut,
             const __grid_constant__ CUtensorMap mWg, const __grid_constant__ CUtensorMap mWu,
             const __grid_constant__ CUtensorMap mWd, const __grid_constant__ CUtensorMap mWm,
             const __grid_constant__ CUtensorMap mWs) {
  extern __shared__ __align__(1024) uint8_t smem_raw[];
  TH(0);
  const uint32_t sb = smem_u32(smem_raw);
  const int tid = threadIdx.x;
  const int b0 = blockIdx.x;
  const int lane = tid & 31;
  const int role = __shfl_sync(0xffffffffu, tid >> 8, 0);

  if (b0 >= NMAIN) {
    const uint32_t tag = ld_relaxed(&g_epoch) + 1;
    const int sp = b0 - NMAIN, vec = 2 + sp;
    const int warp = __shfl_sync(0xffffffffu, tid >> 5, 0);
    float* sc = reinterpret_cast<float*>(smem_raw + SM_STASH);
    float* red = reinterpret_cast<float*>(smem_raw + SM_STASH + 4096);
    const int ridx = (lane >> 3) * 2 * RV + (sp & 1) * RV + 16 * RS + (sp >> 1) * 16 + (warp & 1) * 8 + (lane & 7);
    if (warp < 8) st_pkt16(&g_rec[warp >> 2][0][ridx + (warp & 2) * 16], 0, 0, 0, 0);
#pragma unroll 1
    for (int i = tid; i < 1024; i += NTHREADS) sc[i] = rbf(silu_f(__bfloat162float(p.c[i])));
    if (tid == 0) {
      tma_prefetch_desc(&mWs);
      for (int s = 0; s < NST2; s++) { mbar_init(sb + BAR_FULL2 + 8 * s, 1); mbar_init(sb + BAR_EMPTY2 + 8 * s, 8); }
      fence_async_smem();
      int it = 0;
      do { __nanosleep(100); spin_guard(it); } while (ld_pkt16(&g_lnst[8 * 32 + 16 * sp]).w != tag);
      if (SPD) __nanosleep(SPD);
    }
    __syncthreads();
    int s = 0; uint32_t ph = 0;
    if (tid == 0) TS(0);
    if (warp == 8) {
      const uint64_t pol = policy_evict_first();
#pragma unroll 1
      for (int n = 0; n < 80; n++) {
        mbar_wait_g(sb + BAR_EMPTY2 + 8 * s, ph ^ 1);
        if (elect_one()) {
          mbar_expect_tx(sb + BAR_FULL2 + 8 * s, 32768);
          if (n < 16) {
            tma_ld_hint(sb + s * ST2, &mWs, (sp & 1) * 1024 + 512 + (n >> 3) * 256 + (sp >> 1) * 128, (n & 7) * 128, sb + BAR_FULL2 + 8 * s, pol);
          } else {
#pragma unroll
            for (int j = 0; j < 4; j++) tma_ld_hint(sb + s * ST2 + j * 8192, &mWm, vec * 1024 + j * 256, (n - 16) * 16, sb + BAR_FULL2 + 8 * s, pol);
          }
        }
        __syncwarp();
        if (++s == NST2) { s = 0; ph ^= 1; }
      }
    } else if (warp < 8) {
      float acc[8];
#pragma unroll
      for (int i = 0; i < 8; i++) acc[i] = 0.f;
      auto stage = [&](uint32_t a0, int da, const float* cp, int dc) {
        mbar_wait_g(sb + BAR_FULL2 + 8 * s, ph);
#pragma unroll
        for (int i = 0; i < 8; i++) {
          const uint4 v = lds128(a0 + s * ST2 + i * da);
          const float c = cp[i * dc];
          acc[0] = fmaf(lo2f(v.x), c, acc[0]); acc[1] = fmaf(hi2f(v.x), c, acc[1]);
          acc[2] = fmaf(lo2f(v.y), c, acc[2]); acc[3] = fmaf(hi2f(v.y), c, acc[3]);
          acc[4] = fmaf(lo2f(v.z), c, acc[4]); acc[5] = fmaf(hi2f(v.z), c, acc[5]);
          acc[6] = fmaf(lo2f(v.w), c, acc[6]); acc[7] = fmaf(hi2f(v.w), c, acc[7]);
        }
        if (__shfl_sync(0xffffffffu, lane, __float_as_uint(acc[7]) & 31) < 32 && lane == 0) mbar_arrive(sb + BAR_EMPTY2 + 8 * s);
        if (++s == NST2) { s = 0; ph ^= 1; }
      };
#pragma unroll 1
      for (int n = 0; n < 16; n++) {
        stage(sb + tid * 16, 4096, sc + (n & 7) * 128 + (tid >> 4), 16);
        if ((n & 7) == 7) {
          float* r2 = red + 2048 + (n & 8) * 256;
#pragma unroll
          for (int i = 0; i < 8; i++) { r2[tid * 8 + i] = acc[i]; acc[i] = 0.f; }
          nb_sync(NB_CONS, 256);
          if (warp < 2) {
            float v0 = 0.f, v1 = 0.f;
#pragma unroll 4
            for (int i = 0; i < 16; i++) { const float2 e = reinterpret_cast<const float2*>(r2)[i * 64 + tid]; v0 += e.x; v1 += e.y; }
            publish_record(&g_rec[tag & 1][0][ridx + (n >> 3) * 32], pack2(mod_value(v0, sp & 1), mod_value(v1, sp & 1)),
                           (lane & 4) * 4 + (lane & 3), sp & 1, true);
          }
          if (tid == 0) TS(1 + (n >> 3));
        }
      }
#pragma unroll 1
      for (int n = 0; n < 64; n++) {
        stage(sb + ((tid >> 5) & 3) * 8192 + (tid >> 7) * 4096 + (tid & 31) * 16, 512, sc + n * 16 + (tid >> 7) * 8, 1);
      }
#pragma unroll
      for (int i = 0; i < 8; i++) red[(tid >> 7) * 1024 + (tid & 127) * 8 + i] = acc[i];
    }
    __syncthreads();
    float dot = 0.f;
#pragma unroll 1
    for (int i = tid; i < 512; i += NTHREADS) {
      uint32_t v = pack2(red[2 * i] + red[1024 + 2 * i], red[2 * i + 1] + red[1024 + 2 * i + 1]);
      st_pkt8(&g_mod[vec * 512 + i], v, tag);
      if (vec == 4) v = hadd2(v, ONE2);
      const uint32_t wr = reinterpret_cast<const uint32_t*>(p.w_r)[i];
      dot = fmaf(lo2f(v), lo2f(wr), fmaf(hi2f(v), hi2f(wr), dot));
    }
#pragma unroll
    for (int o = 16; o; o >>= 1) dot += __shfl_xor_sync(0xffffffffu, dot, o);
    if (lane == 0) sc[warp] = dot;
    __syncthreads();
    if (tid == 0) {
      dot = 0.f;
      for (int w = 0; w < 12; w++) dot += sc[w];
      fence_release_gpu();
      st_pkt8(&g_vdone[(vec - 2) * 16], __float_as_uint(dot), tag);
      TS(11);
#pragma unroll 1
      for (int i = 0; i < 128; i++) {
        const int u = i * 4 + (b0 - NMAIN);
        l2_prefetch(p.wo + (size_t)((4 * ((u >> 4) & 7) + (u >> 7)) * 128 + (u & 15) * 8) * 1024, 16384);
        __nanosleep(PFW);
      }
    }
    return;
  }

  const uint32_t rank = b0 & 1;
  const bool slab = !(b0 & 32), late = b0 & 16;
  const uint32_t c0 = clock();
  if (tid == 352) TS(0);
  auto load_slab = [&]() {
    const bf16* wp = p.w_mod + (size_t)(512 * rank + 2 * (tid & ~31) + 2 * (lane & 3) + ((lane >> 2) & 1)) * 6144 + 32 * (b0 >> 1) + 8 * (lane >> 3);
    const uint64_t pef = policy_evict_first();
#pragma unroll
    for (int i = 0; i < 8; i++)
      asm volatile("cp.async.cg.shared.global.L2::cache_hint [%0], [%1], 16, %2;"
        :: "r"(sb + SM_WSLAB + tid * 16 + i * 4096), "l"(wp + (size_t)i * 8 * 6144), "l"(pef) : "memory");
  };
  if (tid == 256) {
    mbar_init(sb + BAR_XH, 1);
    fence_async_smem();
    mbar_expect_tx(sb + BAR_XH, 32768);
    if (XD) while ((uint32_t)clock() - c0 < XD) {}
#pragma unroll
    for (int i = 0; i < 2; i++)
      asm volatile("cp.async.bulk.shared::cluster.global.mbarrier::complete_tx::bytes [%0], [%1], 16384, [%2];"
        :: "r"(sb + SM_XROW + i * ST1), "l"(p.x + (size_t)b0 * 16384 + i * 8192), "r"(sb + BAR_XH) : "memory");
  }
  __syncwarp();
  uint32_t cw[8];
#pragma unroll
  for (int i = 0; i < 8; i++) cw[i] = 0;
  if (!role && slab) {
#pragma unroll
    for (int i = 0; i < 8; i++) cw[i] = ld_relaxed(reinterpret_cast<const uint32_t*>(p.c) + 256 * rank + (tid & ~28) + 4 * i);
  }
  uint32_t epoch = 0;
  if (!role) epoch = ld_relaxed(&p.sc->epoch[lane]);
  if (!role && slab && !late) load_slab();
#define TILE_ROLES() \
  mbar_wait(sb + BAR_ROLE, 0); \
  const int b = 2 * __shfl_sync(0xffffffffu, lds32(sb + SM_ROLE), 0) + rank; \
  const int rt = b >> 3;     \
  const int ct = b & 7;

  if (role) {
    asm volatile("setmaxnreg.dec.sync.aligned.u32 24;");
    const int warp = __shfl_sync(0xffffffffu, tid >> 5, 0);
    if (tid == 256) {
      mbar_init(sb + BAR_RED, 1);
      for (int s = 0; s < 2; s++) mbar_init(sb + BAR_OF + 8 * s, 1);
      mbar_init(sb + BAR_ROLE, 1);
      for (int s = 0; s < 5; s++) { mbar_init(sb + BAR_FULL1 + 8 * s, 1); mbar_init(sb + BAR_EMPTY1 + 8 * s, 4); }
      for (int s = 0; s < 2; s++) { mbar_init(sb + BAR_STASH + 8 * s, 1); mbar_init(sb + BAR_X + 8 * s, 1); }
      for (int s = 0; s < 4; s++) mbar_init(sb + BAR_HS + 8 * s, 1);
      mbar_init(sb + BAR_G, 16); mbar_init(sb + BAR_T1, 1); mbar_init(sb + BAR_HF, 1);
      mbar_init(sb + BAR_SFREE, 4); mbar_init(sb + BAR_TFREE, 8);
      mbar_init(sb + BAR_FFN, 4); mbar_init(sb + BAR_FFN + 8, 2);
      mbar_init(sb + BAR_CAND, 1); mbar_init(sb + BAR_VEC, 32); for (int s = 0; s < 3; s++) mbar_init(sb + BAR_TAB + 8 * s, 32);
      mbar_expect_tx(sb + BAR_RED, 1024);
      mbar_expect_tx(sb + BAR_ROLE, 4);
      asm volatile("fence.mbarrier_init.release.cluster;" ::: "memory");
    }
    __syncwarp();
    asm volatile("barrier.cluster.arrive.relaxed.aligned;" ::: "memory");
    const int ridx = ((lane >> 1) & 3) * 2 * RV + (b0 >> 6) * RV + ((b0 >> 1) & 31) * RS + 2 * rank + (lane & 1) + (lane >> 3) * 4;
    if (warp == 11 && slab && lane < 2 * RS) { st_pkt16(&g_rec[0][0][ridx], 0, 0, 0, 0); st_pkt16(&g_rec[1][0][ridx], 0, 0, 0, 0); }
    if (tid == 256) {
      tma_prefetch_desc(&mWq); tma_prefetch_desc(&mX); tma_prefetch_desc(&mH); tma_prefetch_desc(&mK); tma_prefetch_desc(&mV); tma_prefetch_desc(&mO);
    }
    uint32_t pairid = 0;
    if (tid == 320 && rank == 0) {
      uint32_t t;
      asm("mov.u32 %0, %%smid;" : "=r"(t));
      t >>= 1;
      uint32_t grp = ((0x73216540u >> (4 * ((t < 32 ? t : t < 60 ? 1 + (t - 32) % 7 : t < 62 ? t - 54 : 0) & 7))) & 7) - 1, slot;
      int it = 0;
      do {
        grp = (grp + 1) & 7;
        asm volatile("atom.relaxed.gpu.global.add.u32 %0, [%1], 1;" : "=r"(slot) : "l"(&p.sc->ticket[grp * 32]) : "memory");
        spin_guard(it);
      } while (slot >= 8);
      pairid = slot * 8 + grp;
    }
    __syncwarp();
    asm volatile("barrier.cluster.wait.aligned;" ::: "memory");
    if (tid == 320 && rank == 0) {
#pragma unroll
      for (int r = 0; r < 2; r++)
        asm volatile("st.async.weak.shared::cluster.mbarrier::complete_tx::bytes.b32 [%0], %1, [%2];"
          :: "r"(mapa(sb + SM_ROLE, r)), "r"(pairid), "r"(mapa(sb + BAR_ROLE, r)) : "memory");
    }
    __syncwarp();
    const uint32_t tag = ld_relaxed(&g_epoch) + 1;
    if (warp == 8) {
      TILE_ROLES();
      const int kvrow = (ct >> 1) * 2048 + 1536, arow = rt * 128 + rank * 64;
      const uint64_t pef = policy_evict_first();
#pragma unroll 1
      for (int pair = 0; pair < 2; pair++) {
        const int wblk = (4 * ct + 2 * pair) * 2;
        if (pair) { mbar_wait_g(sb + BAR_HF, 0); fence_async_global(); }
#pragma unroll 1
        for (int n = 0; n < 16; n++) {
          const uint32_t s = n & 3, st = sb + SM_RING + s * ST1, fb = sb + BAR_FULL1 + 8 * s;
          if (n == 2 && pair == 0) mbar_wait_g(sb + BAR_G, 0);
          mbar_wait_g(fb + (BAR_EMPTY1 - BAR_FULL1), ((n >> 2) & 1) ^ 1);
          if (elect_one()) {
            mbar_expect_tx(fb, 49152);
            if (pair) tma_ld_mc_hint(st + rank * 8192, &mH, n * 64, arow, fb, pef); else
            tma_ld_mc(st + rank * 8192, pair ? &mH : &mX, n * 64, arow, fb);
            tma_ld3_hint(st + 16384, &mWq, n * 64, wblk, fb, pef);
          }
          __syncwarp();
        }
#pragma unroll 1
        for (int n = 0; n < 16; n++) {
          const uint32_t s = n & 3, st = sb + SM_RING + s * ST1 + rank * 8192, fb = sb + BAR_FULL1 + 8 * s;
          const int h0 = n == 0 ? 0 : n == 15 ? 14 : n + 1, h1 = n == 0 ? 1 : n == 15 ? 15 : n - 1;
          mbar_wait_g(fb + (BAR_EMPTY1 - BAR_FULL1), ((n >> 2) & 1) ^ 1);
          if (elect_one()) {
            mbar_expect_tx(fb, 32768);
            tma_ld_mc(st, n == 15 ? &mV : &mK, rank * 64, kvrow + (h0 & 7) * 64, fb);
            tma_ld_mc(st + 16384, n == 0 ? &mK : &mV, rank * 64, kvrow + (h1 & 7) * 64, fb);
            if (n == 3 && pair == 1) mbar_arrive(sb + BAR_T1);
          }
          __syncwarp();
        }
      }
      {
        uint32_t s = 0, ph = 1;
#pragma unroll 1
        for (int half = 0; half < 2; half++) {
          mbar_wait_g(sb + BAR_OF + 8 * half, 0);
          fence_async_global();
#pragma unroll 1
          for (int n = 32 * half; n < 32 * half + 32; n++) {
            const uint32_t st = sb + SM_RING + s * ST1, fb = sb + BAR_FULL1 + 8 * s;
            const int k0 = ((n & 14) * 2 + (n >> 4)) * 128 + (n & 1) * 64;
            mbar_wait_g(n == 8 ? sb + BAR_SFREE : fb + (BAR_EMPTY1 - BAR_FULL1), n == 8 ? 0 : ph ^ (s >> 2));
            if (elect_one()) {
              mbar_expect_tx(fb, 32768);
              tma_ld_mc_hint(st + rank * 8192, &mO, k0, arow, fb, pef);
              tma_ld3_hint(st + 16384, &mWo, k0, 2 * ct, fb, pef);
            }
            __syncwarp();
            if (++s == 5 || n == 3) { s = 0; ph ^= 1; }
          }
        }
        if (b < NFFN) {
#pragma unroll 1
          for (s = 0; s < 2; s++) {
            mbar_wait_g(sb + BAR_EMPTY1 + 8 * s, 0);
            if (elect_one()) {
              mbar_expect_tx(sb + BAR_FFN + 8, 32768);
              tma_ld3_hint(sb + SM_RING + s * ST1, &mWd, b * 32, s * 8, sb + BAR_FFN + 8, pef);
            }
            __syncwarp();
          }
        }
      }
    } else if (warp <= 10) {
      const int w = warp - 9;
      TILE_ROLES();
      const uint32_t st = sb + SM_STASH + w * 16384;
#pragma unroll 1
      for (int j = 0; j < 2; j++) {
        nb_sync(NB_OST + w, 160);
        if (elect_one()) {
          fence_async_smem();
          tma_st(&mH, (2 * ct + j) * 64, rt * 128 + w * 64, st + 4096);
          bulk_commit();
          bulk_wait_read();
          mbar_arrive(sb + BAR_HS + 16 * w + 8 * j);
          if (j) {
            bulk_wait_all();
            fence_async_global();
            fence_release_gpu();
            red_add_relaxed(&g_hflag[rt * 32], 1);
          }
        }
        __syncwarp();
      }
#pragma unroll 1
      for (int r = 0; r < 4; r++) {
        nb_sync(NB_OST + w, 160);
        if (elect_one()) {
          fence_async_smem();
          const int hcol = (4 * ct + r) * 128;
          tma_st(&mO, hcol, rt * 128 + w * 64, st);
          tma_st(&mO, hcol + 64, rt * 128 + w * 64, st + 8192);
          bulk_commit();
          bulk_wait_read();
          if (r < 2) {
            mbar_arrive(sb + BAR_STASH + 8 * w);
          } else if (r == 2) {
            mbar_expect_tx(sb + BAR_X + 8 * w, 16384);
            tma_ld_hint(st, &mX, ct * 128, rt * 128 + w * 64, sb + BAR_X + 8 * w, policy_evict_first());
            tma_ld_hint(st + 8192, &mX, ct * 128 + 64, rt * 128 + w * 64, sb + BAR_X + 8 * w, policy_evict_first());
          } else {
            mbar_arrive_cl(mapa(sb + BAR_SFREE, 0)); mbar_arrive_cl(mapa(sb + BAR_SFREE, 1));
          }
          bulk_wait_all();
          fence_async_global();
          fence_release_gpu();
          red_add_relaxed(&g_oflag[(rt * 4 + r) * 32], 1);
        }
        __syncwarp();
      }
      nb_sync(NB_OST + w, 160);
      int skip = -1;
      mbar_wait_g(sb + BAR_CAND, 0);
      const bool has_cand = (lds32(sb + SM_CAND) >> 6) == w;
      if (has_cand) {
        nb_sync(NB_WIN + w, 160);
        skip = (int)lds32(sb + SM_WROW + 4 * w) - (rt * 128 + w * 64);
      }
      if ((unsigned)skip >= 64u) {
        if (elect_one()) {
          fence_async_smem();
          tma_st(&mOut, ct * 128, rt * 128 + w * 64, sb + SM_OUT + w * 16384);
          tma_st(&mOut, ct * 128 + 64, rt * 128 + w * 64, sb + SM_OUT + w * 16384 + 8192);
          bulk_commit();
          bulk_wait_read();
        }
        __syncwarp();
      } else {
        uint4* dst = reinterpret_cast<uint4*>(p.out + (size_t)(rt * 128 + w * 64 + (lane >> 4)) * 1024 + ct * 128) + (lane & 15);
#pragma unroll 2
        for (int r = lane >> 4; r < 64; r += 2) {
          const uint4 v = lds128(sb + SM_OUT + w * 16384 + ((lane >> 3) & 1) * 8192 + r * 128 + (((lane ^ r) & 7) * 16));
          if (r != skip) *dst = v;
          dst += 256;
        }
      }
      if (!has_cand) nb_sync(NB_WIN + w, 160);
    } else {
      if (slab) {
        mbar_wait_g(sb + BAR_RED, 0);
        float v = 0.f;
#pragma unroll
        for (int w = 0; w < 8; w++) v += lds_f32(sb + SM_RED + w * 128 + lane * 4);
        v += __shfl_xor_sync(0xffffffffu, v, 16);
        v = mod_value(v, b0 >> 6);
        publish_record(&g_rec[tag & 1][0][ridx], pack2(v, __shfl_down_sync(0xffffffffu, v, 1)), 2 * (lane & 1), b0 >> 6, lane < 8);
        if (lane == 0) TS(1);
      }
      mbar_wait_g(sb + BAR_G, 0);
#pragma unroll 1
      for (int i = 1; i < 4; i++) {
        const uint4* mp = &g_rec[tag & 1][(b0 >> 1) & (NREP - 1)][i == 1 ? (8 + (lane >> 2)) * RS + (lane & 3) : 16 * RS - 64 + 32 * i + lane];
        uint4 v0, v1; int it = 0;
        while (true) {
          v0 = ld_pkt16(mp); v1 = ld_pkt16(mp + RV);
          if (v0.x != 0 && v1.x != 0) break;
          spin_guard(it); __nanosleep(PLD);
        }
        put_record(sb, 32 * i + lane, v0);
        put_record(sb, 128 + 32 * i + lane, v1);
        mbar_arrive(sb + BAR_TAB - 8 + 8 * i);
        if (lane == 0) {
          TS(3 + i + (i > 2));
          if (i == 1) l2_prefetch(((b0 & 64) ? p.vc : p.kc) + (size_t)(((b0 >> 4) & 3) * 2048 + 1536) * 128 + (b0 & 15) * 4096, 8192);
        }
        __syncwarp();
      }
      TILE_ROLES();
      if (lane == 0) {
        int it = 0;
        do { __nanosleep(500); spin_guard(it); } while (ld_relaxed(&g_hflag[rt * 32]) != tag * 16u);
        fence_acquire_gpu();
        mbar_arrive(sb + BAR_HF);
        if (b < NFFN) for (int i = 0; i < 8; i++) { __nanosleep(800); l2_prefetch(p.wd + (size_t)(b * 32 + i * 4) * 1024, 8192); }
      }
      __syncwarp();
      {
        uint2 v; int it = 0;
        do { __nanosleep(1000); v = ld_pkt8(&g_vdone[(lane & 3) * 16]); spin_guard(it); }
        while (!(v.y == tag));
        __syncwarp();
        fence_acquire_gpu();
        if (lane == 1 || lane == 2) sts32(sb + SM_SCAL + (2 - lane) * 4, v.x);
      }
#pragma unroll 1
      for (int i = 0; i < 2; i++) {
        const int q = i * 32 + lane, pi = ct * 64 + q;
        const uint32_t vga = g_mod[2 * 512 + pi].x, vsb = g_mod[3 * 512 + pi].x, vcb = g_mod[4 * 512 + pi].x, vgb = g_mod[5 * 512 + pi].x;
        const uint32_t wr = reinterpret_cast<const uint32_t*>(p.w_r)[pi];
        const uint32_t c1 = hadd2(vcb, ONE2);
        const float al = lo2f(c1) * lo2f(wr), ah = hi2f(c1) * hi2f(wr);
        const uint32_t o8 = (q & 3) * 8 + ((q >> 2) & 1) * 4;
        sts32(sb + SM_GA + (q >> 3) * 32 + o8, vga);
        sts128(sb + SM_REC + q * 16, c1, vsb, vgb, 0);
        const uint32_t ahi = pack2(al, ah), alo = pack2(al - lo2f(ahi), ah - hi2f(ahi));
        const uint32_t ba = sb + SM_B1 + (q >> 3) * 128 + o8;
        sts32(ba, ONE2); sts32(ba + 32, ahi); sts32(ba + 64, alo); sts32(ba + 96, 0);
      }
      if (lane == 0) TS(28);
      if (lane == 0) {
        tma_prefetch_desc(&mWo); tma_prefetch_desc(&mOut); tma_prefetch_desc(&mWd); tma_prefetch_desc(&mWg); tma_prefetch_desc(&mWu);
#pragma unroll 1
        for (int r = 0; r < 4; r++) {
          int it = 0;
          do { __nanosleep(200); spin_guard(it); } while (ld_relaxed(&g_oflag[(rt * 4 + r) * 32]) != tag * 16u);
          if (r & 1) { fence_acquire_gpu(); mbar_arrive(sb + BAR_OF + 8 * (r >> 1)); }
          if (r == 1 && b < NFFN) {
            const uint64_t pef = policy_evict_first();
            mbar_wait_g(sb + BAR_T1, 0);
#pragma unroll 1
            for (int i = 0; i < 4; i++) {
              mbar_expect_tx(sb + BAR_FFN, 16384);
              tma_ld_hint(sb + SM_RING + i * ST1 + 32768, &mWg, b * 32, i * 256, sb + BAR_FFN, pef);
              __nanosleep(GATED);
            }
          }
        }
      }
      __syncwarp();
      if (b < NFFN) {
        mbar_wait_g(sb + BAR_TFREE, 0);
        const uint64_t pef = policy_evict_first();
#pragma unroll 1
        for (int i = 0; i < 5; i++) {
          if (i > 0 && lane == 0) {
            mbar_expect_tx(sb + BAR_FFN, 16384);
            tma_ld_hint(sb + SM_RING + (i - 1) * ST1 + 32768, &mWu, b * 32, (i - 1) * 256, sb + BAR_FFN, pef);
          }
          if (i < 4) {
#pragma unroll 1
            for (int j = 0; j < 8; j++) {
              asm volatile("prefetch.global.L2 [%0];" :: "l"(p.wu + (size_t)(i * 256 + j * 32 + lane) * 3584 + b * 32) : "memory");
              __nanosleep(UPD);
            }
            __nanosleep(500);
          }
        }
      }
      if (lane == 0) TS(29);
#pragma unroll 1
      for (int i = lane; i < 128; i += 32) st_pkt16(&g_stats[b * 128 + i], 0, 0, 0, 0);
      st_pkt16(&g_cand[b * 32 + lane], 0, 0, 0, 0);
      if (lane < ESTR) st_pkt16(&g_entry[(ct * 16 + rt) * ESTR + lane], 0, 0, 0, 0);
#pragma unroll 1
      for (int i = lane; i < (b < NFFN ? 512 : 0); i += 32) st_pkt16(&g_ypart[((i >> 2) * NFFN + b) * 4 + (i & 3)], 0, 0, 0, 0);
      mbar_arrive(sb + BAR_VEC);
      uint4* const cp = &g_cand[b * 32 + lane];
      uint4* const ep = &g_entry[(ct * 16 + rt) * ESTR];
      nb_sync(NB_AMAX, 288);
      TV(0);
      const uint4 e = lds128(sb + SM_AMAX + (lane & 7) * 16);
      const int tmax = __reduce_max_sync(0xffffffffu, (int)e.x);
      const int wl = __ffs(__ballot_sync(0xffffffffu, (int)e.x == tmax)) - 1;
      const uint32_t row = __shfl_sync(0xffffffffu, e.y, wl);
      const uint32_t xa = sb + SM_X2 + (row >> 6) * 16384 + (lane >> 4) * 8192 + (row & 63) * 128 + (lane & 3) * 4
                        + ((((lane >> 1) & 6) ^ (row & 7)) * 16);
      const uint32_t v0 = lds32(xa), v1 = lds32(xa ^ 16);
      if (lane == wl) st_pkt16(ep, e.w, rt * 128 + row, e.z, tag);
      st_pkt16(cp, v0, v1, tag, 0);
      if (lane == 0) { sts32(sb + SM_CAND, row); mbar_arrive(sb + BAR_CAND); }
      TV(1);
      if (lane == 0) TS(15);
    }
  } else {
    const int warp = tid >> 5;
    const int wg = warp >> 2, wq = warp & 3;
    const int g = lane >> 2, t = lane & 3;
    uint32_t tag;
    uint32_t ln[4];
    float acc[128];
    uint32_t bf[16];
    auto gemv = [&]() {
          asm volatile("cp.async.wait_all;" ::: "memory");
          float d0[4] = {0.f, 0.f, 0.f, 0.f}, d1[4] = {0.f, 0.f, 0.f, 0.f};
#pragma unroll
          for (int i = 0; i < 8; i++) {
            const uint4 wv = lds128(sb + SM_WSLAB + tid * 16 + i * 4096);
            const uint32_t a[4] = {wv.x, wv.y, wv.z, wv.w};
            mma16816((i & 1) ? d1 : d0, a, bf[2 * i], bf[2 * i + 1]);
          }
#pragma unroll
          for (int i = 0; i < 4; i++) { d0[i] += d1[i]; d0[i] += __shfl_xor_sync(0xffffffffu, d0[i], 6); }
          const uint32_t dst = mapa(sb + SM_MISC, t & 1) - SM_MISC;
          if (!(lane & 6)) st_async_f32x4(dst + SM_RED + warp * 128 + rank * 64 + g * 8, d0, dst + BAR_RED);
          TH(4);
    };
    {
      asm volatile("barrier.cluster.arrive.relaxed.aligned;" ::: "memory");
      if (lane == 0) st_pkt16(&g_lnst[8 * b0 + warp], 0, 0, 0, 0);
      TH(1);
      asm volatile("setmaxnreg.inc.sync.aligned.u32 240;");
      TH(2);
#pragma unroll
      for (int i = 0; i < 8; i++) {
        const float sv = silu_f((g & 4) ? hi2f(cw[i]) : lo2f(cw[i]));
        const uint32_t sp = (g & 1) ? pack2(0.f, sv) : pack2(sv, 0.f);
        bf[2 * i] = (g & 2) ? 0 : sp; bf[2 * i + 1] = (g & 2) ? sp : 0;
      }
      asm volatile("barrier.cluster.wait.aligned;" ::: "memory");
#pragma unroll
      for (int i = 0; i < 128; i++) acc[i] = 0.f;
      reg_fence<128>(acc);
      tag = __shfl_sync(0xffffffffu, epoch, 0) + 1;
      if (slab && late) { while ((uint32_t)clock() - c0 < WL) {} load_slab(); }
      TH(3);
      if (slab && !late) gemv();
      {
        {
          mbar_wait(sb + BAR_XH, 0);
          TH(5);
          float ds[4] = {0.f, 0.f, 0.f, 0.f}, dq[4][4];
#pragma unroll
          for (int i = 0; i < 4; i++) { dq[i][0] = dq[i][1] = dq[i][2] = dq[i][3] = 0.f; }
#pragma unroll
          for (int i = 0; i < 8; i++) {
            uint32_t a[4];
            ldsm4(sb + SM_XROW + wg * ST1 + wq * 4096 + ((lane >> 3) & 1) * 2048 + i * 256 + (lane >> 4) * 128 + (lane & 7) * 16, a);
            mma16816(ds, a, ONE2, ONE2);
            mma1688(dq[0], a[0], a[1], a[0]); mma1688(dq[1], a[0], a[1], a[1]);
            mma1688(dq[2], a[2], a[3], a[2]); mma1688(dq[3], a[2], a[3], a[3]);
          }
          const bool dg = t == (g >> 1);
          const float q0 = dg ? ((g & 1) ? dq[0][1] + dq[2][1] : dq[0][0] + dq[2][0]) : 0.f;
          const float q1 = dg ? ((g & 1) ? dq[1][3] + dq[3][3] : dq[1][2] + dq[3][2]) : 0.f;
          float q = ((lane & 1) ? q1 : q0) + __shfl_xor_sync(0xffffffffu, (lane & 1) ? q0 : q1, 1);
          float sm = (lane & 1) ? ds[2] : ds[0];
          q += __shfl_xor_sync(0xffffffffu, q, 2);
#pragma unroll
          for (int o = 4; o <= 16; o <<= 1) { q += __shfl_xor_sync(0xffffffffu, q, o); sm += __shfl_xor_sync(0xffffffffu, sm, o); }
          const float mean = sm * (1.f / 1024.f);
          const float rd = rcp_f(rbf(sqrt_f(rbf(rbf(fmaxf(fmaf(-mean, mean, q * (1.f / 1024.f)), 0.f)) + 1e-5f))));
          const float mean1 = __shfl_sync(0xffffffffu, mean, 1), rd1 = __shfl_sync(0xffffffffu, rd, 1);
          const uint32_t rh = pack2(rd, rd1);
          if (lane == 0) st_pkt16(&g_lnst[8 * b0 + warp], pack2(-rbf(mean) * lo2f(rh), -rbf(mean1) * hi2f(rh)), rh, 0, tag);
          TH(6);
          if (tid == 0) TS(2);
        }
      }
    }
    if (slab && late) gemv();
    TILE_ROLES();
    const uint32_t xa0 = sb + SM_RING + (warp * 16 + (lane & 15)) * 128 + (((lane >> 4) ^ (lane & 7)) * 16);
    uint32_t V[16];
    {
      const uint4* mp = &g_rec[tag & 1][(b0 >> 1) & (NREP - 1)][RV * wg + (lane >> 2) * RS + (lane & 3)];
      const uint4* lp = &g_lnst[(8 * rt + warp) * 8 + (g >> 1)];
      mbar_wait(sb + BAR_FULL1, 0);
#pragma unroll
      for (int kk = 0; kk < 4; kk++) ldsm4(xa0 ^ (kk * 32), V + 4 * kk);
      uint4 v0 = make_uint4(1, 0, 0, 0), l0, l1;
      int it = 0;
      while ((uint32_t)clock() - c0 < HD) {}
      do { if (wq == 0) v0 = ld_pkt16(mp);
           l0 = ld_pkt16(lp); l1 = ld_pkt16(lp + 4); spin_guard(it); }
        while (!(__all_sync(0xffffffffu, v0.x != 0 && l0.w == tag && l1.w == tag)));
      TH(7);
      if (wq == 0) put_record(sb, 128 * wg + lane, v0);
      const uint32_t sel = (g & 1) ? 0x3232 : 0x1010;
      ln[0] = __byte_perm(l0.x, 0, sel); ln[1] = __byte_perm(l0.y, 0, sel);
      ln[2] = __byte_perm(l1.x, 0, sel); ln[3] = __byte_perm(l1.y, 0, sel);
      __syncwarp();
      if (lane < 2) mbar_arrive_cl(mapa(sb + BAR_G, lane));
      nb_sync(NB_CONS, 256);
      if (tid == 0) TS(3);
      TH(13);
    }

    const uint32_t rel = mapa(sb + SM_MISC, lane & 1) - SM_MISC;
    const uint32_t stsm_addr = sb + SM_STASH + wg * 16384 + (wq * 16 + (lane & 15)) * 128 + (((lane >> 4) ^ (lane & 7)) * 16);

    uint32_t ph = 0;
    uint32_t X[32];
    {
      const uint32_t tab0 = sb + SM_STASH + wg * 16384 + t * 16;
      const uint64_t db0 = mk_desc(sb + SM_RING + 16384, 8192);
      uint32_t A[2][16];
      uint32_t xa[4];
#pragma unroll
      for (int kk = 0; kk < 4; kk++) xa[kk] = xa0 ^ (kk * 32);
      uint32_t tab = tab0;
      reg_fence<4>(xa);
      asm volatile("{\n.reg .pred p;\nsetp.eq.u32 p, %4, 0;\n@p ld.shared.v4.u32 {%0,%1,%2,%3}, [%5];\n}"
        : "+r"(ln[2]), "+r"(ln[0]), "+r"(ln[3]), "+r"(ln[1]) : "r"(tag), "r"(sb));
      int hs = 2 * ct;
      uint4 R[4];
#pragma unroll
      for (int kk = 0; kk < 4; kk++) R[kk] = lds128(tab + (kk >> 1) * 2048 + (kk & 1) * 64);
#pragma unroll 1
      for (int k4 = 0; k4 < 4; k4++) {
#pragma unroll
        for (int s = 0; s < 4; s++) {
          uint32_t* a = A[s & 1];
          const int sn = (s + 1) & 3;
          const uint32_t pn = (k4 + (s == 3)) & 1;
          modulate_frags(a, V, R, ln);
          if (hs == (s & 2)) {
            if (s & 1) mbar_wait(sb + BAR_HS + 16 * wg, 0);
#pragma unroll
            for (int kk = 0; kk < 4; kk++) stsm4((stsm_addr + 4096) ^ (kk * 32), a[4 * kk], a[4 * kk + 1], a[4 * kk + 2], a[4 * kk + 3]);
            nb_arrive(NB_OST + wg, 160);
          }
          if (s == 0 && k4 == 0) TH(8);
          if (s == 0 && k4 == 0 && tid == 0) { TS(6); TSC(61); }
          wg_fence();
#pragma unroll
          for (int kk = 0; kk < 4; kk++) wgmma_rs256<1>(acc, a + 4 * kk, db0 + s * (ST1 >> 4) + kk * 128);
          wg_commit();
          if (s == 3 && k4 < 3) mbar_wait(sb + BAR_TAB + 8 * k4, 0);
#pragma unroll
          for (int kk = 0; kk < 4; kk++) R[kk] = lds128(tab + (s + 1) * 128 + (kk >> 1) * 2048 + (kk & 1) * 64);
          wg_wait<1>();
          if (k4 == 0) TH(9 + s);
          reg_fence<16>(A[(s & 1) ^ 1]);
          if ((tid & 127) < 2 && (s | k4)) mbar_arrive_cl(rel + BAR_EMPTY1 + 8 * ((s + 3) & 3));
          if (s < 3 || k4 < 3) {
            mbar_wait(sb + BAR_FULL1 + 8 * sn, pn);
#pragma unroll
            for (int kk = 0; kk < 4; kk++) ldsm4(xa[kk] + sn * ST1, V + 4 * kk);
          }
        }
        tab += 512; hs -= 4;
      }
      mbar_wait(sb + BAR_HS + 16 * wg + 8, 0);
      wg_wait<0>();
      reg_fence<128>(acc);
    }
#pragma unroll 1
    for (int pair = 0; pair < 2; pair++) {
      uint32_t Q[32];
      TR(0);
      {
        if ((tid & 127) < 2) mbar_arrive_cl(rel + BAR_EMPTY1 + 8 * 3);
        if (pair == 1) mbar_wait(sb + BAR_STASH + 8 * wg, 1);
#pragma unroll
        for (int i = 0; i < 32; i++) Q[i] = pack2(acc[2 * i], acc[2 * i + 1]);
        const uint32_t qs = sb + SM_STASH + wg * 16384 + wq * 2048 + lane * 16;
#pragma unroll
        for (int i = 0; i < 8; i++)
          sts128(qs + (i & 3) * 512 + (i >> 2) * 8192, pack2(acc[64 + 8 * i], acc[65 + 8 * i]), pack2(acc[66 + 8 * i], acc[67 + 8 * i]),
                 pack2(acc[68 + 8 * i], acc[69 + 8 * i]), pack2(acc[70 + 8 * i], acc[71 + 8 * i]));
      }
      if (tid == 0) TS(8 + pair * 2);
      TR(1);
      float O[64], SL[32], SH[32];
      uint32_t PL[16], PH[16];
      SoftmaxState z;
      const uint64_t d0 = mk_desc(sb + SM_RING, 8192);
      {
        mbar_wait(sb + BAR_FULL1, ph);
        wg_fence();
        issue_qk(SL, Q, d0);
        wg_commit();
        issue_qk(SH, Q, d0 + 1024);
        wg_commit();
#pragma unroll
        for (int i = 0; i < 64; i++) O[i] = 0.f;
        reg_fence<64>(O);
        wg_wait<1>();
        reg_fence<32>(SL);
        softmax_start(z);
        softmax_half(SL, PL, O, z, true, tag);
        wg_wait<0>();
        reg_fence<32>(SH);
        if ((tid & 127) < 2) mbar_arrive_cl(rel + BAR_EMPTY1);
      }
      float lp0 = 0.f, lp1 = 0.f;
      uint32_t dB = (uint32_t)d0 + 1 * (ST1 >> 4), dA = (uint32_t)d0 + 2 * (ST1 >> 4);
      const uint32_t dBx = dB ^ ((uint32_t)d0 + 3 * (ST1 >> 4)), dAx = dA ^ (uint32_t)d0;
      uint32_t so = 0;
      bool ready = false;
#pragma unroll 1
      for (int i = 0; i < 7; i++) {
        TA(0);
        TR(2 + i);
        if (!ready) mbar_wait(sb + BAR_FULL1 + 8 + so, ph);
        TA(1);
        TA(2);
        wg_fence();
        issue_qk(SL, Q, (d0 & 0xffffffff00000000ull) | dB);
        if (i == 4) {
          __syncwarp();
          stage_o(O, lp0, lp1, stsm_addr);
        }
        wg_fence();
        issue_pv(O, PL, ((d0 & 0xffffffff00000000ull) | dB) + 1024, i != 4);
        wg_commit();
        if (i == 4) {
          nb_arrive(NB_OST + wg, 160);
        }
        TA(3);
        ph ^= i & 1;
        ready = mbar_test(sb + BAR_FULL1 + 16 - so, ph);
        softmax_half(SH, PH, O, z, false, tag);
        TA(4);
        wg_wait<0>();
        TA(5);
        reg_fence<32>(SL); reg_fence<16>(PL);
        if ((tid & 127) < 2) mbar_arrive_cl(rel + BAR_EMPTY1 + 8 + so);
        if (!ready) mbar_wait(sb + BAR_FULL1 + 16 - so, ph);
        TA(6);
        wg_fence();
        issue_qk(SH, Q, (d0 & 0xffffffff00000000ull) | dA);
        wg_commit();
        issue_pv(O, PH, ((d0 & 0xffffffff00000000ull) | dA) + 1024, 1);
        wg_commit();
        if (i == 2) {
          wg_wait<1>();
          reg_fence<32>(Q);
          const uint32_t qs = sb + SM_STASH + wg * 16384 + wq * 2048 + lane * 16;
#pragma unroll
          for (int j = 0; j < 8; j++) { const uint4 v = lds128(qs + (j & 3) * 512 + (j >> 2) * 8192); Q[4 * j] = v.x; Q[4 * j + 1] = v.y; Q[4 * j + 2] = v.z; Q[4 * j + 3] = v.w; }
        }
        TA(10);
        if (i == 3) { lp0 = z.l0; lp1 = z.l1; row_rcp(lp0, lp1); softmax_start(z); }
        TA(7);
        so ^= 16; dB ^= dBx; dA ^= dAx;
        ready = mbar_test(sb + BAR_FULL1 + 8 + so, ph);
        softmax_half(SL, PL, O, z, i == 3, tag);
        TA(8);
        wg_wait<0>();
        TA(9);
        reg_fence<32>(SH); reg_fence<16>(PH); reg_fence<64>(O); reg_fence<32>(Q);
        if ((tid & 127) < 2) mbar_arrive_cl(rel + BAR_EMPTY1 + so);
      }
      TAFLUSH();
      TR(9);
      {
        if (!ready) mbar_wait(sb + BAR_FULL1 + 8 * 3, ph);
        ph ^= 1;
        const uint64_t dv = d0 + 3 * (ST1 >> 4);
        wg_fence();
        issue_pv(O, PL, dv, 1);
        wg_commit();
        bb_fence(tag);
        softmax_half(SH, PH, O, z, false, tag);
        wg_fence();
        issue_pv(O, PH, dv + 1024, 1);
        wg_commit();
        TR(10);
        row_rcp(z.l0, z.l1);
        mbar_wait(sb + (pair ? BAR_X : BAR_STASH) + 8 * wg, 0);
#pragma unroll
        for (int kk = 0; kk < 8; kk++) ldsm4((stsm_addr + (kk >> 2) * 8192) ^ ((kk & 3) * 32), X + 4 * kk);
        reg_fence<32>(X);
        __syncwarp();
        wg_wait<0>();
        reg_fence<64>(O);
        TR(11);
        if ((tid & 127) < 2) mbar_arrive_cl(rel + BAR_EMPTY1 + 8 * 3);
        stage_o(O, z.l0, z.l1, stsm_addr);
        nb_arrive(NB_OST + wg, 160);
      }
      TR(12);
      if (tid == 0) { TS(9 + pair * 2); TSC(62); }
      if (pair == 1) break;
      {
        mbar_wait(sb + BAR_FULL1, ph);
        const uint64_t da = mk_desc(sb + SM_RING + wg * 8192, 16), db = mk_desc(sb + SM_RING + 16384, 8192);
        wg_fence();
        wgmma_ss256_z<1>(acc, da, db);
#pragma unroll
        for (int kk = 1; kk < 4; kk++) wgmma_ss256<1>(acc, da + kk * 2, db + kk * 128, 1);
        wg_commit();
      }
#pragma unroll 1
      for (int kt = 1; kt < 16; kt++) {
        const uint32_t s = kt & 3;
        if (s == 0) ph ^= 1;
        mbar_wait(sb + BAR_FULL1 + 8 * s, ph);
        const uint32_t st = sb + SM_RING + s * ST1;
        const uint64_t da = mk_desc(st + wg * 8192, 16), db = mk_desc(st + 16384, 8192);
        wg_fence();
#pragma unroll
        for (int kk = 0; kk < 4; kk++) wgmma_ss256<1>(acc, da + kk * 2, db + kk * 128, 1);
        wg_commit();
        wg_wait<1>();
        if ((tid & 127) < 2) mbar_arrive_cl(rel + BAR_EMPTY1 + 8 * ((s + 3) & 3));
      }
      ph ^= 1;
      wg_wait<0>();
      reg_fence<128>(acc);
      TR(13);
    }

    uint4 WG[16], WU[16];
    const int fp = 64 * warp + 8 * g + t;
    uint32_t fsb0, fsb1, fcb0, fcb1, fgb0, fgb1;
    const uint32_t gu_base = sb + SM_RING + (warp >> 1) * ST1 + 32768 + (warp & 1) * 8192;
    const uint32_t gu_addr = gu_base + t * 128 + (g & 1) * 64 + ((g >> 1) ^ t) * 16;
    {
      const uint64_t da0 = mk_desc(sb + SM_RING + __shfl_sync(0xffffffffu, wg, 0) * 8192, 16), db0 = mk_desc(sb + SM_RING + 16384, 8192);
#pragma unroll
      for (int n = 0; n < 4 + 5 * X_PEEL; n++) {
        const int s = n < 4 ? n : (n - 4) % 5;
        mbar_wait(sb + BAR_FULL1 + 8 * s, n < 4 ? 0 : ((n - 4) / 5 + (s < 4)) & 1);
        if (n < 4) TSX(40 + wg * 6 + n);
        const uint64_t da = da0 + s * (ST1 >> 4), db = db0 + s * (ST1 >> 4);
        wg_fence();
        if (n == 0) wgmma_ss128_z<1>(acc, da, db); else wgmma_ss128<1>(acc, da, db, 1);
#pragma unroll
        for (int kk = 1; kk < 4; kk++) wgmma_ss128<1>(acc, da + kk * 2, db + kk * 128, 1);
        wg_commit();
        if (n == 1) {
          mbar_wait(sb + BAR_OF, 0);
          const uint2* mp = &g_mod[3 * 512 + fp];
          fsb0 = ld_pkt8(mp).x; fsb1 = ld_pkt8(mp + 4).x; fcb0 = ld_pkt8(mp + 512).x; fcb1 = ld_pkt8(mp + 516).x;
          fgb0 = ld_pkt8(mp + 1024).x; fgb1 = ld_pkt8(mp + 1028).x;
        }
        if (n == 0 && b < NFFN) mbar_wait(sb + BAR_FFN, 0);
        {
          constexpr int NT = 4 + 5 * X_PEEL, F0 = NT > 16 ? NT - 16 : 0;
#pragma unroll
          for (int i = 0; i < 16; i++) if (F0 + i * (NT - F0) / 16 == n) WG[i] = lds128(gu_addr + i * 512);
        }
        if (n > 0) {
          wg_wait<1>();
          if ((tid & 127) < 2) mbar_arrive_cl(rel + BAR_EMPTY1 + 8 * (n == 4 ? 3 : s ? s - 1 : 4));
        }
      }
      TSX(44 + wg * 6);
      {
        uint32_t dep = 0;
#pragma unroll
        for (int i = 0; i < 16; i++) dep ^= WG[i].x;
        if (__shfl_sync(0xffffffffu, tag, dep & 31) == tag && lane == 2) mbar_arrive(sb + BAR_TFREE);
      }
#pragma unroll 1
      for (int r = X_PEEL; r < 12; r++) {
#pragma unroll
        for (int s = 0; s < 5; s++) {
          mbar_wait(sb + BAR_FULL1 + 8 * s, (r + (s < 4)) & 1);
          const uint64_t da = da0 + s * (ST1 >> 4), db = db0 + s * (ST1 >> 4);
          wg_fence();
#pragma unroll
          for (int kk = 0; kk < 4; kk++) wgmma_ss128<1>(acc, da + kk * 2, db + kk * 128, 1);
          wg_commit();
          wg_wait<1>();
          if ((tid & 127) < 2) mbar_arrive_cl(rel + BAR_EMPTY1 + 8 * (s ? s - 1 : (r == 0 ? 3 : 4)));
        }
      }
    }
    mbar_wait(sb + BAR_VEC, 0);
    const int lrow = warp * 16 + g;
    uint2 ga[8], b1[8];
#pragma unroll
    for (int kk = 0; kk < 8; kk++) { ga[kk] = lds64(sb + SM_GA + kk * 32 + t * 8); b1[kk] = lds64(sb + SM_B1 + min(g, 3) * 32 + t * 8 + kk * 128); }
    uint4* const stp = &g_stats[b * 128 + lrow + 8 * t];
    bb_fence(tag);
    wg_wait<0>();
    reg_fence<64>(acc);
    if (tid == 0) { TS(12); TSC(63); }

    TT(0);
    {
      float d1[4] = {0.f, 0.f, 0.f, 0.f}, d2[4] = {0.f, 0.f, 0.f, 0.f}, d3[4] = {0.f, 0.f, 0.f, 0.f};
      float d4[4] = {0.f, 0.f, 0.f, 0.f}, d5[4] = {0.f, 0.f, 0.f, 0.f};
#pragma unroll
      for (int kk = 0; kk < 8; kk++) {
        uint32_t* x = X + 4 * kk;
        x[0] = hfma2(ga[kk].x, pack2(acc[8 * kk + 0], acc[8 * kk + 1]), x[0]);
        x[1] = hfma2(ga[kk].x, pack2(acc[8 * kk + 2], acc[8 * kk + 3]), x[1]);
        x[2] = hfma2(ga[kk].y, pack2(acc[8 * kk + 4], acc[8 * kk + 5]), x[2]);
        x[3] = hfma2(ga[kk].y, pack2(acc[8 * kk + 6], acc[8 * kk + 7]), x[3]);
        mma16816(d1, x, b1[kk].x, b1[kk].y);
        mma1688(d2, x[0], x[1], x[0]); mma1688(d3, x[0], x[1], x[1]);
        mma1688(d4, x[2], x[3], x[2]); mma1688(d5, x[2], x[3], x[3]);
      }
      const int qb = lane & 28;
      const float q0 = __shfl_sync(0xffffffffu, (g & 1) ? d2[1] + d4[1] : d2[0] + d4[0], qb | (g >> 1));
      const float q1 = __shfl_sync(0xffffffffu, (g & 1) ? d3[3] + d5[3] : d3[2] + d5[2], qb | (g >> 1));
      const float e0 = __shfl_xor_sync(0xffffffffu, t ? d1[0] : d1[3], 1);
      const float e1 = __shfl_sync(0xffffffffu, d1[2], qb);
      if (t < 2) st_pkt16(stp, __float_as_uint(t ? e1 : d1[0]), __float_as_uint(t ? q1 : q0),
                          __float_as_uint((t ? d1[2] : d1[1]) + e0), tag);
    }
    TSY(13);
    TT(1);
    float mb, rd, den, br;
    {
      const uint4* sp = &g_stats[(rt * 8 + 4 * (t & 1)) * 128 + lrow + 4 * (t & 2)];
      mbar_wait(sb + BAR_EMPTY1 + 8 * 3, 0);
#pragma unroll
      for (int kk = 0; kk < 8; kk++) stsm4((stsm_addr - SM_STASH + SM_X2 + (kk >> 2) * 8192) ^ ((kk & 3) * 32), X[4 * kk], X[4 * kk + 1], X[4 * kk + 2], X[4 * kk + 3]);
      if (b < NFFN) mbar_wait(sb + BAR_FFN, 1);
#pragma unroll
      for (int i = 0; i < WU1; i++) WU[i] = lds128(gu_addr + i * 512);
      bb_fence(tag);
      TT(2);
      uint4 v0, v1, v2, v3;
      int it = 0;
      do { v0 = ld_pkt16(sp); v1 = ld_pkt16(sp + 128); v2 = ld_pkt16(sp + 256); v3 = ld_pkt16(sp + 384); spin_guard(it); }
        while (!(__all_sync(0xffffffffu, v0.w == tag && v1.w == tag && v2.w == tag && v3.w == tag)));
      TT(3);
      float sm = (__uint_as_float(v0.x) + __uint_as_float(v1.x)) + (__uint_as_float(v2.x) + __uint_as_float(v3.x));
      float sq = (__uint_as_float(v0.y) + __uint_as_float(v1.y)) + (__uint_as_float(v2.y) + __uint_as_float(v3.y));
      float dt = (__uint_as_float(v0.z) + __uint_as_float(v1.z)) + (__uint_as_float(v2.z) + __uint_as_float(v3.z));
      sm += __shfl_xor_sync(0xffffffffu, sm, 1); sq += __shfl_xor_sync(0xffffffffu, sq, 1); dt += __shfl_xor_sync(0xffffffffu, dt, 1);
      const uint2 scal = lds64(sb + SM_SCAL);
      const float mu = sm * (1.f / 1024.f);
      mb = rbf(mu);
      den = rbf(sqrt_f(rbf(rbf(fmaxf(fmaf(-mu, mu, sq * (1.f / 1024.f)), 0.f)) + 1e-5f)));
      rd = rcp_f(den);
      br = fmaf(fmaf(-mb, __uint_as_float(scal.x), dt), rd, __uint_as_float(scal.y));
    }
    TSY(14);
    TT(4);
    {
      const int rb = __float_as_int(br);
      const int key = rb ^ ((rb >> 31) & 0x7fffffff);
      const int wmax = __reduce_max_sync(0xffffffffu, key);
      if (lane == __ffs(__ballot_sync(0xffffffffu, key == wmax)) - 1)
        sts128(sb + SM_AMAX + warp * 16, (uint32_t)key, lrow + 4 * (t & 2), pack2(mb, den), (uint32_t)rb);
      __syncwarp();
      nb_arrive(NB_AMAX, 288);
    }
    TT(5);
    const uint4* ep = &g_entry[(warp * 16 + (lane & 15)) * ESTR];
    const uint32_t slot = sb + SM_STASH + wg * 8192 + (tid & 127) * 16;
    cp_async16(slot, ep);
    {
      const float rh = rbf(rd);
      const uint32_t u = pack2(-mb * rh, rh);
      const int qb = lane & 28;
      const uint32_t u0 = __shfl_sync(0xffffffffu, u, qb), u1 = __shfl_sync(0xffffffffu, u, qb | 2);
      const uint32_t m0 = __byte_perm(u0, 0, 0x1010), h0 = __byte_perm(u0, 0, 0x3232);
      const uint32_t m1 = __byte_perm(u1, 0, 0x1010), h1 = __byte_perm(u1, 0, 0x3232);
#pragma unroll
      for (int j = 0; j < 16; j++) {
        const uint4 rec = lds128(sb + SM_REC + (4 * j + t) * 16);
        X[2 * j] = hfma2(rec.z, hfma2(hfma2(X[2 * j], h0, m0), rec.x, rec.y), X[2 * j]);
        X[2 * j + 1] = hfma2(rec.z, hfma2(hfma2(X[2 * j + 1], h1, m1), rec.x, rec.y), X[2 * j + 1]);
      }
#pragma unroll
      for (int kk = 0; kk < 8; kk++) stsm4((stsm_addr - SM_STASH + SM_OUT + (kk >> 2) * 8192) ^ ((kk & 3) * 32), X[4 * kk], X[4 * kk + 1], X[4 * kk + 2], X[4 * kk + 3]);
    }
    cp_async_wait();
    uint4 ent = lds128(slot);
    TSY(16);
    TT(6);
    int wrow;
    uint32_t xs0, xs1, hs0, hs1;
    uint32_t WD[64];
    const uint32_t wd_addr = sb + SM_RING + wg * ST1 + wq * 8192 + ((lane & 7) + ((lane >> 4) << 3)) * 128 + ((((lane >> 3) & 1) ^ (lane & 7)) * 16);
    {
      auto leader = [&]() {
        const int key = ent.w == tag ? (int)ent.x ^ (((int)ent.x >> 31) & 0x7fffffff) : (int)0x80000000;
        const int gmax = __reduce_max_sync(0xffffffffu, key);
        return __ffs(__ballot_sync(0xffffffffu, key == gmax)) - 1;
      };
      int wt = leader(), it = 0;
      TT(7);
      nb_arrive(NB_OST + wg, 160);
      TT(8);
      cp_async16(slot + 2048, &g_cand[(wt * 8 + warp) * 32 + lane]);
      if (ent.w != tag) cp_async16(slot, ep);
#pragma unroll
      for (int i = WU1; i < 16; i++) WU[i] = lds128(gu_addr + i * 512);
      if (b < NFFN) mbar_wait(sb + BAR_FFN + 8, 0);
#pragma unroll
      for (int mt = 0; mt < 8; mt++)
#pragma unroll
        for (int s = 0; s < 2; s++) ldsm4t((wd_addr + (mt >> 2) * 4096 + s * 2048) ^ ((mt & 3) * 32), WD + (mt * 2 + s) * 4);
      cp_async_wait();
      uint4 v = lds128(slot + 2048);
      ent = lds128(slot);
      TT(9);
      while (true) {
        const int have = wt;
        wt = leader();
        if (__all_sync(0xffffffffu, ent.w == tag && have == wt && v.z == tag)) break;
        v = ld_pkt16(&g_cand[(wt * 8 + warp) * 32 + lane]);
        if (ent.w != tag) ent = ld_pkt16(ep);
        spin_guard(it);
      }
      TT(10);
      ent.x = __shfl_sync(0xffffffffu, ent.x, wt); wrow = __shfl_sync(0xffffffffu, ent.y, wt); ent.z = __shfl_sync(0xffffffffu, ent.z, wt);
      xs0 = v.x; xs1 = v.y;
      const uint32_t mm = __byte_perm(ent.z, 0, 0x1010);
      const float rs = rcp_f(hi2f(ent.z));
      const uint32_t e0 = hsub2(xs0, mm), e1 = hsub2(xs1, mm);
      hs0 = hfma2(pack2(lo2f(e0) * rs, hi2f(e0) * rs), hadd2(fcb0, ONE2), fsb0);
      hs1 = hfma2(pack2(lo2f(e1) * rs, hi2f(e1) * rs), hadd2(fcb1, ONE2), fsb1);
    }
    if ((tid & 127) == 0) sts32(sb + SM_WROW + 4 * wg, wrow);
    nb_arrive(NB_WIN + wg, 160);
    TSY(17);
    TT(11);
    if (b < NFFN) {
      float da[4][4];
#pragma unroll
      for (int i = 0; i < 4; i++) { da[i][0] = da[i][1] = da[i][2] = da[i][3] = 0.f; }
      const uint32_t selv = ((g & 1) ? 0x1044 : 0x4410) + ((g & 4) ? ((g & 1) ? 0x2200 : 0x0022) : 0);
      const uint32_t sel0 = (g & 2) ? 0x4444 : selv, sel1 = (g & 2) ? selv : 0x4444;
#pragma unroll
      for (int s = 0; s < 16; s++) {
        const uint32_t v = __shfl_sync(0xffffffffu, (s & 1) ? hs1 : hs0, 4 * (s >> 1) + t);
        const uint32_t b0 = __byte_perm(v, 0, sel0), b1 = __byte_perm(v, 0, sel1);
        const uint32_t a0[4] = {WG[s].x, WG[s].y, WG[s].z, WG[s].w};
        const uint32_t a1[4] = {WU[s].x, WU[s].y, WU[s].z, WU[s].w};
        mma16816(da[(s & 1) * 2], a0, b0, b1);
        mma16816(da[(s & 1) * 2 + 1], a1, b0, b1);
      }
      {
        float v[4];
#pragma unroll
        for (int i = 0; i < 4; i++) {
          const float vg = da[0][i] + da[2][i], vu = da[1][i] + da[3][i];
          v[i] = ((g & 1) ? vu : vg) + __shfl_xor_sync(0xffffffffu, (g & 1) ? vg : vu, 6);
        }
        if ((t >> 1) == (g & 1))
          sts128(gu_base + (g & 1) * 128 + (g >> 1) * 32 + (t & 1) * 16, __float_as_uint(v[0]), __float_as_uint(v[1]), __float_as_uint(v[2]), __float_as_uint(v[3]));
      }
      TT(12);
      nb_sync(NB_CONS, 256);
      float gp[8], up[8];
#pragma unroll
      for (int w = 0; w < 8; w++) {
        const uint32_t a = sb + SM_RING + (w >> 1) * ST1 + 32768 + (w & 1) * 8192 + lane * 4;
        gp[w] = lds_f32(a); up[w] = lds_f32(a + 128);
      }
      const float gsum = ((gp[0] + gp[1]) + (gp[2] + gp[3])) + ((gp[4] + gp[5]) + (gp[6] + gp[7]));
      const float usum = ((up[0] + up[1]) + (up[2] + up[3])) + ((up[4] + up[5]) + (up[6] + up[7]));
      const float act = rbf(silu_f(rbf(gsum))) * rbf(usum);
      TT(13);
      const uint32_t ap = pack2(act, __shfl_down_sync(0xffffffffu, act, 1));
      const uint32_t b00 = __shfl_sync(0xffffffffu, ap, 2 * t), b01 = __shfl_sync(0xffffffffu, ap, 2 * t + 8);
      const uint32_t b10 = __shfl_sync(0xffffffffu, ap, 2 * t + 16), b11 = __shfl_sync(0xffffffffu, ap, 2 * t + 24);
      float y[8][4];
#pragma unroll
      for (int mt = 0; mt < 8; mt++) {
        y[mt][0] = y[mt][1] = y[mt][2] = y[mt][3] = 0.f;
        mma16816(y[mt], WD + (mt * 2) * 4, b00, b01);
        mma16816(y[mt], WD + (mt * 2 + 1) * 4, b10, b11);
      }
#pragma unroll
      for (int e = 0; e < 2; e++) {
        const float v0 = t == 0 ? y[e][0] : t == 1 ? y[2 + e][0] : t == 2 ? y[4 + e][0] : y[6 + e][0];
        const float v1 = t == 0 ? y[e][2] : t == 1 ? y[2 + e][2] : t == 2 ? y[4 + e][2] : y[6 + e][2];
        const int f = 16 * warp + 2 * (2 * t + e) + (g >> 2);
        st_pkt16(&g_ypart[(f * NFFN + b) * 4 + (g & 3)], __float_as_uint(v0), __float_as_uint(v1), tag, 0);
      }
    }
    TSY(18);
    TT(14);
    {
      const int pw = warp - (warp > (b >> 4));
      if (warp != (b >> 4)) {
        const uint4* yp = &g_ypart[b * NFFN * 4 + pw * 64 + lane];
        uint4 v0, v1;
        int it = 0;
        { const uint32_t c1 = clock(); while ((uint32_t)clock() - c1 < (b < NFFN ? YD : YD + 1500)) {} }
        do { v0 = ld_pkt16(yp); v1 = ld_pkt16(yp + 32); spin_guard(it); }
        while (!(__all_sync(0xffffffffu, v0.z == tag && v1.z == tag)));
        float y0 = __uint_as_float(v0.x) + __uint_as_float(v1.x), y1 = __uint_as_float(v0.y) + __uint_as_float(v1.y);
#pragma unroll
        for (int o = 4; o <= 16; o <<= 1) { y0 += __shfl_xor_sync(0xffffffffu, y0, o); y1 += __shfl_xor_sync(0xffffffffu, y1, o); }
        if (lane < 4) sts64(sb + SM_YRED + pw * 32 + lane * 8, __float_as_uint(y0), __float_as_uint(y1));
      }
    }
    TT(15);
    if (warp != (b >> 4)) {
      nb_arrive(NB_CONS, 256);
    } else {
      nb_sync(NB_CONS, 256);
      float y0 = 0.f, y1 = 0.f;
      if (lane < 28) { const uint2 e = lds64(sb + SM_YRED + lane * 8); y0 = __uint_as_float(e.x); y1 = __uint_as_float(e.y); }
#pragma unroll
      for (int o = 4; o <= 16; o <<= 1) { y0 += __shfl_xor_sync(0xffffffffu, y0, o); y1 += __shfl_xor_sync(0xffffffffu, y1, o); }
      const int src = 2 * (t & 1);
      const float ya = __shfl_sync(0xffffffffu, y0, src), yb = __shfl_sync(0xffffffffu, y0, src + 1);
      const float yc = __shfl_sync(0xffffffffu, y1, src), yd = __shfl_sync(0xffffffffu, y1, src + 1);
      if (g == ((b >> 1) & 7) && (t >> 1) == (b & 1)) {
        const float rs = rbf(__uint_as_float(ent.x));
        const float sg = sigmoid_f(rs);
        const uint32_t sg2 = pack2(sg, sg);
        const uint32_t o0 = hadd2(xs0, hmul2(fgb0, hadd2(hs0, hmul2(pack2(ya, yb), sg2))));
        const uint32_t o1 = hadd2(xs1, hmul2(fgb1, hadd2(hs1, hmul2(pack2(yc, yd), sg2))));
        uint32_t* op = reinterpret_cast<uint32_t*>(p.out + (size_t)wrow * 1024) + fp;
        op[0] = o0; op[4] = o1;
      }
      if (b == 0) {
        if (lane < 8) st_relaxed(&p.sc->ticket[lane * 32], 0);
        st_relaxed(&p.sc->epoch[lane], tag);
      }
      if (lane == 0) TS(19);
    }
  }
}

typedef CUresult (*EncodeFn)(CUtensorMap*, CUtensorMapDataType, cuuint32_t, void*, const cuuint64_t*, const cuuint64_t*,
                             const cuuint32_t*, const cuuint32_t*, CUtensorMapInterleave, CUtensorMapSwizzle,
                             CUtensorMapL2promotion, CUtensorMapFloatOOBfill);

CUtensorMap make_map(EncodeFn enc, const void* ptr, uint64_t rows, uint64_t cols, uint32_t box_rows, uint32_t box_cols, CUtensorMapSwizzle sw) {
  CUtensorMap m;
  cuuint64_t dims[2] = {cols, rows};
  cuuint64_t strides[1] = {cols * 2};
  cuuint32_t box[2] = {box_cols, box_rows};
  cuuint32_t es[2] = {1, 1};
  enc(&m, CU_TENSOR_MAP_DATA_TYPE_BFLOAT16, 2, const_cast<void*>(ptr), dims, strides, box, es, CU_TENSOR_MAP_INTERLEAVE_NONE, sw,
      CU_TENSOR_MAP_L2_PROMOTION_L2_128B, CU_TENSOR_MAP_FLOAT_OOB_FILL_NONE);
  return m;
}

CUtensorMap make_map3(EncodeFn enc, const void* ptr, uint64_t rows, uint64_t cols, uint32_t box_rows, uint32_t box_blks) {
  CUtensorMap m;
  cuuint64_t dims[3] = {64, rows, cols / 64};
  cuuint64_t strides[2] = {cols * 2, 128};
  cuuint32_t box[3] = {64, box_rows, box_blks};
  cuuint32_t es[3] = {1, 1, 1};
  enc(&m, CU_TENSOR_MAP_DATA_TYPE_BFLOAT16, 3, const_cast<void*>(ptr), dims, strides, box, es, CU_TENSOR_MAP_INTERLEAVE_NONE,
      CU_TENSOR_MAP_SWIZZLE_128B, CU_TENSOR_MAP_L2_PROMOTION_L2_128B, CU_TENSOR_MAP_FLOAT_OOB_FILL_NONE);
  return m;
}

}

extern "C" void kernel_launch(void* const* d_in, const int* in_sizes, int n_in, void* d_out, int out_size) {
  (void)in_sizes; (void)n_in; (void)out_size;
  Params p;
  p.x = (const bf16*)d_in[0]; p.kc = (const bf16*)d_in[1]; p.vc = (const bf16*)d_in[2];
  p.wq = (const bf16*)d_in[3]; p.wo = (const bf16*)d_in[4]; p.w_r = (const bf16*)d_in[6];
  p.wg = (const bf16*)d_in[7]; p.wu = (const bf16*)d_in[8]; p.wd = (const bf16*)d_in[9];
  p.c = (const bf16*)d_in[10]; p.w_mod = (const bf16*)d_in[11]; p.out = (bf16*)d_out;

  void* fn = nullptr;
  cudaDriverEntryPointQueryResult st;
  cudaGetDriverEntryPoint("cuTensorMapEncodeTiled", &fn, cudaEnableDefault, &st);
  EncodeFn enc = (EncodeFn)fn;
  void* scp = nullptr;
  cudaGetSymbolAddress(&scp, g_scratch);
  p.sc = (Scratch*)scp;
  void *hp = p.sc->h, *op = p.sc->o;
  const CUtensorMapSwizzle S128 = CU_TENSOR_MAP_SWIZZLE_128B;
  CUtensorMap mH = make_map(enc, hp, 2048, 1024, 64, 64, S128);
  CUtensorMap mWq = make_map3(enc, p.wq, 1024, 4096, 64, 4);
  CUtensorMap mK = make_map(enc, p.kc, 8192, 128, 64, 64, S128);
  CUtensorMap mV = make_map(enc, p.vc, 8192, 128, 64, 64, S128);
  CUtensorMap mO = make_map(enc, op, 2048, 4096, 64, 64, S128);
  CUtensorMap mWo = make_map3(enc, p.wo, 4096, 1024, 64, 2);
  CUtensorMap mX = make_map(enc, p.x, 2048, 1024, 64, 64, S128);
  CUtensorMap mOut = make_map(enc, p.out, 2048, 1024, 64, 64, S128);
  CUtensorMap mWg = make_map(enc, p.wg, 1024, 3584, 256, 32, CU_TENSOR_MAP_SWIZZLE_64B);
  CUtensorMap mWu = make_map(enc, p.wu, 1024, 3584, 256, 32, CU_TENSOR_MAP_SWIZZLE_64B);
  CUtensorMap mWd = make_map3(enc, p.wd, 3584, 1024, 32, 8);
  CUtensorMap mWm = make_map(enc, p.w_mod, 1024, 6144, 16, 256, CU_TENSOR_MAP_SWIZZLE_NONE);
  CUtensorMap mWs = make_map(enc, p.w_mod, 1024, 6144, 128, 128, CU_TENSOR_MAP_SWIZZLE_NONE);
  cudaFuncSetAttribute(fused_kernel, cudaFuncAttributeMaxDynamicSharedMemorySize, SMEM_BYTES);
  fused_kernel<<<NCTA, NTHREADS, SMEM_BYTES>>>(p, mH, mWq, mK, mV, mO, mWo, mX, mOut, mWg, mWu, mWd, mWm, mWs);
}
```

```cpp
#include <cuda_runtime.h>
#include <cuda_bf16.h>
#include <cuda.h>
#include <stdint.h>
#include <stddef.h>

#define UPD 200
#define GATED 1500
#define WL 3000
#define XD 0
#define PLD 200
#define ESTR 8
#define HD 6000
#define YD 500
#define SPD 0
#define PFW 100
#define X_PEEL 1
#define WU1 12

namespace {

typedef __nv_bfloat16 bf16;

constexpr int NTHREADS = 384;
constexpr int NMAIN = 128;
constexpr int NCTA = 132;
#define RS 8
constexpr int RV = 16 * RS + 64;
constexpr int NREP = 4;
constexpr int NFFN = 112;

constexpr uint32_t SM_RING = 0;
constexpr uint32_t ST1 = 49152;
constexpr uint32_t ST2 = 32768;
constexpr int NST2 = 6;
constexpr uint32_t SM_STASH = 196608;
constexpr uint32_t SM_MISC = 229376;
constexpr uint32_t BAR_FULL1 = SM_MISC + 0;
constexpr uint32_t BAR_EMPTY1 = SM_MISC + 40;
constexpr uint32_t BAR_FULL2 = SM_MISC + 0;
constexpr uint32_t BAR_EMPTY2 = SM_MISC + 48;
constexpr uint32_t BAR_STASH = SM_MISC + 160;
constexpr uint32_t BAR_SFREE = SM_MISC + 176;
constexpr uint32_t BAR_TFREE = SM_MISC + 184;
constexpr uint32_t BAR_FFN = SM_MISC + 192;
constexpr uint32_t BAR_VEC = SM_MISC + 208;
constexpr uint32_t BAR_RED = SM_MISC + 216;
constexpr uint32_t BAR_XH = SM_MISC + 152;
constexpr uint32_t BAR_HS = SM_MISC + 80;
constexpr uint32_t BAR_G = SM_MISC + 112;
constexpr uint32_t BAR_T1 = SM_MISC + 120;
constexpr uint32_t BAR_HF = SM_MISC + 128;
constexpr uint32_t BAR_X = SM_MISC + 136;
constexpr uint32_t BAR_OF = SM_MISC + 224;
constexpr uint32_t BAR_ROLE = SM_MISC + 240;
constexpr uint32_t SM_ROLE = SM_MISC + 248;
constexpr uint32_t SM_GA = SM_MISC + 256;
constexpr uint32_t SM_SCAL = SM_MISC + 512;
constexpr uint32_t SM_WROW = SM_MISC + 520;
constexpr uint32_t SM_AMAX = SM_MISC + 528;
constexpr uint32_t SM_YRED = SM_MISC + 656;
constexpr uint32_t SM_X2 = 2 * ST1, SM_OUT = 3 * ST1;
constexpr uint32_t SM_REC = SM_MISC + 1024;
constexpr uint32_t BAR_TAB = SM_MISC + 1000;
constexpr uint32_t BAR_CAND = SM_MISC + 880;
constexpr uint32_t SM_CAND = SM_MISC + 888;
constexpr uint32_t SM_WSLAB = 2 * 49152 + 16384;
constexpr uint32_t SM_XROW = 2 * 49152;
constexpr uint32_t SM_RED = SM_MISC + 2048;
constexpr uint32_t SM_B1 = SM_MISC + 2048;
constexpr uint32_t SMEM_BYTES = 232448;

constexpr int NB_CONS = 1, NB_WIN = 2  , NB_OST = 4  , NB_AMAX = 6;

struct __align__(1024) Scratch {
  uint32_t epoch[32];
  uint32_t hflag[16 * 32];
  uint32_t oflag[64 * 32];
  uint2 vdone[4 * 16];
  uint32_t pad[96 + 512];
  uint32_t ticket[8 * 32];
  uint2 mod[3072];
  uint4 rec[2][NREP][2 * RV];
  uint4 lnst[1024];
  uint4 entry[8 * 16 * 8];
  uint4 cand[16 * 8 * 32];
  uint4 stats[16 * 8 * 128];
  uint4 ypart[128 * NFFN * 4];
  unsigned long long ts[NCTA * 64];
  uint16_t h[2048 * 1024];
  uint16_t o[2048 * 4096];
};
__device__ Scratch g_scratch;
#define g_epoch (p.sc->epoch[0])
#define g_hflag (p.sc->hflag)
#define g_oflag (p.sc->oflag)
#define g_mod (p.sc->mod)
#define g_entry (p.sc->entry)
#define g_cand (p.sc->cand)
#define g_stats (p.sc->stats)
#define g_ypart (p.sc->ypart)
#define g_vdone (p.sc->vdone)
#define g_lnst (p.sc->lnst)
#define g_rec (p.sc->rec)
#define g_ts (p.sc->ts)
#define g_h (p.sc->h)

struct Params {
  const bf16* w_mod; const bf16* c; Scratch* sc; const bf16* x; const bf16* w_r; bf16* out;
  const bf16* wq; const bf16* wo; const bf16* wg; const bf16* wu; const bf16* wd; const bf16* kc; const bf16* vc;
};

__device__ __forceinline__ uint32_t smem_u32(const void* p) { return (uint32_t)__cvta_generic_to_shared(p); }
__device__ __forceinline__ void mbar_init(uint32_t bar, uint32_t cnt) { asm volatile("mbarrier.init.shared::cta.b64 [%0], %1;" :: "r"(bar), "r"(cnt) : "memory"); }
__device__ __forceinline__ void mbar_expect_tx(uint32_t bar, uint32_t bytes) { asm volatile("mbarrier.arrive.expect_tx.shared::cta.b64 _, [%0], %1;" :: "r"(bar), "r"(bytes) : "memory"); }
__device__ __forceinline__ void mbar_arrive(uint32_t bar) { asm volatile("mbarrier.arrive.shared::cta.b64 _, [%0];" :: "r"(bar) : "memory"); }
__device__ __forceinline__ void mbar_arrive_cl(uint32_t cluster_addr) { asm volatile("mbarrier.arrive.shared::cluster.b64 _, [%0];" :: "r"(cluster_addr) : "memory"); }
__device__ __forceinline__ uint32_t mapa(uint32_t addr, uint32_t cta) { uint32_t r; asm("mapa.shared::cluster.u32 %0, %1, %2;" : "=r"(r) : "r"(addr), "r"(cta)); return r; }
__device__ __forceinline__ bool mbar_test(uint32_t bar, uint32_t parity) {
  uint32_t ok;
  asm volatile("{\n.reg .pred p;\nmbarrier.test_wait.parity.shared::cta.b64 p, [%1], %2;\nselp.u32 %0, 1, 0, p;\n}" : "=r"(ok) : "r"(bar), "r"(parity) : "memory");
  return ok;
}
constexpr int SPIN_LIMIT = 300000;
__device__ __forceinline__ void spin_guard(int& it) {
  asm volatile("{\n.reg .pred p;\n.reg .b64 z;\nadd.s32 %0, %0, 1;\nsetp.gt.s32 p, %0, %1;\nmov.b64 z, 0;\n@p st.volatile.global.u32 [z], %0;\n}" : "+r"(it) : "n"(SPIN_LIMIT));
}
__device__ __forceinline__ void mbar_wait_g(uint32_t bar, uint32_t parity) {
  asm volatile("{\n.reg .pred p, q;\n.reg .b32 c;\n.reg .b64 z;\nmov.b32 c, 0;\nmov.b64 z, 0;\nMW_LOOP:\n"
               "mbarrier.try_wait.parity.shared::cta.b64 p, [%0], %1;\nadd.s32 c, c, 1;\nsetp.gt.s32 q, c, %2;\n"
               "@q st.volatile.global.u32 [z], c;\n@!p bra MW_LOOP;\n}" :: "r"(bar), "r"(parity), "n"(SPIN_LIMIT) : "memory");
}
__device__ __forceinline__ void mbar_wait(uint32_t bar, uint32_t parity) {
  asm volatile("{\n.reg .pred p;\nMW_LOOP:\nmbarrier.try_wait.parity.shared::cta.b64 p, [%0], %1;\n@!p bra MW_LOOP;\n}" :: "r"(bar), "r"(parity) : "memory");
}
__device__ __forceinline__ void bb_fence(uint32_t v) {
  asm volatile("{\n.reg .pred p;\n.reg .u32 c;\nsetp.ne.u32 p, %0, 0;\n@p bra.uni BF_DONE;\nBF_LOOP:\nnanosleep.u32 1;\nmov.u32 c, %%clock;\nsetp.eq.u32 p, c, 0;\n@p bra.uni BF_LOOP;\nBF_DONE:\n}" :: "r"(v) : "memory");
}
__device__ __forceinline__ bool elect_one() {
  uint32_t pred;
  asm volatile("{\n.reg .pred P;\nelect.sync _|P, 0xffffffff;\nselp.u32 %0, 1, 0, P;\n}" : "=r"(pred));
  return pred;
}
__device__ __forceinline__ void tma_ld(uint32_t dst, const CUtensorMap* m, int c0, int c1, uint32_t bar) {
  asm volatile("cp.async.bulk.tensor.2d.shared::cluster.global.mbarrier::complete_tx::bytes [%0], [%1, {%3, %4}], [%2];"
    :: "r"(dst), "l"(m), "r"(bar), "r"(c0), "r"(c1) : "memory");
}
__device__ __forceinline__ void tma_ld_hint(uint32_t dst, const CUtensorMap* m, int c0, int c1, uint32_t bar, uint64_t pol) {
  asm volatile("cp.async.bulk.tensor.2d.shared::cluster.global.mbarrier::complete_tx::bytes.L2::cache_hint [%0], [%1, {%3, %4}], [%2], %5;"
    :: "r"(dst), "l"(m), "r"(bar), "r"(c0), "r"(c1), "l"(pol) : "memory");
}
__device__ __forceinline__ void tma_ld_mc(uint32_t dst, const CUtensorMap* m, int c0, int c1, uint32_t bar) {
  asm volatile("cp.async.bulk.tensor.2d.shared::cluster.global.mbarrier::complete_tx::bytes.multicast::cluster [%0], [%1, {%3, %4}], [%2], %5;"
    :: "r"(dst), "l"(m), "r"(bar), "r"(c0), "r"(c1), "h"((uint16_t)3) : "memory");
}
__device__ __forceinline__ void tma_ld_mc_hint(uint32_t dst, const CUtensorMap* m, int c0, int c1, uint32_t bar, uint64_t pol) {
  asm volatile("cp.async.bulk.tensor.2d.shared::cluster.global.mbarrier::complete_tx::bytes.multicast::cluster.L2::cache_hint [%0], [%1, {%3, %4}], [%2], %5, %6;"
    :: "r"(dst), "l"(m), "r"(bar), "r"(c0), "r"(c1), "h"((uint16_t)3), "l"(pol) : "memory");
}
__device__ __forceinline__ void tma_ld3_hint(uint32_t dst, const CUtensorMap* m, int row, int blk, uint32_t bar, uint64_t pol) {
  asm volatile("cp.async.bulk.tensor.3d.shared::cluster.global.mbarrier::complete_tx::bytes.L2::cache_hint [%0], [%1, {0, %3, %4}], [%2], %5;"
    :: "r"(dst), "l"(m), "r"(bar), "r"(row), "r"(blk), "l"(pol) : "memory");
}
__device__ __forceinline__ void tma_st(const CUtensorMap* m, int c0, int c1, uint32_t src) {
  asm volatile("cp.async.bulk.tensor.2d.global.shared::cta.bulk_group [%0, {%2, %3}], [%1];" :: "l"(m), "r"(src), "r"(c0), "r"(c1) : "memory");
}
__device__ __forceinline__ void tma_prefetch_desc(const CUtensorMap* m) { asm volatile("prefetch.tensormap [%0];" :: "l"(m) : "memory"); }
__device__ __forceinline__ void l2_prefetch(const void* p, uint32_t bytes) { asm volatile("cp.async.bulk.prefetch.L2.global [%0], %1;" :: "l"(p), "r"(bytes) : "memory"); }
__device__ __forceinline__ void bulk_commit() { asm volatile("cp.async.bulk.commit_group;" ::: "memory"); }
__device__ __forceinline__ void bulk_wait_read() { asm volatile("cp.async.bulk.wait_group.read 0;" ::: "memory"); }
__device__ __forceinline__ void bulk_wait_all() { asm volatile("cp.async.bulk.wait_group 0;" ::: "memory"); }
__device__ __forceinline__ void fence_async_smem() { asm volatile("fence.proxy.async.shared::cta;" ::: "memory"); }
__device__ __forceinline__ void fence_async_global() { asm volatile("fence.proxy.async.global;" ::: "memory"); }
__device__ __forceinline__ void fence_acquire_gpu() { asm volatile("fence.acquire.gpu;" ::: "memory"); }
__device__ __forceinline__ void fence_release_gpu() { asm volatile("fence.release.gpu;" ::: "memory"); }
__device__ __forceinline__ void st_async_f32x4(uint32_t cluster_addr, const float* v, uint32_t cluster_bar) {
  asm volatile("st.async.weak.shared::cluster.mbarrier::complete_tx::bytes.v4.f32 [%0], {%1,%2,%3,%4}, [%5];"
    :: "r"(cluster_addr), "f"(v[0]), "f"(v[1]), "f"(v[2]), "f"(v[3]), "r"(cluster_bar) : "memory");
}
__device__ __forceinline__ void nb_sync(int id, int n) { asm volatile("bar.sync %0, %1;" :: "r"(id), "r"(n) : "memory"); }
__device__ __forceinline__ void nb_arrive(int id, int n) { asm volatile("bar.arrive %0, %1;" :: "r"(id), "r"(n) : "memory"); }
__device__ __forceinline__ void wg_fence() { asm volatile("wgmma.fence.sync.aligned;" ::: "memory"); }
__device__ __forceinline__ void wg_commit() { asm volatile("wgmma.commit_group.sync.aligned;" ::: "memory"); }
template <int N> __device__ __forceinline__ void wg_wait() { asm volatile("wgmma.wait_group.sync.aligned %0;" :: "n"(N) : "memory"); }
template <int N> __device__ __forceinline__ void reg_fence(float* a) {
#pragma unroll
  for (int i = 0; i < N; i++) asm volatile("" : "+f"(a[i]) :: "memory");
}
template <int N> __device__ __forceinline__ void reg_fence(uint32_t* a) {
#pragma unroll
  for (int i = 0; i < N; i++) asm volatile("" : "+r"(a[i]) :: "memory");
}
__device__ __forceinline__ uint64_t mk_desc(uint32_t addr, uint32_t lbo) {
  return (uint64_t)((addr & 0x3FFFF) >> 4) | ((uint64_t)(lbo >> 4) << 16) | ((uint64_t)(1024 >> 4) << 32) | (1ull << 62);
}

__device__ __forceinline__ uint64_t policy_evict_first() { uint64_t pol; asm("createpolicy.fractional.L2::evict_first.b64 %0, 1.0;" : "=l"(pol)); return pol; }
__device__ __forceinline__ uint32_t ld_relaxed(const uint32_t* p) { uint32_t v; asm volatile("ld.relaxed.gpu.global.u32 %0, [%1];" : "=r"(v) : "l"(p) : "memory"); return v; }
__device__ __forceinline__ void st_relaxed(uint32_t* p, uint32_t v) { asm volatile("st.relaxed.gpu.global.u32 [%0], %1;" :: "l"(p), "r"(v) : "memory"); }
__device__ __forceinline__ void red_add_relaxed(uint32_t* p, uint32_t v) { asm volatile("red.relaxed.gpu.global.add.u32 [%0], %1;" :: "l"(p), "r"(v) : "memory"); }
__device__ __forceinline__ uint2 ld_pkt8(const uint2* p) {
  uint2 v; asm volatile("{\n.reg .b64 t;\nld.relaxed.gpu.global.b64 t, [%2];\nmov.b64 {%0,%1}, t;\n}" : "=r"(v.x), "=r"(v.y) : "l"(p) : "memory"); return v;
}
__device__ __forceinline__ void st_pkt8(uint2* p, uint32_t a, uint32_t b) {
  asm volatile("{\n.reg .b64 t;\nmov.b64 t, {%1,%2};\nst.relaxed.gpu.global.b64 [%0], t;\n}" :: "l"(p), "r"(a), "r"(b) : "memory");
}
__device__ __forceinline__ uint4 ld_pkt16(const uint4* p) {
  uint4 v; asm volatile("{\n.reg .b128 t;\n.reg .b64 a, b;\nld.relaxed.gpu.global.b128 t, [%4];\nmov.b128 {a, b}, t;\nmov.b64 {%0,%1}, a;\nmov.b64 {%2,%3}, b;\n}"
    : "=r"(v.x), "=r"(v.y), "=r"(v.z), "=r"(v.w) : "l"(p) : "memory"); return v;
}
__device__ __forceinline__ void st_pkt16(uint4* p, uint32_t x, uint32_t y, uint32_t z, uint32_t w) {
  asm volatile("{\n.reg .b128 t;\n.reg .b64 a, b;\nmov.b64 a, {%1,%2};\nmov.b64 b, {%3,%4};\nmov.b128 t, {a, b};\nst.relaxed.gpu.global.b128 [%0], t;\n}"
    :: "l"(p), "r"(x), "r"(y), "r"(z), "r"(w) : "memory");
}
__device__ __forceinline__ void cp_async16(uint32_t dst, const void* src) { asm volatile("cp.async.cg.shared.global [%0], [%1], 16;" :: "r"(dst), "l"(src) : "memory"); }
__device__ __forceinline__ void cp_async_wait() { asm volatile("cp.async.wait_all;" ::: "memory"); }
__device__ __forceinline__ uint32_t lds32(uint32_t a) { uint32_t v; asm volatile("ld.shared.u32 %0, [%1];" : "=r"(v) : "r"(a) : "memory"); return v; }
__device__ __forceinline__ float lds_f32(uint32_t a) { float v; asm volatile("ld.shared.f32 %0, [%1];" : "=f"(v) : "r"(a) : "memory"); return v; }
__device__ __forceinline__ uint2 lds64(uint32_t a) { uint2 v; asm volatile("ld.shared.v2.u32 {%0,%1}, [%2];" : "=r"(v.x), "=r"(v.y) : "r"(a) : "memory"); return v; }
__device__ __forceinline__ uint4 lds128(uint32_t a) { uint4 v; asm volatile("ld.shared.v4.u32 {%0,%1,%2,%3}, [%4];" : "=r"(v.x), "=r"(v.y), "=r"(v.z), "=r"(v.w) : "r"(a) : "memory"); return v; }
__device__ __forceinline__ void sts32(uint32_t a, uint32_t v) { asm volatile("st.shared.u32 [%0], %1;" :: "r"(a), "r"(v) : "memory"); }
__device__ __forceinline__ void sts64(uint32_t a, uint32_t x, uint32_t y) { asm volatile("st.shared.v2.u32 [%0], {%1,%2};" :: "r"(a), "r"(x), "r"(y) : "memory"); }
__device__ __forceinline__ void sts128(uint32_t a, uint32_t x, uint32_t y, uint32_t z, uint32_t w) { asm volatile("st.shared.v4.u32 [%0], {%1,%2,%3,%4};" :: "r"(a), "r"(x), "r"(y), "r"(z), "r"(w) : "memory"); }
__device__ __forceinline__ void stsm4(uint32_t a, uint32_t x, uint32_t y, uint32_t z, uint32_t w) {
  asm volatile("stmatrix.sync.aligned.m8n8.x4.shared.b16 [%0], {%1,%2,%3,%4};" :: "r"(a), "r"(x), "r"(y), "r"(z), "r"(w) : "memory");
}
__device__ __forceinline__ void ldsm4(uint32_t a, uint32_t* r) {
  asm volatile("ldmatrix.sync.aligned.m8n8.x4.shared.b16 {%0,%1,%2,%3}, [%4];" : "=r"(r[0]), "=r"(r[1]), "=r"(r[2]), "=r"(r[3]) : "r"(a) : "memory");
}
__device__ __forceinline__ void ldsm4t(uint32_t a, uint32_t* r) {
  asm volatile("ldmatrix.sync.aligned.m8n8.x4.trans.shared.b16 {%0,%1,%2,%3}, [%4];" : "=r"(r[0]), "=r"(r[1]), "=r"(r[2]), "=r"(r[3]) : "r"(a) : "memory");
}
__device__ __forceinline__ void mma16816(float* d, const uint32_t* a, uint32_t b0, uint32_t b1) {
  asm volatile("mma.sync.aligned.m16n8k16.row.col.f32.bf16.bf16.f32 {%0,%1,%2,%3}, {%4,%5,%6,%7}, {%8,%9}, {%0,%1,%2,%3};"
    : "+f"(d[0]), "+f"(d[1]), "+f"(d[2]), "+f"(d[3]) : "r"(a[0]), "r"(a[1]), "r"(a[2]), "r"(a[3]), "r"(b0), "r"(b1));
}
__device__ __forceinline__ void mma1688(float* d, uint32_t a0, uint32_t a1, uint32_t b0) {
  asm volatile("mma.sync.aligned.m16n8k8.row.col.f32.bf16.bf16.f32 {%0,%1,%2,%3}, {%4,%5}, {%6}, {%0,%1,%2,%3};"
    : "+f"(d[0]), "+f"(d[1]), "+f"(d[2]), "+f"(d[3]) : "r"(a0), "r"(a1), "r"(b0));
}
__device__ __forceinline__ uint32_t pack2(float lo, float hi) { uint32_t r; asm("cvt.rn.bf16x2.f32 %0, %1, %2;" : "=r"(r) : "f"(hi), "f"(lo)); return r; }
__device__ __forceinline__ float lo2f(uint32_t v) { return __uint_as_float(v << 16); }
__device__ __forceinline__ float hi2f(uint32_t v) { return __uint_as_float(v & 0xffff0000u); }
__device__ __forceinline__ uint32_t hmul2(uint32_t a, uint32_t b) { uint32_t r; asm("mul.rn.bf16x2 %0, %1, %2;" : "=r"(r) : "r"(a), "r"(b)); return r; }
__device__ __forceinline__ uint32_t hadd2(uint32_t a, uint32_t b) { uint32_t r; asm("add.rn.bf16x2 %0, %1, %2;" : "=r"(r) : "r"(a), "r"(b)); return r; }
__device__ __forceinline__ uint32_t hsub2(uint32_t a, uint32_t b) { uint32_t r; asm("sub.rn.bf16x2 %0, %1, %2;" : "=r"(r) : "r"(a), "r"(b)); return r; }
__device__ __forceinline__ uint32_t hfma2(uint32_t a, uint32_t b, uint32_t c) { uint32_t r; asm("fma.rn.bf16x2 %0, %1, %2, %3;" : "=r"(r) : "r"(a), "r"(b), "r"(c)); return r; }
__device__ __forceinline__ float rbf(float v) { return lo2f(pack2(v, 0.f)); }
__device__ __forceinline__ float ex2(float v) { float r; asm("ex2.approx.ftz.f32 %0, %1;" : "=f"(r) : "f"(v)); return r; }
__device__ __forceinline__ float rcp_f(float v) { float r; asm("rcp.approx.ftz.f32 %0, %1;" : "=f"(r) : "f"(v)); return r; }
__device__ __forceinline__ float sqrt_f(float v) { float r; asm("sqrt.approx.ftz.f32 %0, %1;" : "=f"(r) : "f"(v)); return r; }
__device__ __forceinline__ float sigmoid_f(float v) { return rcp_f(1.f + ex2(-1.4426950408889634f * v)); }
__device__ __forceinline__ float silu_f(float v) { return v * sigmoid_f(v); }
constexpr uint32_t ONE2 = 0x3f803f80u;

#define R8(a,o) "+f"(a[o+0]), "+f"(a[o+1]), "+f"(a[o+2]), "+f"(a[o+3]), "+f"(a[o+4]), "+f"(a[o+5]), "+f"(a[o+6]), "+f"(a[o+7])
#define R64(a,o) R8(a,o), R8(a,o+8), R8(a,o+16), R8(a,o+24), R8(a,o+32), R8(a,o+40), R8(a,o+48), R8(a,o+56)
#define D64 "{%0,%1,%2,%3,%4,%5,%6,%7,%8,%9,%10,%11,%12,%13,%14,%15,%16,%17,%18,%19,%20,%21,%22,%23,%24,%25,%26,%27,%28,%29,%30,%31," \
            "%32,%33,%34,%35,%36,%37,%38,%39,%40,%41,%42,%43,%44,%45,%46,%47,%48,%49,%50,%51,%52,%53,%54,%55,%56,%57,%58,%59,%60,%61,%62,%63"
#define D128 D64 ",%64,%65,%66,%67,%68,%69,%70,%71,%72,%73,%74,%75,%76,%77,%78,%79,%80,%81,%82,%83,%84,%85,%86,%87,%88,%89,%90,%91,%92,%93,%94,%95," \
            "%96,%97,%98,%99,%100,%101,%102,%103,%104,%105,%106,%107,%108,%109,%110,%111,%112,%113,%114,%115,%116,%117,%118,%119,%120,%121,%122,%123,%124,%125,%126,%127"

template <int TB> __device__ __forceinline__ void wgmma_ss128(float* d, uint64_t da, uint64_t db, int acc) {
  asm volatile("{\n.reg .pred p;\nsetp.ne.b32 p, %66, 0;\nwgmma.mma_async.sync.aligned.m64n128k16.f32.bf16.bf16 " D64 "}, %64, %65, p, 1, 1, 0, %67;\n}"
    : R64(d, 0) : "l"(da), "l"(db), "r"(acc), "n"(TB));
}
template <int TB> __device__ __forceinline__ void wgmma_rs128(float* d, const uint32_t* a, uint64_t db, int acc) {
  asm volatile("{\n.reg .pred p;\nsetp.ne.b32 p, %69, 0;\nwgmma.mma_async.sync.aligned.m64n128k16.f32.bf16.bf16 " D64 "}, {%64,%65,%66,%67}, %68, p, 1, 1, %70;\n}"
    : R64(d, 0) : "r"(a[0]), "r"(a[1]), "r"(a[2]), "r"(a[3]), "l"(db), "r"(acc), "n"(TB));
}
template <int TB> __device__ __forceinline__ void wgmma_ss256(float* d, uint64_t da, uint64_t db, int acc) {
  asm volatile("{\n.reg .pred p;\nsetp.ne.b32 p, %130, 0;\nwgmma.mma_async.sync.aligned.m64n256k16.f32.bf16.bf16 " D128 "}, %128, %129, p, 1, 1, 0, %131;\n}"
    : R64(d, 0), R64(d, 64) : "l"(da), "l"(db), "r"(acc), "n"(TB));
}

#define W8(a,o) "=f"(a[o+0]), "=f"(a[o+1]), "=f"(a[o+2]), "=f"(a[o+3]), "=f"(a[o+4]), "=f"(a[o+5]), "=f"(a[o+6]), "=f"(a[o+7])
#define W64(a,o) W8(a,o), W8(a,o+8), W8(a,o+16), W8(a,o+24), W8(a,o+32), W8(a,o+40), W8(a,o+48), W8(a,o+56)
template <int TB> __device__ __forceinline__ void wgmma_ss128_z(float* d, uint64_t da, uint64_t db) {
  asm volatile("wgmma.mma_async.sync.aligned.m64n128k16.f32.bf16.bf16 " D64 "}, %64, %65, 0, 1, 1, 0, %66;"
    : W64(d, 0) : "l"(da), "l"(db), "n"(TB));
}
template <int TB> __device__ __forceinline__ void wgmma_rs128_z(float* d, const uint32_t* a, uint64_t db) {
  asm volatile("wgmma.mma_async.sync.aligned.m64n128k16.f32.bf16.bf16 " D64 "}, {%64,%65,%66,%67}, %68, 0, 1, 1, %69;"
    : W64(d, 0) : "r"(a[0]), "r"(a[1]), "r"(a[2]), "r"(a[3]), "l"(db), "n"(TB));
}
template <int TB> __device__ __forceinline__ void wgmma_ss256_z(float* d, uint64_t da, uint64_t db) {
  asm volatile("wgmma.mma_async.sync.aligned.m64n256k16.f32.bf16.bf16 " D128 "}, %128, %129, 0, 1, 1, 0, %130;"
    : W64(d, 0), W64(d, 64) : "l"(da), "l"(db), "n"(TB));
}

template <int TB> __device__ __forceinline__ void wgmma_rs256(float* d, const uint32_t* a, uint64_t db) {
  asm volatile("wgmma.mma_async.sync.aligned.m64n256k16.f32.bf16.bf16 " D128 "}, {%128,%129,%130,%131}, %132, 1, 1, 1, %133;"
    : R64(d, 0), R64(d, 64) : "r"(a[0]), "r"(a[1]), "r"(a[2]), "r"(a[3]), "l"(db), "n"(TB));
}
template <int TB> __device__ __forceinline__ void wgmma_rs256_z(float* d, const uint32_t* a, uint64_t db) {
  asm volatile("wgmma.mma_async.sync.aligned.m64n256k16.f32.bf16.bf16 " D128 "}, {%128,%129,%130,%131}, %132, 0, 1, 1, %133;"
    : W64(d, 0), W64(d, 64) : "r"(a[0]), "r"(a[1]), "r"(a[2]), "r"(a[3]), "l"(db), "n"(TB));
}
#define D32 "{%0,%1,%2,%3,%4,%5,%6,%7,%8,%9,%10,%11,%12,%13,%14,%15,%16,%17,%18,%19,%20,%21,%22,%23,%24,%25,%26,%27,%28,%29,%30,%31}"
__device__ __forceinline__ void wgmma_rs64(float* d, const uint32_t* a, uint64_t db) {
  asm volatile("wgmma.mma_async.sync.aligned.m64n64k16.f32.bf16.bf16 " D32 ", {%32,%33,%34,%35}, %36, 1, 1, 1, 0;"
    : R8(d, 0), R8(d, 8), R8(d, 16), R8(d, 24) : "r"(a[0]), "r"(a[1]), "r"(a[2]), "r"(a[3]), "l"(db));
}
__device__ __forceinline__ void wgmma_rs64_z(float* d, const uint32_t* a, uint64_t db) {
  asm volatile("wgmma.mma_async.sync.aligned.m64n64k16.f32.bf16.bf16 " D32 ", {%32,%33,%34,%35}, %36, 0, 1, 1, 0;"
    : W8(d, 0), W8(d, 8), W8(d, 16), W8(d, 24) : "r"(a[0]), "r"(a[1]), "r"(a[2]), "r"(a[3]), "l"(db));
}
__device__ __forceinline__ void issue_qk(float* S, const uint32_t* Q, uint64_t dk) {
  wgmma_rs64_z(S, Q, dk);
#pragma unroll
  for (int kk = 1; kk < 8; kk++) wgmma_rs64(S, Q + 4 * kk, dk + (kk >> 2) * 512 + (kk & 3) * 2);
}
__device__ __forceinline__ void issue_pv(float* O, const uint32_t* P, uint64_t dv, int acc) {
#pragma unroll
  for (int kk = 0; kk < 4; kk++) wgmma_rs128<1>(O, P + 4 * kk, dv + kk * 128, kk ? 1 : acc);
}

#define TS(i)
#define TSC(i)
#define TSX(i)
#define TSY(k) do { if ((tid & 127) == 0) TS((k) + 40 * wg); } while (0)
#define TT(k)
#define TV(k)
#define TR(k)
#define TH(k)
#define TA(k)
#define TAFLUSH()

struct SoftmaxState { float c0, c1, l0, l1; bool shifted; };
constexpr float SM_SCALE = 0.08838834764831845f * 1.4426950408889634f;
__device__ __forceinline__ void softmax_start(SoftmaxState& z) { z.c0 = z.c1 = z.l0 = z.l1 = 0.f; z.shifted = false; }
__device__ __forceinline__ void softmax_half(float* S, uint32_t* P, float* O, SoftmaxState& z, bool first, uint32_t tag) {
  const float lo0 = z.l0, lo1 = z.l1;
  float lim = 1.2676506002282294e30f;
  const float low = first ? 8.673617379884035e-19f : 0.f;
  if (z.shifted) {
#pragma unroll
    for (int j = 0; j < 32; j++) S[j] += (j & 2) ? z.c1 : z.c0;
  }
#pragma unroll 1
  while (true) {
    bb_fence(tag);
#pragma unroll
    for (int j = 0; j < 8; j++) {
      const float p0 = ex2(S[4 * j]), p1 = ex2(S[4 * j + 1]), p2 = ex2(S[4 * j + 2]), p3 = ex2(S[4 * j + 3]);
      z.l0 += p0; z.l1 += p2; z.l0 += p1; z.l1 += p3;
      P[2 * j] = pack2(p0, p1); P[2 * j + 1] = pack2(p2, p3);
    }
    if (!__any_sync(0xffffffffu, !(z.l0 < lim && z.l1 < lim && fminf(z.l0, z.l1) >= low) && lim > 0.f)) break;
    float d0 = fmaxf(S[0], S[1]), d1 = fmaxf(S[2], S[3]);
#pragma unroll
    for (int j = 1; j < 8; j++) { d0 = fmaxf(d0, fmaxf(S[4 * j], S[4 * j + 1])); d1 = fmaxf(d1, fmaxf(S[4 * j + 2], S[4 * j + 3])); }
    d0 = fmaxf(d0, __shfl_xor_sync(0xffffffffu, d0, 1)); d1 = fmaxf(d1, __shfl_xor_sync(0xffffffffu, d1, 1));
    d0 = fmaxf(d0, __shfl_xor_sync(0xffffffffu, d0, 2)); d1 = fmaxf(d1, __shfl_xor_sync(0xffffffffu, d1, 2));
    if (!first) { d0 = fmaxf(d0, 0.f); d1 = fmaxf(d1, 0.f); }
    z.shifted = true;
    z.c0 -= d0; z.c1 -= d1;
#pragma unroll
    for (int j = 0; j < 32; j++) S[j] -= (j & 2) ? d1 : d0;
    const float a0 = first ? 1.f : ex2(-d0), a1 = first ? 1.f : ex2(-d1);
    z.l0 = lo0 * a0; z.l1 = lo1 * a1;
    lim = -1.f;
    wg_wait<0>();
    reg_fence<64>(O);
#pragma unroll
    for (int j = 0; j < 16; j++) { O[4 * j] *= a0; O[4 * j + 1] *= a0; O[4 * j + 2] *= a1; O[4 * j + 3] *= a1; }
  }
}

__device__ __forceinline__ void modulate_frags(uint32_t* A, const uint32_t* V, const uint4* R, const uint32_t* ln) {
#pragma unroll
  for (int kk = 0; kk < 4; kk++) {
    const uint4 sa = R[kk >> 1], c1 = R[2 + (kk >> 1)];
#pragma unroll
    for (int j = 0; j < 4; j++) {
      const uint32_t n = hfma2(V[4 * kk + j], ln[(j & 1) * 2 + 1], ln[(j & 1) * 2]);
      A[4 * kk + j] = (kk & 1) ? ((j & 2) ? hfma2(n, c1.w, sa.x) : hfma2(n, c1.z, sa.w)) : ((j & 2) ? hfma2(n, c1.y, sa.z) : hfma2(n, c1.x, sa.y));
    }
  }
}
__device__ __forceinline__ void publish_record(uint4* dst, uint32_t pk, int src, int vec, bool doit) {
  const int r = vec ? 0 : 12;
  const uint32_t x = __shfl_sync(0xffffffffu, pk, src + r), y = __shfl_sync(0xffffffffu, pk, src + ((r + 4) & 12));
  const uint32_t z = __shfl_sync(0xffffffffu, pk, src + ((r + 8) & 12)), w = __shfl_sync(0xffffffffu, pk, src + ((r + 12) & 12));
  if (doit) st_pkt16(dst, ~x, y, z, w);
}
__device__ __forceinline__ void put_record(uint32_t sb, int idx, const uint4& v) {
  sts128(sb + SM_STASH + idx * 16, ~v.x, v.y, v.z, v.w);
  sts128(sb + SM_STASH + 16384 + idx * 16, ~v.x, v.y, v.z, v.w);
}
__device__ __forceinline__ float mod_value(float v, int vec) {
  v = rbf(v);
  return (vec ? rbf(1.f + v) : v) * SM_SCALE;
}

__device__ __forceinline__ void row_rcp(float& l0, float& l1) {
  l0 += __shfl_xor_sync(0xffffffffu, l0, 1); l1 += __shfl_xor_sync(0xffffffffu, l1, 1);
  l0 += __shfl_xor_sync(0xffffffffu, l0, 2); l1 += __shfl_xor_sync(0xffffffffu, l1, 2);
  l0 = rcp_f(l0); l1 = rcp_f(l1);
}
__device__ __forceinline__ void stage_o(const float* O, float r0, float r1, uint32_t stsm_addr) {
#pragma unroll
  for (int kk = 0; kk < 8; kk++) {
    stsm4((stsm_addr + (kk >> 2) * 8192) ^ ((kk & 3) * 32),
          pack2(O[8 * kk + 0] * r0, O[8 * kk + 1] * r0), pack2(O[8 * kk + 2] * r1, O[8 * kk + 3] * r1),
          pack2(O[8 * kk + 4] * r0, O[8 * kk + 5] * r0), pack2(O[8 * kk + 6] * r1, O[8 * kk + 7] * r1));
  }
}

__global__ void __cluster_dims__(2, 1, 1) __launch_bounds__(NTHREADS, 1)
fused_kernel(const Params p, const __grid_constant__ CUtensorMap mH, const __grid_constant__ CUtensorMap mWq,
             const __grid_constant__ CUtensorMap mK, const __grid_constant__ CUtensorMap mV,
             const __grid_constant__ CUtensorMap mO, const __grid_constant__ CUtensorMap mWo,
             const __grid_constant__ CUtensorMap mX, const __grid_constant__ CUtensorMap mOut,
             const __grid_constant__ CUtensorMap mWg, const __grid_constant__ CUtensorMap mWu,
             const __grid_constant__ CUtensorMap mWd, const __grid_constant__ CUtensorMap mWm,
             const __grid_constant__ CUtensorMap mWs) {
  extern __shared__ __align__(1024) uint8_t smem_raw[];
  TH(0);
  const uint32_t sb = smem_u32(smem_raw);
  const int tid = threadIdx.x;
  const int b0 = blockIdx.x;
  const int lane = tid & 31;
  const int role = __shfl_sync(0xffffffffu, tid >> 8, 0);

  if (b0 >= NMAIN) {
    const uint32_t tag = ld_relaxed(&g_epoch) + 1;
    const int sp = b0 - NMAIN, vec = 2 + sp;
    const int warp = __shfl_sync(0xffffffffu, tid >> 5, 0);
    float* sc = reinterpret_cast<float*>(smem_raw + SM_STASH);
    float* red = reinterpret_cast<float*>(smem_raw + SM_STASH + 4096);
    const int ridx = (lane >> 3) * 2 * RV + (sp & 1) * RV + 16 * RS + (sp >> 1) * 16 + (warp & 1) * 8 + (lane & 7);
    if (warp < 8) st_pkt16(&g_rec[warp >> 2][0][ridx + (warp & 2) * 16], 0, 0, 0, 0);
#pragma unroll 1
    for (int i = tid; i < 1024; i += NTHREADS) sc[i] = rbf(silu_f(__bfloat162float(p.c[i])));
    if (tid == 0) {
      tma_prefetch_desc(&mWs);
      for (int s = 0; s < NST2; s++) { mbar_init(sb + BAR_FULL2 + 8 * s, 1); mbar_init(sb + BAR_EMPTY2 + 8 * s, 8); }
      fence_async_smem();
      int it = 0;
      do { __nanosleep(100); spin_guard(it); } while (ld_pkt16(&g_lnst[8 * 32 + 16 * sp]).w != tag);
      if (SPD) __nanosleep(SPD);
    }
    __syncthreads();
    int s = 0; uint32_t ph = 0;
    if (tid == 0) TS(0);
    if (warp == 8) {
      const uint64_t pol = policy_evict_first();
#pragma unroll 1
      for (int n = 0; n < 80; n++) {
        mbar_wait_g(sb + BAR_EMPTY2 + 8 * s, ph ^ 1);
        if (elect_one()) {
          mbar_expect_tx(sb + BAR_FULL2 + 8 * s, 32768);
          if (n < 16) {
            tma_ld_hint(sb + s * ST2, &mWs, (sp & 1) * 1024 + 512 + (n >> 3) * 256 + (sp >> 1) * 128, (n & 7) * 128, sb + BAR_FULL2 + 8 * s, pol);
          } else {
#pragma unroll
            for (int j = 0; j < 4; j++) tma_ld_hint(sb + s * ST2 + j * 8192, &mWm, vec * 1024 + j * 256, (n - 16) * 16, sb + BAR_FULL2 + 8 * s, pol);
          }
        }
        __syncwarp();
        if (++s == NST2) { s = 0; ph ^= 1; }
      }
    } else if (warp < 8) {
      float acc[8];
#pragma unroll
      for (int i = 0; i < 8; i++) acc[i] = 0.f;
      auto stage = [&](uint32_t a0, int da, const float* cp, int dc) {
        mbar_wait_g(sb + BAR_FULL2 + 8 * s, ph);
#pragma unroll
        for (int i = 0; i < 8; i++) {
          const uint4 v = lds128(a0 + s * ST2 + i * da);
          const float c = cp[i * dc];
          acc[0] = fmaf(lo2f(v.x), c, acc[0]); acc[1] = fmaf(hi2f(v.x), c, acc[1]);
          acc[2] = fmaf(lo2f(v.y), c, acc[2]); acc[3] = fmaf(hi2f(v.y), c, acc[3]);
          acc[4] = fmaf(lo2f(v.z), c, acc[4]); acc[5] = fmaf(hi2f(v.z), c, acc[5]);
          acc[6] = fmaf(lo2f(v.w), c, acc[6]); acc[7] = fmaf(hi2f(v.w), c, acc[7]);
        }
        if (__shfl_sync(0xffffffffu, lane, __float_as_uint(acc[7]) & 31) < 32 && lane == 0) mbar_arrive(sb + BAR_EMPTY2 + 8 * s);
        if (++s == NST2) { s = 0; ph ^= 1; }
      };
#pragma unroll 1
      for (int n = 0; n < 16; n++) {
        stage(sb + tid * 16, 4096, sc + (n & 7) * 128 + (tid >> 4), 16);
        if ((n & 7) == 7) {
          float* r2 = red + 2048 + (n & 8) * 256;
#pragma unroll
          for (int i = 0; i < 8; i++) { r2[tid * 8 + i] = acc[i]; acc[i] = 0.f; }
          nb_sync(NB_CONS, 256);
          if (warp < 2) {
            float v0 = 0.f, v1 = 0.f;
#pragma unroll 4
            for (int i = 0; i < 16; i++) { const float2 e = reinterpret_cast<const float2*>(r2)[i * 64 + tid]; v0 += e.x; v1 += e.y; }
            publish_record(&g_rec[tag & 1][0][ridx + (n >> 3) * 32], pack2(mod_value(v0, sp & 1), mod_value(v1, sp & 1)),
                           (lane & 4) * 4 + (lane & 3), sp & 1, true);
          }
          if (tid == 0) TS(1 + (n >> 3));
        }
      }
#pragma unroll 1
      for (int n = 0; n < 64; n++) {
        stage(sb + ((tid >> 5) & 3) * 8192 + (tid >> 7) * 4096 + (tid & 31) * 16, 512, sc + n * 16 + (tid >> 7) * 8, 1);
      }
#pragma unroll
      for (int i = 0; i < 8; i++) red[(tid >> 7) * 1024 + (tid & 127) * 8 + i] = acc[i];
    }
    __syncthreads();
    float dot = 0.f;
#pragma unroll 1
    for (int i = tid; i < 512; i += NTHREADS) {
      uint32_t v = pack2(red[2 * i] + red[1024 + 2 * i], red[2 * i + 1] + red[1024 + 2 * i + 1]);
      st_pkt8(&g_mod[vec * 512 + i], v, tag);
      if (vec == 4) v = hadd2(v, ONE2);
      const uint32_t wr = reinterpret_cast<const uint32_t*>(p.w_r)[i];
      dot = fmaf(lo2f(v), lo2f(wr), fmaf(hi2f(v), hi2f(wr), dot));
    }
#pragma unroll
    for (int o = 16; o; o >>= 1) dot += __shfl_xor_sync(0xffffffffu, dot, o);
    if (lane == 0) sc[warp] = dot;
    __syncthreads();
    if (tid == 0) {
      dot = 0.f;
      for (int w = 0; w < 12; w++) dot += sc[w];
      fence_release_gpu();
      st_pkt8(&g_vdone[(vec - 2) * 16], __float_as_uint(dot), tag);
      TS(11);
#pragma unroll 1
      for (int i = 0; i < 128; i++) {
        const int u = i * 4 + (b0 - NMAIN);
        l2_prefetch(p.wo + (size_t)((4 * ((u >> 4) & 7) + (u >> 7)) * 128 + (u & 15) * 8) * 1024, 16384);
        __nanosleep(PFW);
      }
    }
    return;
  }

  const uint32_t rank = b0 & 1;
  const bool slab = !(b0 & 32), late = b0 & 16;
  const uint32_t c0 = clock();
  if (tid == 352) TS(0);
  auto load_slab = [&]() {
    const bf16* wp = p.w_mod + (size_t)(512 * rank + 2 * (tid & ~31) + 2 * (lane & 3) + ((lane >> 2) & 1)) * 6144 + 32 * (b0 >> 1) + 8 * (lane >> 3);
    const uint64_t pef = policy_evict_first();
#pragma unroll
    for (int i = 0; i < 8; i++)
      asm volatile("cp.async.cg.shared.global.L2::cache_hint [%0], [%1], 16, %2;"
        :: "r"(sb + SM_WSLAB + tid * 16 + i * 4096), "l"(wp + (size_t)i * 8 * 6144), "l"(pef) : "memory");
  };
  if (tid == 256) {
    mbar_init(sb + BAR_XH, 1);
    fence_async_smem();
    mbar_expect_tx(sb + BAR_XH, 32768);
    if (XD) while ((uint32_t)clock() - c0 < XD) {}
#pragma unroll
    for (int i = 0; i < 2; i++)
      asm volatile("cp.async.bulk.shared::cluster.global.mbarrier::complete_tx::bytes [%0], [%1], 16384, [%2];"
        :: "r"(sb + SM_XROW + i * ST1), "l"(p.x + (size_t)b0 * 16384 + i * 8192), "r"(sb + BAR_XH) : "memory");
  }
  __syncwarp();
  uint32_t cw[8];
#pragma unroll
  for (int i = 0; i < 8; i++) cw[i] = 0;
  if (!role && slab) {
#pragma unroll
    for (int i = 0; i < 8; i++) cw[i] = ld_relaxed(reinterpret_cast<const uint32_t*>(p.c) + 256 * rank + (tid & ~28) + 4 * i);
  }
  uint32_t epoch = 0;
  if (!role) epoch = ld_relaxed(&p.sc->epoch[lane]);
  if (!role && slab && !late) load_slab();
#define TILE_ROLES() \
  mbar_wait(sb + BAR_ROLE, 0); \
  const int b = 2 * __shfl_sync(0xffffffffu, lds32(sb + SM_ROLE), 0) + rank; \
  const int rt = b >> 3;     \
  const int ct = b & 7;

  if (role) {
    asm volatile("setmaxnreg.dec.sync.aligned.u32 24;");
    const int warp = __shfl_sync(0xffffffffu, tid >> 5, 0);
    if (tid == 256) {
      mbar_init(sb + BAR_RED, 1);
      for (int s = 0; s < 2; s++) mbar_init(sb + BAR_OF + 8 * s, 1);
      mbar_init(sb + BAR_ROLE, 1);
      for (int s = 0; s < 5; s++) { mbar_init(sb + BAR_FULL1 + 8 * s, 1); mbar_init(sb + BAR_EMPTY1 + 8 * s, 4); }
      for (int s = 0; s < 2; s++) { mbar_init(sb + BAR_STASH + 8 * s, 1); mbar_init(sb + BAR_X + 8 * s, 1); }
      for (int s = 0; s < 4; s++) mbar_init(sb + BAR_HS + 8 * s, 1);
      mbar_init(sb + BAR_G, 16); mbar_init(sb + BAR_T1, 1); mbar_init(sb + BAR_HF, 1);
      mbar_init(sb + BAR_SFREE, 4); mbar_init(sb + BAR_TFREE, 8);
      mbar_init(sb + BAR_FFN, 4); mbar_init(sb + BAR_FFN + 8, 2);
      mbar_init(sb + BAR_CAND, 1); mbar_init(sb + BAR_VEC, 32); for (int s = 0; s < 3; s++) mbar_init(sb + BAR_TAB + 8 * s, 32);
      mbar_expect_tx(sb + BAR_RED, 1024);
      mbar_expect_tx(sb + BAR_ROLE, 4);
      asm volatile("fence.mbarrier_init.release.cluster;" ::: "memory");
    }
    __syncwarp();
    asm volatile("barrier.cluster.arrive.relaxed.aligned;" ::: "memory");
    const int ridx = ((lane >> 1) & 3) * 2 * RV + (b0 >> 6) * RV + ((b0 >> 1) & 31) * RS + 2 * rank + (lane & 1) + (lane >> 3) * 4;
    if (warp == 11 && slab && lane < 2 * RS) { st_pkt16(&g_rec[0][0][ridx], 0, 0, 0, 0); st_pkt16(&g_rec[1][0][ridx], 0, 0, 0, 0); }
    if (tid == 256) {
      tma_prefetch_desc(&mWq); tma_prefetch_desc(&mX); tma_prefetch_desc(&mH); tma_prefetch_desc(&mK); tma_prefetch_desc(&mV); tma_prefetch_desc(&mO);
    }
    uint32_t pairid = 0;
    if (tid == 320 && rank == 0) {
      uint32_t t;
      asm("mov.u32 %0, %%smid;" : "=r"(t));
      t >>= 1;
      uint32_t grp = ((0x73216540u >> (4 * ((t < 32 ? t : t < 60 ? 1 + (t - 32) % 7 : t < 62 ? t - 54 : 0) & 7))) & 7) - 1, slot;
      int it = 0;
      do {
        grp = (grp + 1) & 7;
        asm volatile("atom.relaxed.gpu.global.add.u32 %0, [%1], 1;" : "=r"(slot) : "l"(&p.sc->ticket[grp * 32]) : "memory");
        spin_guard(it);
      } while (slot >= 8);
      pairid = slot * 8 + grp;
    }
    __syncwarp();
    asm volatile("barrier.cluster.wait.aligned;" ::: "memory");
    if (tid == 320 && rank == 0) {
#pragma unroll
      for (int r = 0; r < 2; r++)
        asm volatile("st.async.weak.shared::cluster.mbarrier::complete_tx::bytes.b32 [%0], %1, [%2];"
          :: "r"(mapa(sb + SM_ROLE, r)), "r"(pairid), "r"(mapa(sb + BAR_ROLE, r)) : "memory");
    }
    __syncwarp();
    const uint32_t tag = ld_relaxed(&g_epoch) + 1;
    if (warp == 8) {
      TILE_ROLES();
      const int kvrow = (ct >> 1) * 2048 + 1536, arow = rt * 128 + rank * 64;
      const uint64_t pef = policy_evict_first();
#pragma unroll 1
      for (int pair = 0; pair < 2; pair++) {
        const int wblk = (4 * ct + 2 * pair) * 2;
        if (pair) { mbar_wait_g(sb + BAR_HF, 0); fence_async_global(); }
#pragma unroll 1
        for (int n = 0; n < 16; n++) {
          const uint32_t s = n & 3, st = sb + SM_RING + s * ST1, fb = sb + BAR_FULL1 + 8 * s;
          if (n == 2 && pair == 0) mbar_wait_g(sb + BAR_G, 0);
          mbar_wait_g(fb + (BAR_EMPTY1 - BAR_FULL1), ((n >> 2) & 1) ^ 1);
          if (elect_one()) {
            mbar_expect_tx(fb, 49152);
            if (pair) tma_ld_mc_hint(st + rank * 8192, &mH, n * 64, arow, fb, pef); else
            tma_ld_mc(st + rank * 8192, pair ? &mH : &mX, n * 64, arow, fb);
            tma_ld3_hint(st + 16384, &mWq, n * 64, wblk, fb, pef);
          }
          __syncwarp();
        }
#pragma unroll 1
        for (int n = 0; n < 16; n++) {
          const uint32_t s = n & 3, st = sb + SM_RING + s * ST1 + rank * 8192, fb = sb + BAR_FULL1 + 8 * s;
          const int h0 = n == 0 ? 0 : n == 15 ? 14 : n + 1, h1 = n == 0 ? 1 : n == 15 ? 15 : n - 1;
          mbar_wait_g(fb + (BAR_EMPTY1 - BAR_FULL1), ((n >> 2) & 1) ^ 1);
          if (elect_one()) {
            mbar_expect_tx(fb, 32768);
            tma_ld_mc(st, n == 15 ? &mV : &mK, rank * 64, kvrow + (h0 & 7) * 64, fb);
            tma_ld_mc(st + 16384, n == 0 ? &mK : &mV, rank * 64, kvrow + (h1 & 7) * 64, fb);
            if (n == 3 && pair == 1) mbar_arrive(sb + BAR_T1);
          }
          __syncwarp();
        }
      }
      {
        uint32_t s = 0, ph = 1;
#pragma unroll 1
        for (int half = 0; half < 2; half++) {
          mbar_wait_g(sb + BAR_OF + 8 * half, 0);
          fence_async_global();
#pragma unroll 1
          for (int n = 32 * half; n < 32 * half + 32; n++) {
            const uint32_t st = sb + SM_RING + s * ST1, fb = sb + BAR_FULL1 + 8 * s;
            const int k0 = ((n & 14) * 2 + (n >> 4)) * 128 + (n & 1) * 64;
            mbar_wait_g(n == 8 ? sb + BAR_SFREE : fb + (BAR_EMPTY1 - BAR_FULL1), n == 8 ? 0 : ph ^ (s >> 2));
            if (elect_one()) {
              mbar_expect_tx(fb, 32768);
              tma_ld_mc_hint(st + rank * 8192, &mO, k0, arow, fb, pef);
              tma_ld3_hint(st + 16384, &mWo, k0, 2 * ct, fb, pef);
            }
            __syncwarp();
            if (++s == 5 || n == 3) { s = 0; ph ^= 1; }
          }
        }
        if (b < NFFN) {
#pragma unroll 1
          for (s = 0; s < 2; s++) {
            mbar_wait_g(sb + BAR_EMPTY1 + 8 * s, 0);
            if (elect_one()) {
              mbar_expect_tx(sb + BAR_FFN + 8, 32768);
              tma_ld3_hint(sb + SM_RING + s * ST1, &mWd, b * 32, s * 8, sb + BAR_FFN + 8, pef);
            }
            __syncwarp();
          }
        }
      }
    } else if (warp <= 10) {
      const int w = warp - 9;
      TILE_ROLES();
      const uint32_t st = sb + SM_STASH + w * 16384;
#pragma unroll 1
      for (int j = 0; j < 2; j++) {
        nb_sync(NB_OST + w, 160);
        if (elect_one()) {
          fence_async_smem();
          tma_st(&mH, (2 * ct + j) * 64, rt * 128 + w * 64, st + 4096);
          bulk_commit();
          bulk_wait_read();
          mbar_arrive(sb + BAR_HS + 16 * w + 8 * j);
          if (j) {
            bulk_wait_all();
            fence_async_global();
            fence_release_gpu();
            red_add_relaxed(&g_hflag[rt * 32], 1);
          }
        }
        __syncwarp();
      }
#pragma unroll 1
      for (int r = 0; r < 4; r++) {
        nb_sync(NB_OST + w, 160);
        if (elect_one()) {
          fence_async_smem();
          const int hcol = (4 * ct + r) * 128;
          tma_st(&mO, hcol, rt * 128 + w * 64, st);
          tma_st(&mO, hcol + 64, rt * 128 + w * 64, st + 8192);
          bulk_commit();
          bulk_wait_read();
          if (r < 2) {
            mbar_arrive(sb + BAR_STASH + 8 * w);
          } else if (r == 2) {
            mbar_expect_tx(sb + BAR_X + 8 * w, 16384);
            tma_ld_hint(st, &mX, ct * 128, rt * 128 + w * 64, sb + BAR_X + 8 * w, policy_evict_first());
            tma_ld_hint(st + 8192, &mX, ct * 128 + 64, rt * 128 + w * 64, sb + BAR_X + 8 * w, policy_evict_first());
          } else {
            mbar_arrive_cl(mapa(sb + BAR_SFREE, 0)); mbar_arrive_cl(mapa(sb + BAR_SFREE, 1));
          }
          bulk_wait_all();
          fence_async_global();
          fence_release_gpu();
          red_add_relaxed(&g_oflag[(rt * 4 + r) * 32], 1);
        }
        __syncwarp();
      }
      nb_sync(NB_OST + w, 160);
      int skip = -1;
      mbar_wait_g(sb + BAR_CAND, 0);
      const bool has_cand = (lds32(sb + SM_CAND) >> 6) == w;
      if (has_cand) {
        nb_sync(NB_WIN + w, 160);
        skip = (int)lds32(sb + SM_WROW + 4 * w) - (rt * 128 + w * 64);
      }
      if ((unsigned)skip >= 64u) {
        if (elect_one()) {
          fence_async_smem();
          tma_st(&mOut, ct * 128, rt * 128 + w * 64, sb + SM_OUT + w * 16384);
          tma_st(&mOut, ct * 128 + 64, rt * 128 + w * 64, sb + SM_OUT + w * 16384 + 8192);
          bulk_commit();
          bulk_wait_read();
        }
        __syncwarp();
      } else {
        uint4* dst = reinterpret_cast<uint4*>(p.out + (size_t)(rt * 128 + w * 64 + (lane >> 4)) * 1024 + ct * 128) + (lane & 15);
#pragma unroll 2
        for (int r = lane >> 4; r < 64; r += 2) {
          const uint4 v = lds128(sb + SM_OUT + w * 16384 + ((lane >> 3) & 1) * 8192 + r * 128 + (((lane ^ r) & 7) * 16));
          if (r != skip) *dst = v;
          dst += 256;
        }
      }
      if (!has_cand) nb_sync(NB_WIN + w, 160);
    } else {
      if (slab) {
        mbar_wait_g(sb + BAR_RED, 0);
        float v = 0.f;
#pragma unroll
        for (int w = 0; w < 8; w++) v += lds_f32(sb + SM_RED + w * 128 + lane * 4);
        v += __shfl_xor_sync(0xffffffffu, v, 16);
        v = mod_value(v, b0 >> 6);
        publish_record(&g_rec[tag & 1][0][ridx], pack2(v, __shfl_down_sync(0xffffffffu, v, 1)), 2 * (lane & 1), b0 >> 6, lane < 8);
        if (lane == 0) TS(1);
      }
      mbar_wait_g(sb + BAR_G, 0);
#pragma unroll 1
      for (int i = 1; i < 4; i++) {
        const uint4* mp = &g_rec[tag & 1][(b0 >> 1) & (NREP - 1)][i == 1 ? (8 + (lane >> 2)) * RS + (lane & 3) : 16 * RS - 64 + 32 * i + lane];
        uint4 v0, v1; int it = 0;
        while (true) {
          v0 = ld_pkt16(mp); v1 = ld_pkt16(mp + RV);
          if (v0.x != 0 && v1.x != 0) break;
          spin_guard(it); __nanosleep(PLD);
        }
        put_record(sb, 32 * i + lane, v0);
        put_record(sb, 128 + 32 * i + lane, v1);
        mbar_arrive(sb + BAR_TAB - 8 + 8 * i);
        if (lane == 0) {
          TS(3 + i + (i > 2));
          if (i == 1) l2_prefetch(((b0 & 64) ? p.vc : p.kc) + (size_t)(((b0 >> 4) & 3) * 2048 + 1536) * 128 + (b0 & 15) * 4096, 8192);
        }
        __syncwarp();
      }
      TILE_ROLES();
      if (lane == 0) {
        int it = 0;
        do { __nanosleep(500); spin_guard(it); } while (ld_relaxed(&g_hflag[rt * 32]) != tag * 16u);
        fence_acquire_gpu();
        mbar_arrive(sb + BAR_HF);
        if (b < NFFN) for (int i = 0; i < 8; i++) { __nanosleep(800); l2_prefetch(p.wd + (size_t)(b * 32 + i * 4) * 1024, 8192); }
      }
      __syncwarp();
      {
        uint2 v; int it = 0;
        do { __nanosleep(1000); v = ld_pkt8(&g_vdone[(lane & 3) * 16]); spin_guard(it); }
        while (!(v.y == tag));
        __syncwarp();
        fence_acquire_gpu();
        if (lane == 1 || lane == 2) sts32(sb + SM_SCAL + (2 - lane) * 4, v.x);
      }
#pragma unroll 1
      for (int i = 0; i < 2; i++) {
        const int q = i * 32 + lane, pi = ct * 64 + q;
        const uint32_t vga = g_mod[2 * 512 + pi].x, vsb = g_mod[3 * 512 + pi].x, vcb = g_mod[4 * 512 + pi].x, vgb = g_mod[5 * 512 + pi].x;
        const uint32_t wr = reinterpret_cast<const uint32_t*>(p.w_r)[pi];
        const uint32_t c1 = hadd2(vcb, ONE2);
        const float al = lo2f(c1) * lo2f(wr), ah = hi2f(c1) * hi2f(wr);
        const uint32_t o8 = (q & 3) * 8 + ((q >> 2) & 1) * 4;
        sts32(sb + SM_GA + (q >> 3) * 32 + o8, vga);
        sts128(sb + SM_REC + q * 16, c1, vsb, vgb, 0);
        const uint32_t ahi = pack2(al, ah), alo = pack2(al - lo2f(ahi), ah - hi2f(ahi));
        const uint32_t ba = sb + SM_B1 + (q >> 3) * 128 + o8;
        sts32(ba, ONE2); sts32(ba + 32, ahi); sts32(ba + 64, alo); sts32(ba + 96, 0);
      }
      if (lane == 0) TS(28);
      if (lane == 0) {
        tma_prefetch_desc(&mWo); tma_prefetch_desc(&mOut); tma_prefetch_desc(&mWd); tma_prefetch_desc(&mWg); tma_prefetch_desc(&mWu);
#pragma unroll 1
        for (int r = 0; r < 4; r++) {
          int it = 0;
          do { __nanosleep(200); spin_guard(it); } while (ld_relaxed(&g_oflag[(rt * 4 + r) * 32]) != tag * 16u);
          if (r & 1) { fence_acquire_gpu(); mbar_arrive(sb + BAR_OF + 8 * (r >> 1)); }
          if (r == 1 && b < NFFN) {
            const uint64_t pef = policy_evict_first();
            mbar_wait_g(sb + BAR_T1, 0);
#pragma unroll 1
            for (int i = 0; i < 4; i++) {
              mbar_expect_tx(sb + BAR_FFN, 16384);
              tma_ld_hint(sb + SM_RING + i * ST1 + 32768, &mWg, b * 32, i * 256, sb + BAR_FFN, pef);
              __nanosleep(GATED);
            }
          }
        }
      }
      __syncwarp();
      if (b < NFFN) {
        mbar_wait_g(sb + BAR_TFREE, 0);
        const uint64_t pef = policy_evict_first();
#pragma unroll 1
        for (int i = 0; i < 5; i++) {
          if (i > 0 && lane == 0) {
            mbar_expect_tx(sb + BAR_FFN, 16384);
            tma_ld_hint(sb + SM_RING + (i - 1) * ST1 + 32768, &mWu, b * 32, (i - 1) * 256, sb + BAR_FFN, pef);
          }
          if (i < 4) {
#pragma unroll 1
            for (int j = 0; j < 8; j++) {
              asm volatile("prefetch.global.L2 [%0];" :: "l"(p.wu + (size_t)(i * 256 + j * 32 + lane) * 3584 + b * 32) : "memory");
              __nanosleep(UPD);
            }
            __nanosleep(500);
          }
        }
      }
      if (lane == 0) TS(29);
#pragma unroll 1
      for (int i = lane; i < 128; i += 32) st_pkt16(&g_stats[b * 128 + i], 0, 0, 0, 0);
      st_pkt16(&g_cand[b * 32 + lane], 0, 0, 0, 0);
      if (lane < ESTR) st_pkt16(&g_entry[(ct * 16 + rt) * ESTR + lane], 0, 0, 0, 0);
#pragma unroll 1
      for (int i = lane; i < (b < NFFN ? 512 : 0); i += 32) st_pkt16(&g_ypart[((i >> 2) * NFFN + b) * 4 + (i & 3)], 0, 0, 0, 0);
      mbar_arrive(sb + BAR_VEC);
      uint4* const cp = &g_cand[b * 32 + lane];
      uint4* const ep = &g_entry[(ct * 16 + rt) * ESTR];
      nb_sync(NB_AMAX, 288);
      TV(0);
      const uint2 e = lds64(sb + SM_AMAX + (lane & 7) * 8);
      const int tmax = __reduce_max_sync(0xffffffffu, (int)e.x);
      const uint32_t row = ~tmax & 127;
      const int wl = row >> 4;
      const uint32_t xa = sb + SM_X2 + (row >> 6) * 16384 + (lane >> 4) * 8192 + (row & 63) * 128 + (lane & 3) * 4
                        + ((((lane >> 1) & 6) ^ (row & 7)) * 16);
      const uint32_t v0 = lds32(xa), v1 = lds32(xa ^ 16);
      if (lane == wl) st_pkt16(ep, (tmax | 127) - rt, rt * 128 + row, e.y, tag);
      st_pkt16(cp, v0, v1, tag, 0);
      if (lane == 0) { sts32(sb + SM_CAND, row); mbar_arrive(sb + BAR_CAND); }
      TV(1);
      if (lane == 0) TS(15);
    }
  } else {
    const int warp = tid >> 5;
    const int wg = warp >> 2, wq = warp & 3;
    const int g = lane >> 2, t = lane & 3;
    uint32_t tag;
    uint32_t ln[4];
    float acc[128];
    uint32_t bf[16];
    auto gemv = [&]() {
          asm volatile("cp.async.wait_all;" ::: "memory");
          float d0[4] = {0.f, 0.f, 0.f, 0.f}, d1[4] = {0.f, 0.f, 0.f, 0.f};
#pragma unroll
          for (int i = 0; i < 8; i++) {
            const uint4 wv = lds128(sb + SM_WSLAB + tid * 16 + i * 4096);
            const uint32_t a[4] = {wv.x, wv.y, wv.z, wv.w};
            mma16816((i & 1) ? d1 : d0, a, bf[2 * i], bf[2 * i + 1]);
          }
#pragma unroll
          for (int i = 0; i < 4; i++) { d0[i] += d1[i]; d0[i] += __shfl_xor_sync(0xffffffffu, d0[i], 6); }
          const uint32_t dst = mapa(sb + SM_MISC, t & 1) - SM_MISC;
          if (!(lane & 6)) st_async_f32x4(dst + SM_RED + warp * 128 + rank * 64 + g * 8, d0, dst + BAR_RED);
          TH(4);
    };
    {
      asm volatile("barrier.cluster.arrive.relaxed.aligned;" ::: "memory");
      if (lane == 0) st_pkt16(&g_lnst[8 * b0 + warp], 0, 0, 0, 0);
      TH(1);
      asm volatile("setmaxnreg.inc.sync.aligned.u32 240;");
      TH(2);
#pragma unroll
      for (int i = 0; i < 8; i++) {
        const float sv = silu_f((g & 4) ? hi2f(cw[i]) : lo2f(cw[i]));
        const uint32_t sp = (g & 1) ? pack2(0.f, sv) : pack2(sv, 0.f);
        bf[2 * i] = (g & 2) ? 0 : sp; bf[2 * i + 1] = (g & 2) ? sp : 0;
      }
      asm volatile("barrier.cluster.wait.aligned;" ::: "memory");
#pragma unroll
      for (int i = 0; i < 128; i++) acc[i] = 0.f;
      reg_fence<128>(acc);
      tag = __shfl_sync(0xffffffffu, epoch, 0) + 1;
      if (slab && late) { while ((uint32_t)clock() - c0 < WL) {} load_slab(); }
      TH(3);
      if (slab && !late) gemv();
      {
        {
          mbar_wait(sb + BAR_XH, 0);
          TH(5);
          float ds[4] = {0.f, 0.f, 0.f, 0.f}, dq[4][4];
#pragma unroll
          for (int i = 0; i < 4; i++) { dq[i][0] = dq[i][1] = dq[i][2] = dq[i][3] = 0.f; }
#pragma unroll
          for (int i = 0; i < 8; i++) {
            uint32_t a[4];
            ldsm4(sb + SM_XROW + wg * ST1 + wq * 4096 + ((lane >> 3) & 1) * 2048 + i * 256 + (lane >> 4) * 128 + (lane & 7) * 16, a);
            mma16816(ds, a, ONE2, ONE2);
            mma1688(dq[0], a[0], a[1], a[0]); mma1688(dq[1], a[0], a[1], a[1]);
            mma1688(dq[2], a[2], a[3], a[2]); mma1688(dq[3], a[2], a[3], a[3]);
          }
          const bool dg = t == (g >> 1);
          const float q0 = dg ? ((g & 1) ? dq[0][1] + dq[2][1] : dq[0][0] + dq[2][0]) : 0.f;
          const float q1 = dg ? ((g & 1) ? dq[1][3] + dq[3][3] : dq[1][2] + dq[3][2]) : 0.f;
          float q = ((lane & 1) ? q1 : q0) + __shfl_xor_sync(0xffffffffu, (lane & 1) ? q0 : q1, 1);
          float sm = (lane & 1) ? ds[2] : ds[0];
          q += __shfl_xor_sync(0xffffffffu, q, 2);
#pragma unroll
          for (int o = 4; o <= 16; o <<= 1) { q += __shfl_xor_sync(0xffffffffu, q, o); sm += __shfl_xor_sync(0xffffffffu, sm, o); }
          const float mean = sm * (1.f / 1024.f);
          const float rd = rcp_f(rbf(sqrt_f(rbf(rbf(fmaxf(fmaf(-mean, mean, q * (1.f / 1024.f)), 0.f)) + 1e-5f))));
          const float mean1 = __shfl_sync(0xffffffffu, mean, 1), rd1 = __shfl_sync(0xffffffffu, rd, 1);
          const uint32_t rh = pack2(rd, rd1);
          if (lane == 0) st_pkt16(&g_lnst[8 * b0 + warp], pack2(-rbf(mean) * lo2f(rh), -rbf(mean1) * hi2f(rh)), rh, 0, tag);
          TH(6);
          if (tid == 0) TS(2);
        }
      }
    }
    if (slab && late) gemv();
    TILE_ROLES();
    const uint32_t xa0 = sb + SM_RING + (warp * 16 + (lane & 15)) * 128 + (((lane >> 4) ^ (lane & 7)) * 16);
    uint32_t V[16];
    {
      const uint4* mp = &g_rec[tag & 1][(b0 >> 1) & (NREP - 1)][RV * wg + (lane >> 2) * RS + (lane & 3)];
      const uint4* lp = &g_lnst[(8 * rt + warp) * 8 + (g >> 1)];
      mbar_wait(sb + BAR_FULL1, 0);
#pragma unroll
      for (int kk = 0; kk < 4; kk++) ldsm4(xa0 ^ (kk * 32), V + 4 * kk);
      uint4 v0 = make_uint4(1, 0, 0, 0), l0, l1;
      int it = 0;
      while ((uint32_t)clock() - c0 < HD) {}
      do { if (wq == 0) v0 = ld_pkt16(mp);
           l0 = ld_pkt16(lp); l1 = ld_pkt16(lp + 4); spin_guard(it); }
        while (!(__all_sync(0xffffffffu, v0.x != 0 && l0.w == tag && l1.w == tag)));
      TH(7);
      if (wq == 0) put_record(sb, 128 * wg + lane, v0);
      const uint32_t sel = (g & 1) ? 0x3232 : 0x1010;
      ln[0] = __byte_perm(l0.x, 0, sel); ln[1] = __byte_perm(l0.y, 0, sel);
      ln[2] = __byte_perm(l1.x, 0, sel); ln[3] = __byte_perm(l1.y, 0, sel);
      __syncwarp();
      if (lane < 2) mbar_arrive_cl(mapa(sb + BAR_G, lane));
      nb_sync(NB_CONS, 256);
      if (tid == 0) TS(3);
      TH(13);
    }

    const uint32_t rel = mapa(sb + SM_MISC, lane & 1) - SM_MISC;
    const uint32_t stsm_addr = sb + SM_STASH + wg * 16384 + (wq * 16 + (lane & 15)) * 128 + (((lane >> 4) ^ (lane & 7)) * 16);

    uint32_t ph = 0;
    uint32_t X[32];
    {
      const uint32_t tab0 = sb + SM_STASH + wg * 16384 + t * 16;
      const uint64_t db0 = mk_desc(sb + SM_RING + 16384, 8192);
      uint32_t A[2][16];
      uint32_t xa[4];
#pragma unroll
      for (int kk = 0; kk < 4; kk++) xa[kk] = xa0 ^ (kk * 32);
      uint32_t tab = tab0;
      reg_fence<4>(xa);
      asm volatile("{\n.reg .pred p;\nsetp.eq.u32 p, %4, 0;\n@p ld.shared.v4.u32 {%0,%1,%2,%3}, [%5];\n}"
        : "+r"(ln[2]), "+r"(ln[0]), "+r"(ln[3]), "+r"(ln[1]) : "r"(tag), "r"(sb));
      int hs = 2 * ct;
      uint4 R[4];
#pragma unroll
      for (int kk = 0; kk < 4; kk++) R[kk] = lds128(tab + (kk >> 1) * 2048 + (kk & 1) * 64);
#pragma unroll 1
      for (int k4 = 0; k4 < 4; k4++) {
#pragma unroll
        for (int s = 0; s < 4; s++) {
          uint32_t* a = A[s & 1];
          const int sn = (s + 1) & 3;
          const uint32_t pn = (k4 + (s == 3)) & 1;
          modulate_frags(a, V, R, ln);
          if (hs == (s & 2)) {
            if (s & 1) mbar_wait(sb + BAR_HS + 16 * wg, 0);
#pragma unroll
            for (int kk = 0; kk < 4; kk++) stsm4((stsm_addr + 4096) ^ (kk * 32), a[4 * kk], a[4 * kk + 1], a[4 * kk + 2], a[4 * kk + 3]);
            nb_arrive(NB_OST + wg, 160);
          }
          if (s == 0 && k4 == 0) TH(8);
          if (s == 0 && k4 == 0 && tid == 0) { TS(6); TSC(61); }
          wg_fence();
#pragma unroll
          for (int kk = 0; kk < 4; kk++) wgmma_rs256<1>(acc, a + 4 * kk, db0 + s * (ST1 >> 4) + kk * 128);
          wg_commit();
          if (s == 3 && k4 < 3) mbar_wait(sb + BAR_TAB + 8 * k4, 0);
#pragma unroll
          for (int kk = 0; kk < 4; kk++) R[kk] = lds128(tab + (s + 1) * 128 + (kk >> 1) * 2048 + (kk & 1) * 64);
          wg_wait<1>();
          if (k4 == 0) TH(9 + s);
          reg_fence<16>(A[(s & 1) ^ 1]);
          if ((tid & 127) < 2 && (s | k4)) mbar_arrive_cl(rel + BAR_EMPTY1 + 8 * ((s + 3) & 3));
          if (s < 3 || k4 < 3) {
            mbar_wait(sb + BAR_FULL1 + 8 * sn, pn);
#pragma unroll
            for (int kk = 0; kk < 4; kk++) ldsm4(xa[kk] + sn * ST1, V + 4 * kk);
          }
        }
        tab += 512; hs -= 4;
      }
      mbar_wait(sb + BAR_HS + 16 * wg + 8, 0);
      wg_wait<0>();
      reg_fence<128>(acc);
    }
#pragma unroll 1
    for (int pair = 0; pair < 2; pair++) {
      uint32_t Q[32];
      TR(0);
      {
        if ((tid & 127) < 2) mbar_arrive_cl(rel + BAR_EMPTY1 + 8 * 3);
        if (pair == 1) mbar_wait(sb + BAR_STASH + 8 * wg, 1);
#pragma unroll
        for (int i = 0; i < 32; i++) Q[i] = pack2(acc[2 * i], acc[2 * i + 1]);
        const uint32_t qs = sb + SM_STASH + wg * 16384 + wq * 2048 + lane * 16;
#pragma unroll
        for (int i = 0; i < 8; i++)
          sts128(qs + (i & 3) * 512 + (i >> 2) * 8192, pack2(acc[64 + 8 * i], acc[65 + 8 * i]), pack2(acc[66 + 8 * i], acc[67 + 8 * i]),
                 pack2(acc[68 + 8 * i], acc[69 + 8 * i]), pack2(acc[70 + 8 * i], acc[71 + 8 * i]));
      }
      if (tid == 0) TS(8 + pair * 2);
      TR(1);
      float O[64], SL[32], SH[32];
      uint32_t PL[16], PH[16];
      SoftmaxState z;
      const uint64_t d0 = mk_desc(sb + SM_RING, 8192);
      {
        mbar_wait(sb + BAR_FULL1, ph);
        wg_fence();
        issue_qk(SL, Q, d0);
        wg_commit();
        issue_qk(SH, Q, d0 + 1024);
        wg_commit();
#pragma unroll
        for (int i = 0; i < 64; i++) O[i] = 0.f;
        reg_fence<64>(O);
        wg_wait<1>();
        reg_fence<32>(SL);
        softmax_start(z);
        softmax_half(SL, PL, O, z, true, tag);
        wg_wait<0>();
        reg_fence<32>(SH);
        if ((tid & 127) < 2) mbar_arrive_cl(rel + BAR_EMPTY1);
      }
      float lp0 = 0.f, lp1 = 0.f;
      uint32_t dB = (uint32_t)d0 + 1 * (ST1 >> 4), dA = (uint32_t)d0 + 2 * (ST1 >> 4);
      const uint32_t dBx = dB ^ ((uint32_t)d0 + 3 * (ST1 >> 4)), dAx = dA ^ (uint32_t)d0;
      uint32_t so = 0;
      bool ready = false;
#pragma unroll 1
      for (int i = 0; i < 7; i++) {
        TA(0);
        TR(2 + i);
        if (!ready) mbar_wait(sb + BAR_FULL1 + 8 + so, ph);
        TA(1);
        TA(2);
        wg_fence();
        issue_qk(SL, Q, (d0 & 0xffffffff00000000ull) | dB);
        if (i == 4) {
          __syncwarp();
          stage_o(O, lp0, lp1, stsm_addr);
        }
        wg_fence();
        issue_pv(O, PL, ((d0 & 0xffffffff00000000ull) | dB) + 1024, i != 4);
        wg_commit();
        if (i == 4) {
          nb_arrive(NB_OST + wg, 160);
        }
        TA(3);
        ph ^= i & 1;
        ready = mbar_test(sb + BAR_FULL1 + 16 - so, ph);
        softmax_half(SH, PH, O, z, false, tag);
        TA(4);
        wg_wait<0>();
        TA(5);
        reg_fence<32>(SL); reg_fence<16>(PL);
        if ((tid & 127) < 2) mbar_arrive_cl(rel + BAR_EMPTY1 + 8 + so);
        if (!ready) mbar_wait(sb + BAR_FULL1 + 16 - so, ph);
        TA(6);
        wg_fence();
        issue_qk(SH, Q, (d0 & 0xffffffff00000000ull) | dA);
        wg_commit();
        issue_pv(O, PH, ((d0 & 0xffffffff00000000ull) | dA) + 1024, 1);
        wg_commit();
        if (i == 2) {
          wg_wait<1>();
          reg_fence<32>(Q);
          const uint32_t qs = sb + SM_STASH + wg * 16384 + wq * 2048 + lane * 16;
#pragma unroll
          for (int j = 0; j < 8; j++) { const uint4 v = lds128(qs + (j & 3) * 512 + (j >> 2) * 8192); Q[4 * j] = v.x; Q[4 * j + 1] = v.y; Q[4 * j + 2] = v.z; Q[4 * j + 3] = v.w; }
        }
        TA(10);
        if (i == 3) { lp0 = z.l0; lp1 = z.l1; row_rcp(lp0, lp1); softmax_start(z); }
        TA(7);
        so ^= 16; dB ^= dBx; dA ^= dAx;
        ready = mbar_test(sb + BAR_FULL1 + 8 + so, ph);
        softmax_half(SL, PL, O, z, i == 3, tag);
        TA(8);
        wg_wait<0>();
        TA(9);
        reg_fence<32>(SH); reg_fence<16>(PH); reg_fence<64>(O); reg_fence<32>(Q);
        if ((tid & 127) < 2) mbar_arrive_cl(rel + BAR_EMPTY1 + so);
      }
      TAFLUSH();
      TR(9);
      {
        if (!ready) mbar_wait(sb + BAR_FULL1 + 8 * 3, ph);
        ph ^= 1;
        const uint64_t dv = d0 + 3 * (ST1 >> 4);
        wg_fence();
        issue_pv(O, PL, dv, 1);
        wg_commit();
        bb_fence(tag);
        softmax_half(SH, PH, O, z, false, tag);
        wg_fence();
        issue_pv(O, PH, dv + 1024, 1);
        wg_commit();
        TR(10);
        row_rcp(z.l0, z.l1);
        mbar_wait(sb + (pair ? BAR_X : BAR_STASH) + 8 * wg, 0);
#pragma unroll
        for (int kk = 0; kk < 8; kk++) ldsm4((stsm_addr + (kk >> 2) * 8192) ^ ((kk & 3) * 32), X + 4 * kk);
        reg_fence<32>(X);
        __syncwarp();
        wg_wait<0>();
        reg_fence<64>(O);
        TR(11);
        if ((tid & 127) < 2) mbar_arrive_cl(rel + BAR_EMPTY1 + 8 * 3);
        stage_o(O, z.l0, z.l1, stsm_addr);
        nb_arrive(NB_OST + wg, 160);
      }
      TR(12);
      if (tid == 0) { TS(9 + pair * 2); TSC(62); }
      if (pair == 1) break;
      {
        mbar_wait(sb + BAR_FULL1, ph);
        const uint64_t da = mk_desc(sb + SM_RING + wg * 8192, 16), db = mk_desc(sb + SM_RING + 16384, 8192);
        wg_fence();
        wgmma_ss256_z<1>(acc, da, db);
#pragma unroll
        for (int kk = 1; kk < 4; kk++) wgmma_ss256<1>(acc, da + kk * 2, db + kk * 128, 1);
        wg_commit();
      }
#pragma unroll 1
      for (int kt = 1; kt < 16; kt++) {
        const uint32_t s = kt & 3;
        if (s == 0) ph ^= 1;
        mbar_wait(sb + BAR_FULL1 + 8 * s, ph);
        const uint32_t st = sb + SM_RING + s * ST1;
        const uint64_t da = mk_desc(st + wg * 8192, 16), db = mk_desc(st + 16384, 8192);
        wg_fence();
#pragma unroll
        for (int kk = 0; kk < 4; kk++) wgmma_ss256<1>(acc, da + kk * 2, db + kk * 128, 1);
        wg_commit();
        wg_wait<1>();
        if ((tid & 127) < 2) mbar_arrive_cl(rel + BAR_EMPTY1 + 8 * ((s + 3) & 3));
      }
      ph ^= 1;
      wg_wait<0>();
      reg_fence<128>(acc);
      TR(13);
    }

    uint4 WG[16], WU[16];
    const int fp = 64 * warp + 8 * g + t;
    uint32_t fsb0, fsb1, fcb0, fcb1, fgb0, fgb1;
    const uint32_t gu_base = sb + SM_RING + (warp >> 1) * ST1 + 32768 + (warp & 1) * 8192;
    const uint32_t gu_addr = gu_base + t * 128 + (g & 1) * 64 + ((g >> 1) ^ t) * 16;
    {
      const uint64_t da0 = mk_desc(sb + SM_RING + __shfl_sync(0xffffffffu, wg, 0) * 8192, 16), db0 = mk_desc(sb + SM_RING + 16384, 8192);
#pragma unroll
      for (int n = 0; n < 4 + 5 * X_PEEL; n++) {
        const int s = n < 4 ? n : (n - 4) % 5;
        mbar_wait(sb + BAR_FULL1 + 8 * s, n < 4 ? 0 : ((n - 4) / 5 + (s < 4)) & 1);
        if (n < 4) TSX(40 + wg * 6 + n);
        const uint64_t da = da0 + s * (ST1 >> 4), db = db0 + s * (ST1 >> 4);
        wg_fence();
        if (n == 0) wgmma_ss128_z<1>(acc, da, db); else wgmma_ss128<1>(acc, da, db, 1);
#pragma unroll
        for (int kk = 1; kk < 4; kk++) wgmma_ss128<1>(acc, da + kk * 2, db + kk * 128, 1);
        wg_commit();
        if (n == 1) {
          mbar_wait(sb + BAR_OF, 0);
          const uint2* mp = &g_mod[3 * 512 + fp];
          fsb0 = ld_pkt8(mp).x; fsb1 = ld_pkt8(mp + 4).x; fcb0 = ld_pkt8(mp + 512).x; fcb1 = ld_pkt8(mp + 516).x;
          fgb0 = ld_pkt8(mp + 1024).x; fgb1 = ld_pkt8(mp + 1028).x;
        }
        if (n == 0 && b < NFFN) mbar_wait(sb + BAR_FFN, 0);
        {
          constexpr int NT = 4 + 5 * X_PEEL, F0 = NT > 16 ? NT - 16 : 0;
#pragma unroll
          for (int i = 0; i < 16; i++) if (F0 + i * (NT - F0) / 16 == n) WG[i] = lds128(gu_addr + i * 512);
        }
        if (n > 0) {
          wg_wait<1>();
          if ((tid & 127) < 2) mbar_arrive_cl(rel + BAR_EMPTY1 + 8 * (n == 4 ? 3 : s ? s - 1 : 4));
        }
      }
      TSX(44 + wg * 6);
      {
        uint32_t dep = 0;
#pragma unroll
        for (int i = 0; i < 16; i++) dep ^= WG[i].x;
        if (__shfl_sync(0xffffffffu, tag, dep & 31) == tag && lane == 2) mbar_arrive(sb + BAR_TFREE);
      }
#pragma unroll 1
      for (int r = X_PEEL; r < 12; r++) {
#pragma unroll
        for (int s = 0; s < 5; s++) {
          mbar_wait(sb + BAR_FULL1 + 8 * s, (r + (s < 4)) & 1);
          const uint64_t da = da0 + s * (ST1 >> 4), db = db0 + s * (ST1 >> 4);
          wg_fence();
#pragma unroll
          for (int kk = 0; kk < 4; kk++) wgmma_ss128<1>(acc, da + kk * 2, db + kk * 128, 1);
          wg_commit();
          wg_wait<1>();
          if ((tid & 127) < 2) mbar_arrive_cl(rel + BAR_EMPTY1 + 8 * (s ? s - 1 : (r == 0 ? 3 : 4)));
        }
      }
    }
    mbar_wait(sb + BAR_VEC, 0);
    const int lrow = warp * 16 + g;
    uint2 ga[8], b1[8];
#pragma unroll
    for (int kk = 0; kk < 8; kk++) { ga[kk] = lds64(sb + SM_GA + kk * 32 + t * 8); b1[kk] = lds64(sb + SM_B1 + min(g, 3) * 32 + t * 8 + kk * 128); }
    uint4* const stp = &g_stats[b * 128 + lrow + 8 * t];
    bb_fence(tag);
    wg_wait<0>();
    reg_fence<64>(acc);
    if (tid == 0) { TS(12); TSC(63); }

    TT(0);
    {
      float d1[4] = {0.f, 0.f, 0.f, 0.f}, d2[4] = {0.f, 0.f, 0.f, 0.f}, d3[4] = {0.f, 0.f, 0.f, 0.f};
      float d4[4] = {0.f, 0.f, 0.f, 0.f}, d5[4] = {0.f, 0.f, 0.f, 0.f};
#pragma unroll
      for (int kk = 0; kk < 8; kk++) {
        uint32_t* x = X + 4 * kk;
        x[0] = hfma2(ga[kk].x, pack2(acc[8 * kk + 0], acc[8 * kk + 1]), x[0]);
        x[1] = hfma2(ga[kk].x, pack2(acc[8 * kk + 2], acc[8 * kk + 3]), x[1]);
        x[2] = hfma2(ga[kk].y, pack2(acc[8 * kk + 4], acc[8 * kk + 5]), x[2]);
        x[3] = hfma2(ga[kk].y, pack2(acc[8 * kk + 6], acc[8 * kk + 7]), x[3]);
        mma16816(d1, x, b1[kk].x, b1[kk].y);
        mma1688(d2, x[0], x[1], x[0]); mma1688(d3, x[0], x[1], x[1]);
        mma1688(d4, x[2], x[3], x[2]); mma1688(d5, x[2], x[3], x[3]);
      }
      const int qb = lane & 28;
      const float q0 = __shfl_sync(0xffffffffu, (g & 1) ? d2[1] + d4[1] : d2[0] + d4[0], qb | (g >> 1));
      const float q1 = __shfl_sync(0xffffffffu, (g & 1) ? d3[3] + d5[3] : d3[2] + d5[2], qb | (g >> 1));
      const float e0 = __shfl_xor_sync(0xffffffffu, t ? d1[0] : d1[3], 1);
      const float e1 = __shfl_sync(0xffffffffu, d1[2], qb);
      if (t < 2) st_pkt16(stp, __float_as_uint(t ? e1 : d1[0]), __float_as_uint(t ? q1 : q0),
                          __float_as_uint((t ? d1[2] : d1[1]) + e0), tag);
    }
    TSY(13);
    TT(1);
    float mb, rd, den, br;
    {
      const uint4* sp = &g_stats[(rt * 8 + 4 * (t & 1)) * 128 + lrow + 4 * (t & 2)];
      mbar_wait(sb + BAR_EMPTY1 + 8 * 3, 0);
#pragma unroll
      for (int kk = 0; kk < 8; kk++) stsm4((stsm_addr - SM_STASH + SM_X2 + (kk >> 2) * 8192) ^ ((kk & 3) * 32), X[4 * kk], X[4 * kk + 1], X[4 * kk + 2], X[4 * kk + 3]);
      if (b < NFFN) mbar_wait(sb + BAR_FFN, 1);
#pragma unroll
      for (int i = 0; i < WU1; i++) WU[i] = lds128(gu_addr + i * 512);
      bb_fence(tag);
      TT(2);
      uint4 v0, v1, v2, v3;
      int it = 0;
      do { v0 = ld_pkt16(sp); v1 = ld_pkt16(sp + 128); v2 = ld_pkt16(sp + 256); v3 = ld_pkt16(sp + 384); spin_guard(it); }
        while (!(__all_sync(0xffffffffu, v0.w == tag && v1.w == tag && v2.w == tag && v3.w == tag)));
      TT(3);
      float sm = (__uint_as_float(v0.x) + __uint_as_float(v1.x)) + (__uint_as_float(v2.x) + __uint_as_float(v3.x));
      float sq = (__uint_as_float(v0.y) + __uint_as_float(v1.y)) + (__uint_as_float(v2.y) + __uint_as_float(v3.y));
      float dt = (__uint_as_float(v0.z) + __uint_as_float(v1.z)) + (__uint_as_float(v2.z) + __uint_as_float(v3.z));
      sm += __shfl_xor_sync(0xffffffffu, sm, 1); sq += __shfl_xor_sync(0xffffffffu, sq, 1); dt += __shfl_xor_sync(0xffffffffu, dt, 1);
      const uint2 scal = lds64(sb + SM_SCAL);
      const float mu = sm * (1.f / 1024.f);
      mb = rbf(mu);
      den = rbf(sqrt_f(rbf(rbf(fmaxf(fmaf(-mu, mu, sq * (1.f / 1024.f)), 0.f)) + 1e-5f)));
      rd = rcp_f(den);
      br = fmaf(fmaf(-mb, __uint_as_float(scal.x), dt), rd, __uint_as_float(scal.y));
    }
    TSY(14);
    TT(4);
    {
      const int rb = __float_as_int(br);
      const int key = ((rb ^ ((rb >> 31) & 0x7fffffff)) | 127) - (lrow + 4 * (t & 2));
      if (key == __reduce_max_sync(0xffffffffu, key)) sts64(sb + SM_AMAX + warp * 8, (uint32_t)key, pack2(mb, den));
      __syncwarp();
      nb_arrive(NB_AMAX, 288);
    }
    TT(5);
    const uint4* ep = &g_entry[(warp * 16 + (lane & 15)) * ESTR];
    const uint32_t slot = sb + SM_STASH + wg * 8192 + (tid & 127) * 16;
    cp_async16(slot, ep);
    {
      const float rh = rbf(rd);
      const uint32_t u = pack2(-mb * rh, rh);
      const int qb = lane & 28;
      const uint32_t u0 = __shfl_sync(0xffffffffu, u, qb), u1 = __shfl_sync(0xffffffffu, u, qb | 2);
      const uint32_t m0 = __byte_perm(u0, 0, 0x1010), h0 = __byte_perm(u0, 0, 0x3232);
      const uint32_t m1 = __byte_perm(u1, 0, 0x1010), h1 = __byte_perm(u1, 0, 0x3232);
#pragma unroll
      for (int j = 0; j < 16; j++) {
        const uint4 rec = lds128(sb + SM_REC + (4 * j + t) * 16);
        X[2 * j] = hfma2(rec.z, hfma2(hfma2(X[2 * j], h0, m0), rec.x, rec.y), X[2 * j]);
        X[2 * j + 1] = hfma2(rec.z, hfma2(hfma2(X[2 * j + 1], h1, m1), rec.x, rec.y), X[2 * j + 1]);
      }
#pragma unroll
      for (int kk = 0; kk < 8; kk++) stsm4((stsm_addr - SM_STASH + SM_OUT + (kk >> 2) * 8192) ^ ((kk & 3) * 32), X[4 * kk], X[4 * kk + 1], X[4 * kk + 2], X[4 * kk + 3]);
    }
    cp_async_wait();
    uint4 ent = lds128(slot);
    TSY(16);
    TT(6);
    int wrow;
    uint32_t xs0, xs1, hs0, hs1;
    uint32_t WD[64];
    const uint32_t wd_addr = sb + SM_RING + wg * ST1 + wq * 8192 + ((lane & 7) + ((lane >> 4) << 3)) * 128 + ((((lane >> 3) & 1) ^ (lane & 7)) * 16);
    {
      int gmax;
      auto leader = [&]() {
        gmax = __reduce_max_sync(0xffffffffu, ent.w == tag ? (int)ent.x : (int)0x8000000f);
        return ~gmax & 15;
      };
      int wt = leader(), it = 0;
      TT(7);
      nb_arrive(NB_OST + wg, 160);
      TT(8);
      cp_async16(slot + 2048, &g_cand[(wt * 8 + warp) * 32 + lane]);
      if (ent.w != tag) cp_async16(slot, ep);
#pragma unroll
      for (int i = WU1; i < 16; i++) WU[i] = lds128(gu_addr + i * 512);
      if (b < NFFN) mbar_wait(sb + BAR_FFN + 8, 0);
#pragma unroll
      for (int mt = 0; mt < 8; mt++)
#pragma unroll
        for (int s = 0; s < 2; s++) ldsm4t((wd_addr + (mt >> 2) * 4096 + s * 2048) ^ ((mt & 3) * 32), WD + (mt * 2 + s) * 4);
      cp_async_wait();
      uint4 v = lds128(slot + 2048);
      ent = lds128(slot);
      TT(9);
      while (true) {
        const int have = wt;
        wt = leader();
        if (__all_sync(0xffffffffu, ent.w == tag && have == wt && v.z == tag)) break;
        v = ld_pkt16(&g_cand[(wt * 8 + warp) * 32 + lane]);
        if (ent.w != tag) ent = ld_pkt16(ep);
        spin_guard(it);
      }
      TT(10);
      ent.x = gmax ^ ((gmax >> 31) & 0x7fffffff);
      wrow = __shfl_sync(0xffffffffu, ent.y, wt); ent.z = __shfl_sync(0xffffffffu, ent.z, wt);
      xs0 = v.x; xs1 = v.y;
      const uint32_t mm = __byte_perm(ent.z, 0, 0x1010);
      const float rs = rcp_f(hi2f(ent.z));
      const uint32_t e0 = hsub2(xs0, mm), e1 = hsub2(xs1, mm);
      hs0 = hfma2(pack2(lo2f(e0) * rs, hi2f(e0) * rs), hadd2(fcb0, ONE2), fsb0);
      hs1 = hfma2(pack2(lo2f(e1) * rs, hi2f(e1) * rs), hadd2(fcb1, ONE2), fsb1);
    }
    if ((tid & 127) == 0) sts32(sb + SM_WROW + 4 * wg, wrow);
    nb_arrive(NB_WIN + wg, 160);
    TSY(17);
    TT(11);
    if (b < NFFN) {
      float da[4][4];
#pragma unroll
      for (int i = 0; i < 4; i++) { da[i][0] = da[i][1] = da[i][2] = da[i][3] = 0.f; }
      const uint32_t selv = ((g & 1) ? 0x1044 : 0x4410) + ((g & 4) ? ((g & 1) ? 0x2200 : 0x0022) : 0);
      const uint32_t sel0 = (g & 2) ? 0x4444 : selv, sel1 = (g & 2) ? selv : 0x4444;
#pragma unroll
      for (int s = 0; s < 16; s++) {
        const uint32_t v = __shfl_sync(0xffffffffu, (s & 1) ? hs1 : hs0, 4 * (s >> 1) + t);
        const uint32_t b0 = __byte_perm(v, 0, sel0), b1 = __byte_perm(v, 0, sel1);
        const uint32_t a0[4] = {WG[s].x, WG[s].y, WG[s].z, WG[s].w};
        const uint32_t a1[4] = {WU[s].x, WU[s].y, WU[s].z, WU[s].w};
        mma16816(da[(s & 1) * 2], a0, b0, b1);
        mma16816(da[(s & 1) * 2 + 1], a1, b0, b1);
      }
      {
        float v[4];
#pragma unroll
        for (int i = 0; i < 4; i++) {
          const float vg = da[0][i] + da[2][i], vu = da[1][i] + da[3][i];
          v[i] = ((g & 1) ? vu : vg) + __shfl_xor_sync(0xffffffffu, (g & 1) ? vg : vu, 6);
        }
        if ((t >> 1) == (g & 1))
          sts128(gu_base + (g & 1) * 128 + (g >> 1) * 32 + (t & 1) * 16, __float_as_uint(v[0]), __float_as_uint(v[1]), __float_as_uint(v[2]), __float_as_uint(v[3]));
      }
      TT(12);
      nb_sync(NB_CONS, 256);
      float gp[8], up[8];
#pragma unroll
      for (int w = 0; w < 8; w++) {
        const uint32_t a = sb + SM_RING + (w >> 1) * ST1 + 32768 + (w & 1) * 8192 + lane * 4;
        gp[w] = lds_f32(a); up[w] = lds_f32(a + 128);
      }
      const float gsum = ((gp[0] + gp[1]) + (gp[2] + gp[3])) + ((gp[4] + gp[5]) + (gp[6] + gp[7]));
      const float usum = ((up[0] + up[1]) + (up[2] + up[3])) + ((up[4] + up[5]) + (up[6] + up[7]));
      const float act = rbf(silu_f(rbf(gsum))) * rbf(usum);
      TT(13);
      const uint32_t ap = pack2(act, __shfl_down_sync(0xffffffffu, act, 1));
      const uint32_t b00 = __shfl_sync(0xffffffffu, ap, 2 * t), b01 = __shfl_sync(0xffffffffu, ap, 2 * t + 8);
      const uint32_t b10 = __shfl_sync(0xffffffffu, ap, 2 * t + 16), b11 = __shfl_sync(0xffffffffu, ap, 2 * t + 24);
      float y[8][4];
#pragma unroll
      for (int mt = 0; mt < 8; mt++) {
        y[mt][0] = y[mt][1] = y[mt][2] = y[mt][3] = 0.f;
        mma16816(y[mt], WD + (mt * 2) * 4, b00, b01);
        mma16816(y[mt], WD + (mt * 2 + 1) * 4, b10, b11);
      }
#pragma unroll
      for (int e = 0; e < 2; e++) {
        const float v0 = t == 0 ? y[e][0] : t == 1 ? y[2 + e][0] : t == 2 ? y[4 + e][0] : y[6 + e][0];
        const float v1 = t == 0 ? y[e][2] : t == 1 ? y[2 + e][2] : t == 2 ? y[4 + e][2] : y[6 + e][2];
        const int f = 16 * warp + 2 * (2 * t + e) + (g >> 2);
        st_pkt16(&g_ypart[(f * NFFN + b) * 4 + (g & 3)], __float_as_uint(v0), __float_as_uint(v1), tag, 0);
      }
    }
    TSY(18);
    TT(14);
    {
      const int pw = warp - (warp > (b >> 4));
      if (warp != (b >> 4)) {
        const uint4* yp = &g_ypart[b * NFFN * 4 + pw * 64 + lane];
        uint4 v0, v1;
        int it = 0;
        { const uint32_t c1 = clock(); while ((uint32_t)clock() - c1 < (b < NFFN ? YD : YD + 1500)) {} }
        do { v0 = ld_pkt16(yp); v1 = ld_pkt16(yp + 32); spin_guard(it); }
        while (!(__all_sync(0xffffffffu, v0.z == tag && v1.z == tag)));
        float y0 = __uint_as_float(v0.x) + __uint_as_float(v1.x), y1 = __uint_as_float(v0.y) + __uint_as_float(v1.y);
#pragma unroll
        for (int o = 4; o <= 16; o <<= 1) { y0 += __shfl_xor_sync(0xffffffffu, y0, o); y1 += __shfl_xor_sync(0xffffffffu, y1, o); }
        if (lane < 4) sts64(sb + SM_YRED + pw * 32 + lane * 8, __float_as_uint(y0), __float_as_uint(y1));
      }
    }
    TT(15);
    if (warp != (b >> 4)) {
      nb_arrive(NB_CONS, 256);
    } else {
      nb_sync(NB_CONS, 256);
      float y0 = 0.f, y1 = 0.f;
      if (lane < 28) { const uint2 e = lds64(sb + SM_YRED + lane * 8); y0 = __uint_as_float(e.x); y1 = __uint_as_float(e.y); }
#pragma unroll
      for (int o = 4; o <= 16; o <<= 1) { y0 += __shfl_xor_sync(0xffffffffu, y0, o); y1 += __shfl_xor_sync(0xffffffffu, y1, o); }
      const int src = 2 * (t & 1);
      const float ya = __shfl_sync(0xffffffffu, y0, src), yb = __shfl_sync(0xffffffffu, y0, src + 1);
      const float yc = __shfl_sync(0xffffffffu, y1, src), yd = __shfl_sync(0xffffffffu, y1, src + 1);
      if (g == ((b >> 1) & 7) && (t >> 1) == (b & 1)) {
        const float rs = rbf(__uint_as_float(ent.x));
        const float sg = sigmoid_f(rs);
        const uint32_t sg2 = pack2(sg, sg);
        const uint32_t o0 = hadd2(xs0, hmul2(fgb0, hadd2(hs0, hmul2(pack2(ya, yb), sg2))));
        const uint32_t o1 = hadd2(xs1, hmul2(fgb1, hadd2(hs1, hmul2(pack2(yc, yd), sg2))));
        uint32_t* op = reinterpret_cast<uint32_t*>(p.out + (size_t)wrow * 1024) + fp;
        op[0] = o0; op[4] = o1;
      }
      if (b == 0) {
        if (lane < 8) st_relaxed(&p.sc->ticket[lane * 32], 0);
        st_relaxed(&p.sc->epoch[lane], tag);
      }
      if (lane == 0) TS(19);
    }
  }
}

typedef CUresult (*EncodeFn)(CUtensorMap*, CUtensorMapDataType, cuuint32_t, void*, const cuuint64_t*, const cuuint64_t*,
                             const cuuint32_t*, const cuuint32_t*, CUtensorMapInterleave, CUtensorMapSwizzle,
                             CUtensorMapL2promotion, CUtensorMapFloatOOBfill);

CUtensorMap make_map(EncodeFn enc, const void* ptr, uint64_t rows, uint64_t cols, uint32_t box_rows, uint32_t box_cols, CUtensorMapSwizzle sw) {
  CUtensorMap m;
  cuuint64_t dims[2] = {cols, rows};
  cuuint64_t strides[1] = {cols * 2};
  cuuint32_t box[2] = {box_cols, box_rows};
  cuuint32_t es[2] = {1, 1};
  enc(&m, CU_TENSOR_MAP_DATA_TYPE_BFLOAT16, 2, const_cast<void*>(ptr), dims, strides, box, es, CU_TENSOR_MAP_INTERLEAVE_NONE, sw,
      CU_TENSOR_MAP_L2_PROMOTION_L2_128B, CU_TENSOR_MAP_FLOAT_OOB_FILL_NONE);
  return m;
}

CUtensorMap make_map3(EncodeFn enc, const void* ptr, uint64_t rows, uint64_t cols, uint32_t box_rows, uint32_t box_blks) {
  CUtensorMap m;
  cuuint64_t dims[3] = {64, rows, cols / 64};
  cuuint64_t strides[2] = {cols * 2, 128};
  cuuint32_t box[3] = {64, box_rows, box_blks};
  cuuint32_t es[3] = {1, 1, 1};
  enc(&m, CU_TENSOR_MAP_DATA_TYPE_BFLOAT16, 3, const_cast<void*>(ptr), dims, strides, box, es, CU_TENSOR_MAP_INTERLEAVE_NONE,
      CU_TENSOR_MAP_SWIZZLE_128B, CU_TENSOR_MAP_L2_PROMOTION_L2_128B, CU_TENSOR_MAP_FLOAT_OOB_FILL_NONE);
  return m;
}

}

extern "C" void kernel_launch(void* const* d_in, const int* in_sizes, int n_in, void* d_out, int out_size) {
  (void)in_sizes; (void)n_in; (void)out_size;
  Params p;
  p.x = (const bf16*)d_in[0]; p.kc = (const bf16*)d_in[1]; p.vc = (const bf16*)d_in[2];
  p.wq = (const bf16*)d_in[3]; p.wo = (const bf16*)d_in[4]; p.w_r = (const bf16*)d_in[6];
  p.wg = (const bf16*)d_in[7]; p.wu = (const bf16*)d_in[8]; p.wd = (const bf16*)d_in[9];
  p.c = (const bf16*)d_in[10]; p.w_mod = (const bf16*)d_in[11]; p.out = (bf16*)d_out;

  void* fn = nullptr;
  cudaDriverEntryPointQueryResult st;
  cudaGetDriverEntryPoint("cuTensorMapEncodeTiled", &fn, cudaEnableDefault, &st);
  EncodeFn enc = (EncodeFn)fn;
  void* scp = nullptr;
  cudaGetSymbolAddress(&scp, g_scratch);
  p.sc = (Scratch*)scp;
  void *hp = p.sc->h, *op = p.sc->o;
  const CUtensorMapSwizzle S128 = CU_TENSOR_MAP_SWIZZLE_128B;
  CUtensorMap mH = make_map(enc, hp, 2048, 1024, 64, 64, S128);
  CUtensorMap mWq = make_map3(enc, p.wq, 1024, 4096, 64, 4);
  CUtensorMap mK = make_map(enc, p.kc, 8192, 128, 64, 64, S128);
  CUtensorMap mV = make_map(enc, p.vc, 8192, 128, 64, 64, S128);
  CUtensorMap mO = make_map(enc, op, 2048, 4096, 64, 64, S128);
  CUtensorMap mWo = make_map3(enc, p.wo, 4096, 1024, 64, 2);
  CUtensorMap mX = make_map(enc, p.x, 2048, 1024, 64, 64, S128);
  CUtensorMap mOut = make_map(enc, p.out, 2048, 1024, 64, 64, S128);
  CUtensorMap mWg = make_map(enc, p.wg, 1024, 3584, 256, 32, CU_TENSOR_MAP_SWIZZLE_64B);
  CUtensorMap mWu = make_map(enc, p.wu, 1024, 3584, 256, 32, CU_TENSOR_MAP_SWIZZLE_64B);
  CUtensorMap mWd = make_map3(enc, p.wd, 3584, 1024, 32, 8);
  CUtensorMap mWm = make_map(enc, p.w_mod, 1024, 6144, 16, 256, CU_TENSOR_MAP_SWIZZLE_NONE);
  CUtensorMap mWs = make_map(enc, p.w_mod, 1024, 6144, 128, 128, CU_TENSOR_MAP_SWIZZLE_NONE);
  cudaFuncSetAttribute(fused_kernel, cudaFuncAttributeMaxDynamicSharedMemorySize, SMEM_BYTES);
  fused_kernel<<<NCTA, NTHREADS, SMEM_BYTES>>>(p, mH, mWq, mK, mV, mO, mWo, mX, mOut, mWg, mWu, mWd, mWm, mWs);
}
```

```cpp
#include <cuda_runtime.h>
#include <cuda_bf16.h>
#include <cuda.h>
#include <stdint.h>
#include <stddef.h>

#define UPD 200
#define GATED 700
#define WL 3500
#define XD 0
#define PLD 200
#define ESTR 8
#define HD 6000
#define YD 500
#define SPT 5000
#define PFW 100
#define X_PEEL 1
#define WU1 12

namespace {

typedef __nv_bfloat16 bf16;

constexpr int NTHREADS = 384;
constexpr int NMAIN = 128;
constexpr int NCTA = 132;
#define RS 8
constexpr int RV = 16 * RS + 64;
constexpr int NREP = 4;
constexpr int NFFN = 112;

constexpr uint32_t SM_RING = 0;
constexpr uint32_t ST1 = 49152;
constexpr uint32_t ST2 = 32768;
constexpr int NST2 = 6;
constexpr uint32_t SM_STASH = 196608;
constexpr uint32_t SM_MISC = 229376;
constexpr uint32_t BAR_FULL1 = SM_MISC + 0;
constexpr uint32_t BAR_EMPTY1 = SM_MISC + 40;
constexpr uint32_t BAR_FULL2 = SM_MISC + 0;
constexpr uint32_t BAR_EMPTY2 = SM_MISC + 48;
constexpr uint32_t BAR_STASH = SM_MISC + 160;
constexpr uint32_t BAR_SFREE = SM_MISC + 176;
constexpr uint32_t BAR_TFREE = SM_MISC + 184;
constexpr uint32_t BAR_FFN = SM_MISC + 192;
constexpr uint32_t BAR_VEC = SM_MISC + 208;
constexpr uint32_t BAR_RED = SM_MISC + 216;
constexpr uint32_t BAR_XH = SM_MISC + 152;
constexpr uint32_t BAR_HS = SM_MISC + 80;
constexpr uint32_t BAR_G = SM_MISC + 112;
constexpr uint32_t BAR_T1 = SM_MISC + 120;
constexpr uint32_t BAR_HF = SM_MISC + 128;
constexpr uint32_t BAR_X = SM_MISC + 136;
constexpr uint32_t BAR_OF = SM_MISC + 224;
constexpr uint32_t BAR_ROLE = SM_MISC + 240;
constexpr uint32_t SM_ROLE = SM_MISC + 248;
constexpr uint32_t SM_GA = SM_MISC + 256;
constexpr uint32_t SM_SCAL = SM_MISC + 512;
constexpr uint32_t SM_WROW = SM_MISC + 520;
constexpr uint32_t SM_AMAX = SM_MISC + 528;
constexpr uint32_t SM_YRED = SM_MISC + 656;
constexpr uint32_t SM_X2 = 2 * ST1, SM_OUT = 3 * ST1;
constexpr uint32_t SM_REC = SM_MISC + 1024;
constexpr uint32_t BAR_TAB = SM_MISC + 1000;
constexpr uint32_t BAR_CAND = SM_MISC + 880;
constexpr uint32_t SM_CAND = SM_MISC + 888;
constexpr uint32_t BAR_WH = SM_MISC + 960;
constexpr uint32_t SM_WSLAB = 2 * 49152 + 16384;
constexpr uint32_t SM_XROW = 2 * 49152;
constexpr uint32_t SM_RED = SM_MISC + 2048;
constexpr uint32_t SM_B1 = SM_MISC + 2048;
constexpr uint32_t SMEM_BYTES = 232448;

constexpr int NB_CONS = 1, NB_WIN = 2  , NB_OST = 4  , NB_AMAX = 6;

struct __align__(1024) Scratch {
  uint32_t epoch[32];
  uint32_t hflag[16 * 32];
  uint32_t oflag[64 * 32];
  uint2 vdone[4 * 16];
  uint32_t pad[96 + 512];
  uint32_t ticket[8 * 32];
  uint2 mod[3072];
  uint4 rec[2][NREP][2 * RV];
  uint4 lnst[1024];
  uint4 entry[8 * 16 * 8];
  uint4 cand[16 * 8 * 32];
  uint4 stats[16 * 8 * 128];
  uint4 ypart[128 * NFFN * 4];
  unsigned long long ts[NCTA * 64];
  uint16_t h[2048 * 1024];
  uint16_t o[2048 * 4096];
};
__device__ Scratch g_scratch;
#define g_epoch (p.sc->epoch[0])
#define g_hflag (p.sc->hflag)
#define g_oflag (p.sc->oflag)
#define g_mod (p.sc->mod)
#define g_entry (p.sc->entry)
#define g_cand (p.sc->cand)
#define g_stats (p.sc->stats)
#define g_ypart (p.sc->ypart)
#define g_vdone (p.sc->vdone)
#define g_lnst (p.sc->lnst)
#define g_rec (p.sc->rec)
#define g_ts (p.sc->ts)
#define g_h (p.sc->h)

struct Params {
  const bf16* w_mod; const bf16* c; Scratch* sc; const bf16* x; const bf16* w_r; bf16* out;
  const bf16* wq; const bf16* wo; const bf16* wg; const bf16* wu; const bf16* wd; const bf16* kc; const bf16* vc;
};

__device__ __forceinline__ uint32_t smem_u32(const void* p) { return (uint32_t)__cvta_generic_to_shared(p); }
__device__ __forceinline__ void mbar_init(uint32_t bar, uint32_t cnt) { asm volatile("mbarrier.init.shared::cta.b64 [%0], %1;" :: "r"(bar), "r"(cnt) : "memory"); }
__device__ __forceinline__ void mbar_expect_tx(uint32_t bar, uint32_t bytes) { asm volatile("mbarrier.arrive.expect_tx.shared::cta.b64 _, [%0], %1;" :: "r"(bar), "r"(bytes) : "memory"); }
__device__ __forceinline__ void mbar_arrive(uint32_t bar) { asm volatile("mbarrier.arrive.shared::cta.b64 _, [%0];" :: "r"(bar) : "memory"); }
__device__ __forceinline__ void mbar_arrive_cl(uint32_t cluster_addr) { asm volatile("mbarrier.arrive.shared::cluster.b64 _, [%0];" :: "r"(cluster_addr) : "memory"); }
__device__ __forceinline__ uint32_t mapa(uint32_t addr, uint32_t cta) { uint32_t r; asm("mapa.shared::cluster.u32 %0, %1, %2;" : "=r"(r) : "r"(addr), "r"(cta)); return r; }
__device__ __forceinline__ bool mbar_test(uint32_t bar, uint32_t parity) {
  uint32_t ok;
  asm volatile("{\n.reg .pred p;\nmbarrier.test_wait.parity.shared::cta.b64 p, [%1], %2;\nselp.u32 %0, 1, 0, p;\n}" : "=r"(ok) : "r"(bar), "r"(parity) : "memory");
  return ok;
}
constexpr int SPIN_LIMIT = 300000;
__device__ __forceinline__ void spin_guard(int& it) {
  asm volatile("{\n.reg .pred p;\n.reg .b64 z;\nadd.s32 %0, %0, 1;\nsetp.gt.s32 p, %0, %1;\nmov.b64 z, 0;\n@p st.volatile.global.u32 [z], %0;\n}" : "+r"(it) : "n"(SPIN_LIMIT));
}
__device__ __forceinline__ void mbar_wait_g(uint32_t bar, uint32_t parity) {
  asm volatile("{\n.reg .pred p, q;\n.reg .b32 c;\n.reg .b64 z;\nmov.b32 c, 0;\nmov.b64 z, 0;\nMW_LOOP:\n"
               "mbarrier.try_wait.parity.shared::cta.b64 p, [%0], %1;\nadd.s32 c, c, 1;\nsetp.gt.s32 q, c, %2;\n"
               "@q st.volatile.global.u32 [z], c;\n@!p bra MW_LOOP;\n}" :: "r"(bar), "r"(parity), "n"(SPIN_LIMIT) : "memory");
}
__device__ __forceinline__ void mbar_wait(uint32_t bar, uint32_t parity) {
  asm volatile("{\n.reg .pred p;\nMW_LOOP:\nmbarrier.try_wait.parity.shared::cta.b64 p, [%0], %1;\n@!p bra MW_LOOP;\n}" :: "r"(bar), "r"(parity) : "memory");
}
__device__ __forceinline__ void bb_fence(uint32_t v) {
  asm volatile("{\n.reg .pred p;\n.reg .u32 c;\nsetp.ne.u32 p, %0, 0;\n@p bra.uni BF_DONE;\nBF_LOOP:\nnanosleep.u32 1;\nmov.u32 c, %%clock;\nsetp.eq.u32 p, c, 0;\n@p bra.uni BF_LOOP;\nBF_DONE:\n}" :: "r"(v) : "memory");
}
__device__ __forceinline__ bool elect_one() {
  uint32_t pred;
  asm volatile("{\n.reg .pred P;\nelect.sync _|P, 0xffffffff;\nselp.u32 %0, 1, 0, P;\n}" : "=r"(pred));
  return pred;
}
__device__ __forceinline__ void tma_ld(uint32_t dst, const CUtensorMap* m, int c0, int c1, uint32_t bar) {
  asm volatile("cp.async.bulk.tensor.2d.shared::cluster.global.mbarrier::complete_tx::bytes [%0], [%1, {%3, %4}], [%2];"
    :: "r"(dst), "l"(m), "r"(bar), "r"(c0), "r"(c1) : "memory");
}
__device__ __forceinline__ void tma_ld_hint(uint32_t dst, const CUtensorMap* m, int c0, int c1, uint32_t bar, uint64_t pol) {
  asm volatile("cp.async.bulk.tensor.2d.shared::cluster.global.mbarrier::complete_tx::bytes.L2::cache_hint [%0], [%1, {%3, %4}], [%2], %5;"
    :: "r"(dst), "l"(m), "r"(bar), "r"(c0), "r"(c1), "l"(pol) : "memory");
}
__device__ __forceinline__ void tma_ld_mc(uint32_t dst, const CUtensorMap* m, int c0, int c1, uint32_t bar) {
  asm volatile("cp.async.bulk.tensor.2d.shared::cluster.global.mbarrier::complete_tx::bytes.multicast::cluster [%0], [%1, {%3, %4}], [%2], %5;"
    :: "r"(dst), "l"(m), "r"(bar), "r"(c0), "r"(c1), "h"((uint16_t)3) : "memory");
}
__device__ __forceinline__ void tma_ld_mc_hint(uint32_t dst, const CUtensorMap* m, int c0, int c1, uint32_t bar, uint64_t pol) {
  asm volatile("cp.async.bulk.tensor.2d.shared::cluster.global.mbarrier::complete_tx::bytes.multicast::cluster.L2::cache_hint [%0], [%1, {%3, %4}], [%2], %5, %6;"
    :: "r"(dst), "l"(m), "r"(bar), "r"(c0), "r"(c1), "h"((uint16_t)3), "l"(pol) : "memory");
}
__device__ __forceinline__ void tma_ld3_hint(uint32_t dst, const CUtensorMap* m, int row, int blk, uint32_t bar, uint64_t pol) {
  asm volatile("cp.async.bulk.tensor.3d.shared::cluster.global.mbarrier::complete_tx::bytes.L2::cache_hint [%0], [%1, {0, %3, %4}], [%2], %5;"
    :: "r"(dst), "l"(m), "r"(bar), "r"(row), "r"(blk), "l"(pol) : "memory");
}
__device__ __forceinline__ void tma_pf3(const CUtensorMap* m, int row, int blk) {
  asm volatile("cp.async.bulk.prefetch.tensor.3d.L2.global [%0, {0, %1, %2}];" :: "l"(m), "r"(row), "r"(blk) : "memory");
}
__device__ __forceinline__ void tma_st(const CUtensorMap* m, int c0, int c1, uint32_t src) {
  asm volatile("cp.async.bulk.tensor.2d.global.shared::cta.bulk_group [%0, {%2, %3}], [%1];" :: "l"(m), "r"(src), "r"(c0), "r"(c1) : "memory");
}
__device__ __forceinline__ void tma_prefetch_desc(const CUtensorMap* m) { asm volatile("prefetch.tensormap [%0];" :: "l"(m) : "memory"); }
__device__ __forceinline__ void l2_prefetch(const void* p, uint32_t bytes) { asm volatile("cp.async.bulk.prefetch.L2.global [%0], %1;" :: "l"(p), "r"(bytes) : "memory"); }
__device__ __forceinline__ void bulk_commit() { asm volatile("cp.async.bulk.commit_group;" ::: "memory"); }
__device__ __forceinline__ void bulk_wait_read() { asm volatile("cp.async.bulk.wait_group.read 0;" ::: "memory"); }
__device__ __forceinline__ void bulk_wait_all() { asm volatile("cp.async.bulk.wait_group 0;" ::: "memory"); }
__device__ __forceinline__ void fence_async_smem() { asm volatile("fence.proxy.async.shared::cta;" ::: "memory"); }
__device__ __forceinline__ void fence_async_global() { asm volatile("fence.proxy.async.global;" ::: "memory"); }
__device__ __forceinline__ void fence_acquire_gpu() { asm volatile("fence.acquire.gpu;" ::: "memory"); }
__device__ __forceinline__ void fence_release_gpu() { asm volatile("fence.release.gpu;" ::: "memory"); }
__device__ __forceinline__ void st_async_f32x4(uint32_t cluster_addr, const float* v, uint32_t cluster_bar) {
  asm volatile("st.async.weak.shared::cluster.mbarrier::complete_tx::bytes.v4.f32 [%0], {%1,%2,%3,%4}, [%5];"
    :: "r"(cluster_addr), "f"(v[0]), "f"(v[1]), "f"(v[2]), "f"(v[3]), "r"(cluster_bar) : "memory");
}
__device__ __forceinline__ void nb_sync(int id, int n) { asm volatile("bar.sync %0, %1;" :: "r"(id), "r"(n) : "memory"); }
__device__ __forceinline__ void nb_arrive(int id, int n) { asm volatile("bar.arrive %0, %1;" :: "r"(id), "r"(n) : "memory"); }
__device__ __forceinline__ void wg_fence() { asm volatile("wgmma.fence.sync.aligned;" ::: "memory"); }
__device__ __forceinline__ void wg_commit() { asm volatile("wgmma.commit_group.sync.aligned;" ::: "memory"); }
template <int N> __device__ __forceinline__ void wg_wait() { asm volatile("wgmma.wait_group.sync.aligned %0;" :: "n"(N) : "memory"); }
template <int N> __device__ __forceinline__ void reg_fence(float* a) {
#pragma unroll
  for (int i = 0; i < N; i++) asm volatile("" : "+f"(a[i]) :: "memory");
}
template <int N> __device__ __forceinline__ void reg_fence(uint32_t* a) {
#pragma unroll
  for (int i = 0; i < N; i++) asm volatile("" : "+r"(a[i]) :: "memory");
}
__device__ __forceinline__ uint64_t mk_desc(uint32_t addr, uint32_t lbo) {
  return (uint64_t)((addr & 0x3FFFF) >> 4) | ((uint64_t)(lbo >> 4) << 16) | ((uint64_t)(1024 >> 4) << 32) | (1ull << 62);
}

__device__ __forceinline__ uint64_t policy_evict_first() { uint64_t pol; asm("createpolicy.fractional.L2::evict_first.b64 %0, 1.0;" : "=l"(pol)); return pol; }
__device__ __forceinline__ uint32_t ld_relaxed(const uint32_t* p) { uint32_t v; asm volatile("ld.relaxed.gpu.global.u32 %0, [%1];" : "=r"(v) : "l"(p) : "memory"); return v; }
__device__ __forceinline__ void st_relaxed(uint32_t* p, uint32_t v) { asm volatile("st.relaxed.gpu.global.u32 [%0], %1;" :: "l"(p), "r"(v) : "memory"); }
__device__ __forceinline__ void red_add_relaxed(uint32_t* p, uint32_t v) { asm volatile("red.relaxed.gpu.global.add.u32 [%0], %1;" :: "l"(p), "r"(v) : "memory"); }
__device__ __forceinline__ uint2 ld_pkt8(const uint2* p) {
  uint2 v; asm volatile("{\n.reg .b64 t;\nld.relaxed.gpu.global.b64 t, [%2];\nmov.b64 {%0,%1}, t;\n}" : "=r"(v.x), "=r"(v.y) : "l"(p) : "memory"); return v;
}
__device__ __forceinline__ void st_pkt8(uint2* p, uint32_t a, uint32_t b) {
  asm volatile("{\n.reg .b64 t;\nmov.b64 t, {%1,%2};\nst.relaxed.gpu.global.b64 [%0], t;\n}" :: "l"(p), "r"(a), "r"(b) : "memory");
}
__device__ __forceinline__ uint4 ld_pkt16(const uint4* p) {
  uint4 v; asm volatile("{\n.reg .b128 t;\n.reg .b64 a, b;\nld.relaxed.gpu.global.b128 t, [%4];\nmov.b128 {a, b}, t;\nmov.b64 {%0,%1}, a;\nmov.b64 {%2,%3}, b;\n}"
    : "=r"(v.x), "=r"(v.y), "=r"(v.z), "=r"(v.w) : "l"(p) : "memory"); return v;
}
__device__ __forceinline__ void st_pkt16(uint4* p, uint32_t x, uint32_t y, uint32_t z, uint32_t w) {
  asm volatile("{\n.reg .b128 t;\n.reg .b64 a, b;\nmov.b64 a, {%1,%2};\nmov.b64 b, {%3,%4};\nmov.b128 t, {a, b};\nst.relaxed.gpu.global.b128 [%0], t;\n}"
    :: "l"(p), "r"(x), "r"(y), "r"(z), "r"(w) : "memory");
}
__device__ __forceinline__ void cp_async16(uint32_t dst, const void* src) { asm volatile("cp.async.cg.shared.global [%0], [%1], 16;" :: "r"(dst), "l"(src) : "memory"); }
__device__ __forceinline__ void cp_async_wait() { asm volatile("cp.async.wait_all;" ::: "memory"); }
__device__ __forceinline__ uint32_t lds32(uint32_t a) { uint32_t v; asm volatile("ld.shared.u32 %0, [%1];" : "=r"(v) : "r"(a) : "memory"); return v; }
__device__ __forceinline__ float lds_f32(uint32_t a) { float v; asm volatile("ld.shared.f32 %0, [%1];" : "=f"(v) : "r"(a) : "memory"); return v; }
__device__ __forceinline__ uint2 lds64(uint32_t a) { uint2 v; asm volatile("ld.shared.v2.u32 {%0,%1}, [%2];" : "=r"(v.x), "=r"(v.y) : "r"(a) : "memory"); return v; }
__device__ __forceinline__ uint4 lds128(uint32_t a) { uint4 v; asm volatile("ld.shared.v4.u32 {%0,%1,%2,%3}, [%4];" : "=r"(v.x), "=r"(v.y), "=r"(v.z), "=r"(v.w) : "r"(a) : "memory"); return v; }
__device__ __forceinline__ void sts32(uint32_t a, uint32_t v) { asm volatile("st.shared.u32 [%0], %1;" :: "r"(a), "r"(v) : "memory"); }
__device__ __forceinline__ void sts64(uint32_t a, uint32_t x, uint32_t y) { asm volatile("st.shared.v2.u32 [%0], {%1,%2};" :: "r"(a), "r"(x), "r"(y) : "memory"); }
__device__ __forceinline__ void sts128(uint32_t a, uint32_t x, uint32_t y, uint32_t z, uint32_t w) { asm volatile("st.shared.v4.u32 [%0], {%1,%2,%3,%4};" :: "r"(a), "r"(x), "r"(y), "r"(z), "r"(w) : "memory"); }
__device__ __forceinline__ void stsm4(uint32_t a, uint32_t x, uint32_t y, uint32_t z, uint32_t w) {
  asm volatile("stmatrix.sync.aligned.m8n8.x4.shared.b16 [%0], {%1,%2,%3,%4};" :: "r"(a), "r"(x), "r"(y), "r"(z), "r"(w) : "memory");
}
__device__ __forceinline__ void ldsm4(uint32_t a, uint32_t* r) {
  asm volatile("ldmatrix.sync.aligned.m8n8.x4.shared.b16 {%0,%1,%2,%3}, [%4];" : "=r"(r[0]), "=r"(r[1]), "=r"(r[2]), "=r"(r[3]) : "r"(a) : "memory");
}
__device__ __forceinline__ void ldsm4t(uint32_t a, uint32_t* r) {
  asm volatile("ldmatrix.sync.aligned.m8n8.x4.trans.shared.b16 {%0,%1,%2,%3}, [%4];" : "=r"(r[0]), "=r"(r[1]), "=r"(r[2]), "=r"(r[3]) : "r"(a) : "memory");
}
__device__ __forceinline__ void mma16816(float* d, const uint32_t* a, uint32_t b0, uint32_t b1) {
  asm volatile("mma.sync.aligned.m16n8k16.row.col.f32.bf16.bf16.f32 {%0,%1,%2,%3}, {%4,%5,%6,%7}, {%8,%9}, {%0,%1,%2,%3};"
    : "+f"(d[0]), "+f"(d[1]), "+f"(d[2]), "+f"(d[3]) : "r"(a[0]), "r"(a[1]), "r"(a[2]), "r"(a[3]), "r"(b0), "r"(b1));
}
__device__ __forceinline__ void mma1688(float* d, uint32_t a0, uint32_t a1, uint32_t b0) {
  asm volatile("mma.sync.aligned.m16n8k8.row.col.f32.bf16.bf16.f32 {%0,%1,%2,%3}, {%4,%5}, {%6}, {%0,%1,%2,%3};"
    : "+f"(d[0]), "+f"(d[1]), "+f"(d[2]), "+f"(d[3]) : "r"(a0), "r"(a1), "r"(b0));
}
__device__ __forceinline__ uint32_t pack2(float lo, float hi) { uint32_t r; asm("cvt.rn.bf16x2.f32 %0, %1, %2;" : "=r"(r) : "f"(hi), "f"(lo)); return r; }
__device__ __forceinline__ float lo2f(uint32_t v) { return __uint_as_float(v << 16); }
__device__ __forceinline__ float hi2f(uint32_t v) { return __uint_as_float(v & 0xffff0000u); }
__device__ __forceinline__ uint32_t hmul2(uint32_t a, uint32_t b) { uint32_t r; asm("mul.rn.bf16x2 %0, %1, %2;" : "=r"(r) : "r"(a), "r"(b)); return r; }
__device__ __forceinline__ uint32_t hadd2(uint32_t a, uint32_t b) { uint32_t r; asm("add.rn.bf16x2 %0, %1, %2;" : "=r"(r) : "r"(a), "r"(b)); return r; }
__device__ __forceinline__ uint32_t hsub2(uint32_t a, uint32_t b) { uint32_t r; asm("sub.rn.bf16x2 %0, %1, %2;" : "=r"(r) : "r"(a), "r"(b)); return r; }
__device__ __forceinline__ uint32_t hfma2(uint32_t a, uint32_t b, uint32_t c) { uint32_t r; asm("fma.rn.bf16x2 %0, %1, %2, %3;" : "=r"(r) : "r"(a), "r"(b), "r"(c)); return r; }
__device__ __forceinline__ float rbf(float v) { return lo2f(pack2(v, 0.f)); }
__device__ __forceinline__ float ex2(float v) { float r; asm("ex2.approx.ftz.f32 %0, %1;" : "=f"(r) : "f"(v)); return r; }
__device__ __forceinline__ float rcp_f(float v) { float r; asm("rcp.approx.ftz.f32 %0, %1;" : "=f"(r) : "f"(v)); return r; }
__device__ __forceinline__ float sqrt_f(float v) { float r; asm("sqrt.approx.ftz.f32 %0, %1;" : "=f"(r) : "f"(v)); return r; }
__device__ __forceinline__ float sigmoid_f(float v) { return rcp_f(1.f + ex2(-1.4426950408889634f * v)); }
__device__ __forceinline__ float silu_f(float v) { return v * sigmoid_f(v); }
constexpr uint32_t ONE2 = 0x3f803f80u;

#define R8(a,o) "+f"(a[o+0]), "+f"(a[o+1]), "+f"(a[o+2]), "+f"(a[o+3]), "+f"(a[o+4]), "+f"(a[o+5]), "+f"(a[o+6]), "+f"(a[o+7])
#define R64(a,o) R8(a,o), R8(a,o+8), R8(a,o+16), R8(a,o+24), R8(a,o+32), R8(a,o+40), R8(a,o+48), R8(a,o+56)
#define D64 "{%0,%1,%2,%3,%4,%5,%6,%7,%8,%9,%10,%11,%12,%13,%14,%15,%16,%17,%18,%19,%20,%21,%22,%23,%24,%25,%26,%27,%28,%29,%30,%31," \
            "%32,%33,%34,%35,%36,%37,%38,%39,%40,%41,%42,%43,%44,%45,%46,%47,%48,%49,%50,%51,%52,%53,%54,%55,%56,%57,%58,%59,%60,%61,%62,%63"
#define D128 D64 ",%64,%65,%66,%67,%68,%69,%70,%71,%72,%73,%74,%75,%76,%77,%78,%79,%80,%81,%82,%83,%84,%85,%86,%87,%88,%89,%90,%91,%92,%93,%94,%95," \
            "%96,%97,%98,%99,%100,%101,%102,%103,%104,%105,%106,%107,%108,%109,%110,%111,%112,%113,%114,%115,%116,%117,%118,%119,%120,%121,%122,%123,%124,%125,%126,%127"

template <int TB> __device__ __forceinline__ void wgmma_ss128(float* d, uint64_t da, uint64_t db, int acc) {
  asm volatile("{\n.reg .pred p;\nsetp.ne.b32 p, %66, 0;\nwgmma.mma_async.sync.aligned.m64n128k16.f32.bf16.bf16 " D64 "}, %64, %65, p, 1, 1, 0, %67;\n}"
    : R64(d, 0) : "l"(da), "l"(db), "r"(acc), "n"(TB));
}
template <int TB> __device__ __forceinline__ void wgmma_rs128(float* d, const uint32_t* a, uint64_t db, int acc) {
  asm volatile("{\n.reg .pred p;\nsetp.ne.b32 p, %69, 0;\nwgmma.mma_async.sync.aligned.m64n128k16.f32.bf16.bf16 " D64 "}, {%64,%65,%66,%67}, %68, p, 1, 1, %70;\n}"
    : R64(d, 0) : "r"(a[0]), "r"(a[1]), "r"(a[2]), "r"(a[3]), "l"(db), "r"(acc), "n"(TB));
}
template <int TB> __device__ __forceinline__ void wgmma_ss256(float* d, uint64_t da, uint64_t db, int acc) {
  asm volatile("{\n.reg .pred p;\nsetp.ne.b32 p, %130, 0;\nwgmma.mma_async.sync.aligned.m64n256k16.f32.bf16.bf16 " D128 "}, %128, %129, p, 1, 1, 0, %131;\n}"
    : R64(d, 0), R64(d, 64) : "l"(da), "l"(db), "r"(acc), "n"(TB));
}

#define W8(a,o) "=f"(a[o+0]), "=f"(a[o+1]), "=f"(a[o+2]), "=f"(a[o+3]), "=f"(a[o+4]), "=f"(a[o+5]), "=f"(a[o+6]), "=f"(a[o+7])
#define W64(a,o) W8(a,o), W8(a,o+8), W8(a,o+16), W8(a,o+24), W8(a,o+32), W8(a,o+40), W8(a,o+48), W8(a,o+56)
template <int TB> __device__ __forceinline__ void wgmma_ss128_z(float* d, uint64_t da, uint64_t db) {
  asm volatile("wgmma.mma_async.sync.aligned.m64n128k16.f32.bf16.bf16 " D64 "}, %64, %65, 0, 1, 1, 0, %66;"
    : W64(d, 0) : "l"(da), "l"(db), "n"(TB));
}
template <int TB> __device__ __forceinline__ void wgmma_rs128_z(float* d, const uint32_t* a, uint64_t db) {
  asm volatile("wgmma.mma_async.sync.aligned.m64n128k16.f32.bf16.bf16 " D64 "}, {%64,%65,%66,%67}, %68, 0, 1, 1, %69;"
    : W64(d, 0) : "r"(a[0]), "r"(a[1]), "r"(a[2]), "r"(a[3]), "l"(db), "n"(TB));
}
template <int TB> __device__ __forceinline__ void wgmma_ss256_z(float* d, uint64_t da, uint64_t db) {
  asm volatile("wgmma.mma_async.sync.aligned.m64n256k16.f32.bf16.bf16 " D128 "}, %128, %129, 0, 1, 1, 0, %130;"
    : W64(d, 0), W64(d, 64) : "l"(da), "l"(db), "n"(TB));
}

template <int TB> __device__ __forceinline__ void wgmma_rs256(float* d, const uint32_t* a, uint64_t db) {
  asm volatile("wgmma.mma_async.sync.aligned.m64n256k16.f32.bf16.bf16 " D128 "}, {%128,%129,%130,%131}, %132, 1, 1, 1, %133;"
    : R64(d, 0), R64(d, 64) : "r"(a[0]), "r"(a[1]), "r"(a[2]), "r"(a[3]), "l"(db), "n"(TB));
}
template <int TB> __device__ __forceinline__ void wgmma_rs256_z(float* d, const uint32_t* a, uint64_t db) {
  asm volatile("wgmma.mma_async.sync.aligned.m64n256k16.f32.bf16.bf16 " D128 "}, {%128,%129,%130,%131}, %132, 0, 1, 1, %133;"
    : W64(d, 0), W64(d, 64) : "r"(a[0]), "r"(a[1]), "r"(a[2]), "r"(a[3]), "l"(db), "n"(TB));
}
#define D32 "{%0,%1,%2,%3,%4,%5,%6,%7,%8,%9,%10,%11,%12,%13,%14,%15,%16,%17,%18,%19,%20,%21,%22,%23,%24,%25,%26,%27,%28,%29,%30,%31}"
__device__ __forceinline__ void wgmma_rs64(float* d, const uint32_t* a, uint64_t db) {
  asm volatile("wgmma.mma_async.sync.aligned.m64n64k16.f32.bf16.bf16 " D32 ", {%32,%33,%34,%35}, %36, 1, 1, 1, 0;"
    : R8(d, 0), R8(d, 8), R8(d, 16), R8(d, 24) : "r"(a[0]), "r"(a[1]), "r"(a[2]), "r"(a[3]), "l"(db));
}
__device__ __forceinline__ void wgmma_rs64_z(float* d, const uint32_t* a, uint64_t db) {
  asm volatile("wgmma.mma_async.sync.aligned.m64n64k16.f32.bf16.bf16 " D32 ", {%32,%33,%34,%35}, %36, 0, 1, 1, 0;"
    : W8(d, 0), W8(d, 8), W8(d, 16), W8(d, 24) : "r"(a[0]), "r"(a[1]), "r"(a[2]), "r"(a[3]), "l"(db));
}
__device__ __forceinline__ void issue_qk(float* S, const uint32_t* Q, uint64_t dk) {
  wgmma_rs64_z(S, Q, dk);
#pragma unroll
  for (int kk = 1; kk < 8; kk++) wgmma_rs64(S, Q + 4 * kk, dk + (kk >> 2) * 512 + (kk & 3) * 2);
}
__device__ __forceinline__ void issue_pv(float* O, const uint32_t* P, uint64_t dv, int acc) {
#pragma unroll
  for (int kk = 0; kk < 4; kk++) wgmma_rs128<1>(O, P + 4 * kk, dv + kk * 128, kk ? 1 : acc);
}

#define TS(i)
#define TSC(i)
#define TSX(i)
#define TSY(k) do { if ((tid & 127) == 0) TS((k) + 40 * wg); } while (0)
#define TT(k)
#define TV(k)
#define TR(k)
#define TQ(k)
#define TH(k)
#define TA(k)
#define TAFLUSH()

struct SoftmaxState { float c0, c1, l0, l1; bool shifted; };
constexpr float SM_SCALE = 0.08838834764831845f * 1.4426950408889634f;
__device__ __forceinline__ void softmax_start(SoftmaxState& z) { z.c0 = z.c1 = z.l0 = z.l1 = 0.f; z.shifted = false; }
__device__ __forceinline__ void softmax_half(float* S, uint32_t* P, float* O, SoftmaxState& z, bool first, uint32_t tag) {
  const float lo0 = z.l0, lo1 = z.l1;
  float lim = 1.2676506002282294e30f;
  const float low = first ? 8.673617379884035e-19f : 0.f;
  if (z.shifted) {
#pragma unroll
    for (int j = 0; j < 32; j++) S[j] += (j & 2) ? z.c1 : z.c0;
  }
#pragma unroll 1
  while (true) {
    bb_fence(tag);
#pragma unroll
    for (int j = 0; j < 8; j++) {
      const float p0 = ex2(S[4 * j]), p1 = ex2(S[4 * j + 1]), p2 = ex2(S[4 * j + 2]), p3 = ex2(S[4 * j + 3]);
      z.l0 += p0; z.l1 += p2; z.l0 += p1; z.l1 += p3;
      P[2 * j] = pack2(p0, p1); P[2 * j + 1] = pack2(p2, p3);
    }
    if (!__any_sync(0xffffffffu, !(z.l0 < lim && z.l1 < lim && fminf(z.l0, z.l1) >= low) && lim > 0.f)) break;
    float d0 = fmaxf(S[0], S[1]), d1 = fmaxf(S[2], S[3]);
#pragma unroll
    for (int j = 1; j < 8; j++) { d0 = fmaxf(d0, fmaxf(S[4 * j], S[4 * j + 1])); d1 = fmaxf(d1, fmaxf(S[4 * j + 2], S[4 * j + 3])); }
    d0 = fmaxf(d0, __shfl_xor_sync(0xffffffffu, d0, 1)); d1 = fmaxf(d1, __shfl_xor_sync(0xffffffffu, d1, 1));
    d0 = fmaxf(d0, __shfl_xor_sync(0xffffffffu, d0, 2)); d1 = fmaxf(d1, __shfl_xor_sync(0xffffffffu, d1, 2));
    if (!first) { d0 = fmaxf(d0, 0.f); d1 = fmaxf(d1, 0.f); }
    z.shifted = true;
    z.c0 -= d0; z.c1 -= d1;
#pragma unroll
    for (int j = 0; j < 32; j++) S[j] -= (j & 2) ? d1 : d0;
    const float a0 = first ? 1.f : ex2(-d0), a1 = first ? 1.f : ex2(-d1);
    z.l0 = lo0 * a0; z.l1 = lo1 * a1;
    lim = -1.f;
    wg_wait<0>();
    reg_fence<64>(O);
#pragma unroll
    for (int j = 0; j < 16; j++) { O[4 * j] *= a0; O[4 * j + 1] *= a0; O[4 * j + 2] *= a1; O[4 * j + 3] *= a1; }
  }
}

__device__ __forceinline__ void modulate_frags(uint32_t* A, const uint32_t* V, const uint4* R, const uint32_t* ln) {
#pragma unroll
  for (int kk = 0; kk < 4; kk++) {
    const uint4 sa = R[kk >> 1], c1 = R[2 + (kk >> 1)];
#pragma unroll
    for (int j = 0; j < 4; j++) {
      const uint32_t n = hfma2(V[4 * kk + j], ln[(j & 1) * 2 + 1], ln[(j & 1) * 2]);
      A[4 * kk + j] = (kk & 1) ? ((j & 2) ? hfma2(n, c1.w, sa.x) : hfma2(n, c1.z, sa.w)) : ((j & 2) ? hfma2(n, c1.y, sa.z) : hfma2(n, c1.x, sa.y));
    }
  }
}
__device__ __forceinline__ void publish_record(uint4* dst, uint32_t pk, int src, int vec, bool doit) {
  const int r = vec ? 0 : 12;
  const uint32_t x = __shfl_sync(0xffffffffu, pk, src + r), y = __shfl_sync(0xffffffffu, pk, src + ((r + 4) & 12));
  const uint32_t z = __shfl_sync(0xffffffffu, pk, src + ((r + 8) & 12)), w = __shfl_sync(0xffffffffu, pk, src + ((r + 12) & 12));
  if (doit) st_pkt16(dst, ~x, y, z, w);
}
__device__ __forceinline__ void put_record(uint32_t sb, int idx, const uint4& v) {
  sts128(sb + SM_STASH + idx * 16, ~v.x, v.y, v.z, v.w);
  sts128(sb + SM_STASH + 16384 + idx * 16, ~v.x, v.y, v.z, v.w);
}
__device__ __forceinline__ float mod_value(float v, int vec) {
  v = rbf(v);
  return (vec ? rbf(1.f + v) : v) * SM_SCALE;
}

__device__ __forceinline__ void row_rcp(float& l0, float& l1) {
  l0 += __shfl_xor_sync(0xffffffffu, l0, 1); l1 += __shfl_xor_sync(0xffffffffu, l1, 1);
  l0 += __shfl_xor_sync(0xffffffffu, l0, 2); l1 += __shfl_xor_sync(0xffffffffu, l1, 2);
  l0 = rcp_f(l0); l1 = rcp_f(l1);
}
__device__ __forceinline__ void stage_o(const float* O, float r0, float r1, uint32_t stsm_addr) {
#pragma unroll
  for (int kk = 0; kk < 8; kk++) {
    stsm4((stsm_addr + (kk >> 2) * 8192) ^ ((kk & 3) * 32),
          pack2(O[8 * kk + 0] * r0, O[8 * kk + 1] * r0), pack2(O[8 * kk + 2] * r1, O[8 * kk + 3] * r1),
          pack2(O[8 * kk + 4] * r0, O[8 * kk + 5] * r0), pack2(O[8 * kk + 6] * r1, O[8 * kk + 7] * r1));
  }
}

__global__ void __cluster_dims__(2, 1, 1) __launch_bounds__(NTHREADS, 1)
fused_kernel(const Params p, const __grid_constant__ CUtensorMap mH, const __grid_constant__ CUtensorMap mWq,
             const __grid_constant__ CUtensorMap mK, const __grid_constant__ CUtensorMap mV,
             const __grid_constant__ CUtensorMap mO, const __grid_constant__ CUtensorMap mWo,
             const __grid_constant__ CUtensorMap mX, const __grid_constant__ CUtensorMap mOut,
             const __grid_constant__ CUtensorMap mWg, const __grid_constant__ CUtensorMap mWu,
             const __grid_constant__ CUtensorMap mWd, const __grid_constant__ CUtensorMap mWm,
             const __grid_constant__ CUtensorMap mWs, const __grid_constant__ CUtensorMap mWh) {
  extern __shared__ __align__(1024) uint8_t smem_raw[];
  TH(0);
  const uint32_t sb = smem_u32(smem_raw);
  const int tid = threadIdx.x;
  const int b0 = blockIdx.x;
  const int lane = tid & 31;
  const int role = __shfl_sync(0xffffffffu, tid >> 8, 0);

  if (b0 >= NMAIN) {
    const uint32_t cs = clock();
    const uint32_t tag = ld_relaxed(&g_epoch) + 1;
    const int sp = b0 - NMAIN, vec = 2 + sp;
    const int warp = __shfl_sync(0xffffffffu, tid >> 5, 0);
    float* sc = reinterpret_cast<float*>(smem_raw + SM_STASH);
    float* red = reinterpret_cast<float*>(smem_raw + SM_STASH + 4096);
    const int ridx = (lane >> 3) * 2 * RV + (sp & 1) * RV + 16 * RS + (sp >> 1) * 16 + (warp & 1) * 8 + (lane & 7);
    if (warp < 8) st_pkt16(&g_rec[warp >> 2][0][ridx + (warp & 2) * 16], 0, 0, 0, 0);
#pragma unroll 1
    for (int i = tid; i < 1024; i += NTHREADS) sc[i] = rbf(silu_f(__bfloat162float(p.c[i])));
    if (tid == 0) {
      tma_prefetch_desc(&mWs);
      for (int s = 0; s < NST2; s++) { mbar_init(sb + BAR_FULL2 + 8 * s, 1); mbar_init(sb + BAR_EMPTY2 + 8 * s, 8); }
      fence_async_smem();
      while ((uint32_t)clock() - cs < SPT) {}
    }
    __syncthreads();
    int s = 0; uint32_t ph = 0;
    if (tid == 0) TS(0);
    if (warp == 8) {
      const uint64_t pol = policy_evict_first();
#pragma unroll 1
      for (int n = 0; n < 80; n++) {
        mbar_wait_g(sb + BAR_EMPTY2 + 8 * s, ph ^ 1);
        if (elect_one()) {
          mbar_expect_tx(sb + BAR_FULL2 + 8 * s, 32768);
          if (n < 16) {
            tma_ld_hint(sb + s * ST2, &mWs, (sp & 1) * 1024 + 512 + (n >> 3) * 256 + (sp >> 1) * 128, (n & 7) * 128, sb + BAR_FULL2 + 8 * s, pol);
          } else {
#pragma unroll
            for (int j = 0; j < 4; j++) tma_ld_hint(sb + s * ST2 + j * 8192, &mWm, vec * 1024 + j * 256, (n - 16) * 16, sb + BAR_FULL2 + 8 * s, pol);
          }
        }
        __syncwarp();
        if (++s == NST2) { s = 0; ph ^= 1; }
      }
    } else if (warp < 8) {
      float acc[8];
#pragma unroll
      for (int i = 0; i < 8; i++) acc[i] = 0.f;
      auto stage = [&](uint32_t a0, int da, const float* cp, int dc) {
        mbar_wait_g(sb + BAR_FULL2 + 8 * s, ph);
#pragma unroll
        for (int i = 0; i < 8; i++) {
          const uint4 v = lds128(a0 + s * ST2 + i * da);
          const float c = cp[i * dc];
          acc[0] = fmaf(lo2f(v.x), c, acc[0]); acc[1] = fmaf(hi2f(v.x), c, acc[1]);
          acc[2] = fmaf(lo2f(v.y), c, acc[2]); acc[3] = fmaf(hi2f(v.y), c, acc[3]);
          acc[4] = fmaf(lo2f(v.z), c, acc[4]); acc[5] = fmaf(hi2f(v.z), c, acc[5]);
          acc[6] = fmaf(lo2f(v.w), c, acc[6]); acc[7] = fmaf(hi2f(v.w), c, acc[7]);
        }
        if (__shfl_sync(0xffffffffu, lane, __float_as_uint(acc[7]) & 31) < 32 && lane == 0) mbar_arrive(sb + BAR_EMPTY2 + 8 * s);
        if (++s == NST2) { s = 0; ph ^= 1; }
      };
#pragma unroll 1
      for (int n = 0; n < 16; n++) {
        stage(sb + tid * 16, 4096, sc + (n & 7) * 128 + (tid >> 4), 16);
        if ((n & 7) == 7) {
          float* r2 = red + 2048 + (n & 8) * 256;
#pragma unroll
          for (int i = 0; i < 8; i++) { r2[tid * 8 + i] = acc[i]; acc[i] = 0.f; }
          nb_sync(NB_CONS, 256);
          if (warp < 2) {
            float v0 = 0.f, v1 = 0.f;
#pragma unroll 4
            for (int i = 0; i < 16; i++) { const float2 e = reinterpret_cast<const float2*>(r2)[i * 64 + tid]; v0 += e.x; v1 += e.y; }
            publish_record(&g_rec[tag & 1][0][ridx + (n >> 3) * 32], pack2(mod_value(v0, sp & 1), mod_value(v1, sp & 1)),
                           (lane & 4) * 4 + (lane & 3), sp & 1, true);
          }
          if (tid == 0) TS(1 + (n >> 3));
        }
      }
#pragma unroll 1
      for (int n = 0; n < 64; n++) {
        stage(sb + ((tid >> 5) & 3) * 8192 + (tid >> 7) * 4096 + (tid & 31) * 16, 512, sc + n * 16 + (tid >> 7) * 8, 1);
      }
#pragma unroll
      for (int i = 0; i < 8; i++) red[(tid >> 7) * 1024 + (tid & 127) * 8 + i] = acc[i];
    }
    __syncthreads();
    float dot = 0.f;
#pragma unroll 1
    for (int i = tid; i < 512; i += NTHREADS) {
      uint32_t v = pack2(red[2 * i] + red[1024 + 2 * i], red[2 * i + 1] + red[1024 + 2 * i + 1]);
      st_pkt8(&g_mod[vec * 512 + i], v, tag);
      if (vec == 4) v = hadd2(v, ONE2);
      const uint32_t wr = reinterpret_cast<const uint32_t*>(p.w_r)[i];
      dot = fmaf(lo2f(v), lo2f(wr), fmaf(hi2f(v), hi2f(wr), dot));
    }
#pragma unroll
    for (int o = 16; o; o >>= 1) dot += __shfl_xor_sync(0xffffffffu, dot, o);
    if (lane == 0) sc[warp] = dot;
    __syncthreads();
    if (tid == 0) {
      dot = 0.f;
      for (int w = 0; w < 12; w++) dot += sc[w];
      fence_release_gpu();
      st_pkt8(&g_vdone[(vec - 2) * 16], __float_as_uint(dot), tag);
      TS(11);
#pragma unroll 1
      for (int i = 0; i < 128; i++) {
        const int u = i * 4 + (b0 - NMAIN);
        l2_prefetch(p.wo + (size_t)((4 * ((u >> 4) & 7) + (u >> 7)) * 128 + (u & 15) * 8) * 1024, 16384);
        __nanosleep(PFW);
      }
    }
    return;
  }

  const uint32_t rank = b0 & 1;
  const bool slab = !(b0 & 32), late = b0 & 16;
  const uint32_t c0 = clock();
  if (tid == 352) TS(0);
  const uint32_t slab_addr = sb + SM_WSLAB + (tid >> 5) * 4096 + (lane & 3) * 128 + (lane & 4) * 16 + (((lane >> 3) ^ lane) & 3) * 16;
  auto load_slab = [&]() {
    const bf16* wp = p.w_mod + (size_t)(512 * rank + 2 * (tid & ~31) + 2 * (lane & 3) + ((lane >> 2) & 1)) * 6144 + 32 * (b0 >> 1) + 8 * (lane >> 3);
    const uint64_t pef = policy_evict_first();
#pragma unroll
    for (int i = 0; i < 8; i++)
      asm volatile("cp.async.cg.shared.global.L2::cache_hint [%0], [%1], 16, %2;"
        :: "r"(slab_addr + i * 512), "l"(wp + (size_t)i * 8 * 6144), "l"(pef) : "memory");
  };
  if (tid == 256) {
    mbar_init(sb + BAR_XH, 1);
    fence_async_smem();
    mbar_expect_tx(sb + BAR_XH, 32768);
    if (XD) while ((uint32_t)clock() - c0 < XD) {}
#pragma unroll
    for (int i = 0; i < 2; i++)
      asm volatile("cp.async.bulk.shared::cluster.global.mbarrier::complete_tx::bytes [%0], [%1], 16384, [%2];"
        :: "r"(sb + SM_XROW + i * ST1), "l"(p.x + (size_t)b0 * 16384 + i * 8192), "r"(sb + BAR_XH) : "memory");
  }
  __syncwarp();
  uint32_t cw[8];
#pragma unroll
  for (int i = 0; i < 8; i++) cw[i] = 0;
  if (!role && slab) {
#pragma unroll
    for (int i = 0; i < 8; i++) cw[i] = ld_relaxed(reinterpret_cast<const uint32_t*>(p.c) + 256 * rank + (tid & ~28) + 4 * i);
  }
  uint32_t epoch = 0;
  if (!role) epoch = ld_relaxed(&p.sc->epoch[lane]);
  if (!role && slab && !late) load_slab();
#define TILE_ROLES() \
  mbar_wait(sb + BAR_ROLE, 0); \
  const int b = 2 * __shfl_sync(0xffffffffu, lds32(sb + SM_ROLE), 0) + rank; \
  const int rt = b >> 3;     \
  const int ct = b & 7;

  if (role) {
    asm volatile("setmaxnreg.dec.sync.aligned.u32 24;");
    const int warp = __shfl_sync(0xffffffffu, tid >> 5, 0);
    if (tid == 256) {
      mbar_init(sb + BAR_RED, 1); mbar_init(sb + BAR_WH, 1);
      for (int s = 0; s < 2; s++) mbar_init(sb + BAR_OF + 8 * s, 1);
      mbar_init(sb + BAR_ROLE, 1);
      for (int s = 0; s < 5; s++) { mbar_init(sb + BAR_FULL1 + 8 * s, 1); mbar_init(sb + BAR_EMPTY1 + 8 * s, 4); }
      for (int s = 0; s < 2; s++) { mbar_init(sb + BAR_STASH + 8 * s, 1); mbar_init(sb + BAR_X + 8 * s, 1); }
      for (int s = 0; s < 4; s++) mbar_init(sb + BAR_HS + 8 * s, 1);
      mbar_init(sb + BAR_G, 16); mbar_init(sb + BAR_T1, 1); mbar_init(sb + BAR_HF, 1);
      mbar_init(sb + BAR_SFREE, 4); mbar_init(sb + BAR_TFREE, 8);
      mbar_init(sb + BAR_FFN, 4); mbar_init(sb + BAR_FFN + 8, 2);
      mbar_init(sb + BAR_CAND, 1); mbar_init(sb + BAR_VEC, 32); for (int s = 0; s < 3; s++) mbar_init(sb + BAR_TAB + 8 * s, 32);
      mbar_expect_tx(sb + BAR_RED, 1024);
      mbar_expect_tx(sb + BAR_ROLE, 4);
      asm volatile("fence.mbarrier_init.release.cluster;" ::: "memory");
    }
    __syncwarp();
    asm volatile("barrier.cluster.arrive.relaxed.aligned;" ::: "memory");
    const int ridx = ((lane >> 1) & 3) * 2 * RV + (b0 >> 6) * RV + ((b0 >> 1) & 31) * RS + 2 * rank + (lane & 1) + (lane >> 3) * 4;
    if (warp == 11 && slab && lane < 2 * RS) { st_pkt16(&g_rec[0][0][ridx], 0, 0, 0, 0); st_pkt16(&g_rec[1][0][ridx], 0, 0, 0, 0); }
    if (tid == 256) {
      tma_prefetch_desc(&mWq); tma_prefetch_desc(&mX); tma_prefetch_desc(&mH); tma_prefetch_desc(&mK); tma_prefetch_desc(&mV); tma_prefetch_desc(&mO);
    }
    uint32_t pairid = 0;
    if (tid == 320 && rank == 0) {
      uint32_t t;
      asm("mov.u32 %0, %%smid;" : "=r"(t));
      t >>= 1;
      uint32_t grp = ((0x73216540u >> (4 * ((t < 32 ? t : t < 60 ? 1 + (t - 32) % 7 : t < 62 ? t - 54 : 0) & 7))) & 7) - 1, slot;
      int it = 0;
      do {
        grp = (grp + 1) & 7;
        asm volatile("atom.relaxed.gpu.global.add.u32 %0, [%1], 1;" : "=r"(slot) : "l"(&p.sc->ticket[grp * 32]) : "memory");
        spin_guard(it);
      } while (slot >= 8);
      pairid = slot * 8 + grp;
    }
    __syncwarp();
    asm volatile("barrier.cluster.wait.aligned;" ::: "memory");
    if (tid == 320 && rank == 0) {
#pragma unroll
      for (int r = 0; r < 2; r++)
        asm volatile("st.async.weak.shared::cluster.mbarrier::complete_tx::bytes.b32 [%0], %1, [%2];"
          :: "r"(mapa(sb + SM_ROLE, r)), "r"(pairid), "r"(mapa(sb + BAR_ROLE, r)) : "memory");
    }
    __syncwarp();
    const uint32_t tag = ld_relaxed(&g_epoch) + 1;
    if (warp == 8) {
      TILE_ROLES();
      const int kvrow = (ct >> 1) * 2048 + 1536, arow = rt * 128 + rank * 64;
      const uint64_t pef = policy_evict_first();
#pragma unroll 1
      for (int pair = 0; pair < 2; pair++) {
        const int wblk = (4 * ct + 2 * pair) * 2;
        if (pair) { mbar_wait_g(sb + BAR_HF, 0); fence_async_global(); }
#pragma unroll 1
        for (int n = 0; n < 16; n++) {
          const uint32_t s = n & 3, st = sb + SM_RING + s * ST1, fb = sb + BAR_FULL1 + 8 * s;
          if (n == 2 && pair == 0) mbar_wait_g(sb + BAR_G, 0);
          mbar_wait_g(fb + (BAR_EMPTY1 - BAR_FULL1), ((n >> 2) & 1) ^ 1);
          if (elect_one()) {
            mbar_expect_tx(fb, 49152);
            if (pair) tma_ld_mc_hint(st + rank * 8192, &mH, n * 64, arow, fb, pef); else
            tma_ld_mc(st + rank * 8192, pair ? &mH : &mX, n * 64, arow, fb);
            tma_ld3_hint(st + 16384, &mWq, n * 64, wblk, fb, pef);
          }
          __syncwarp();
        }
#pragma unroll 1
        for (int n = 0; n < 16; n++) {
          const uint32_t s = n & 3, st = sb + SM_RING + s * ST1 + rank * 8192, fb = sb + BAR_FULL1 + 8 * s;
          const int h0 = n == 0 ? 0 : n == 15 ? 14 : n + 1, h1 = n == 0 ? 1 : n == 15 ? 15 : n - 1;
          mbar_wait_g(fb + (BAR_EMPTY1 - BAR_FULL1), ((n >> 2) & 1) ^ 1);
          if (elect_one()) {
            mbar_expect_tx(fb, 32768);
            tma_ld_mc(st, n == 15 ? &mV : &mK, rank * 64, kvrow + (h0 & 7) * 64, fb);
            tma_ld_mc(st + 16384, n == 0 ? &mK : &mV, rank * 64, kvrow + (h1 & 7) * 64, fb);
            if (n == 3 && pair == 1) mbar_arrive(sb + BAR_T1);
          }
          __syncwarp();
        }
      }
      {
        uint32_t s = 0, ph = 1;
#pragma unroll 1
        for (int half = 0; half < 2; half++) {
          mbar_wait_g(sb + BAR_OF + 8 * half, 0);
          fence_async_global();
#pragma unroll 1
          for (int n = 32 * half; n < 32 * half + 32; n++) {
            const uint32_t st = sb + SM_RING + s * ST1, fb = sb + BAR_FULL1 + 8 * s;
            const int k0 = ((n & 14) * 2 + (n >> 4)) * 128 + (n & 1) * 64;
            mbar_wait_g(n == 8 ? sb + BAR_SFREE : fb + (BAR_EMPTY1 - BAR_FULL1), n == 8 ? 0 : ph ^ (s >> 2));
            if (elect_one()) {
              mbar_expect_tx(fb, 32768);
              tma_ld_mc_hint(st + rank * 8192, &mO, k0, arow, fb, pef);
              tma_ld3_hint(st + 16384, &mWo, k0, 2 * ct, fb, pef);
            }
            __syncwarp();
            if (++s == 5 || n == 3) { s = 0; ph ^= 1; }
          }
        }
        if (b < NFFN) {
#pragma unroll 1
          for (s = 0; s < 2; s++) {
            mbar_wait_g(sb + BAR_EMPTY1 + 8 * s, 0);
            if (elect_one()) {
              mbar_expect_tx(sb + BAR_FFN + 8, 32768);
              tma_ld3_hint(sb + SM_RING + s * ST1, &mWd, b * 32, s * 8, sb + BAR_FFN + 8, pef);
            }
            __syncwarp();
          }
        }
      }
    } else if (warp <= 10) {
      const int w = warp - 9;
      if (slab && late && w == 0 && lane == 0) {
        tma_prefetch_desc(&mWh);
        mbar_expect_tx(sb + BAR_WH, 32768);
        while ((uint32_t)clock() - c0 < WL) {}
        const uint64_t pef = policy_evict_first();
#pragma unroll
        for (int i = 0; i < 2; i++) tma_ld_hint(sb + SM_WSLAB + i * 16384, &mWh, 32 * (b0 >> 1), 512 * rank + 256 * i, sb + BAR_WH, pef);
      }
      __syncwarp();
      TILE_ROLES();
      const uint32_t st = sb + SM_STASH + w * 16384;
#pragma unroll 1
      for (int j = 0; j < 2; j++) {
        nb_sync(NB_OST + w, 160);
        if (elect_one()) {
          fence_async_smem();
          tma_st(&mH, (2 * ct + j) * 64, rt * 128 + w * 64, st + 4096);
          bulk_commit();
          bulk_wait_read();
          mbar_arrive(sb + BAR_HS + 16 * w + 8 * j);
          if (j) {
            bulk_wait_all();
            fence_async_global();
            fence_release_gpu();
            red_add_relaxed(&g_hflag[rt * 32], 1);
          }
        }
        __syncwarp();
      }
#pragma unroll 1
      for (int r = 0; r < 4; r++) {
        nb_sync(NB_OST + w, 160);
        if (elect_one()) {
          fence_async_smem();
          const int hcol = (4 * ct + r) * 128;
          tma_st(&mO, hcol, rt * 128 + w * 64, st);
          tma_st(&mO, hcol + 64, rt * 128 + w * 64, st + 8192);
          bulk_commit();
          bulk_wait_read();
          if (r < 2) {
            mbar_arrive(sb + BAR_STASH + 8 * w);
          } else if (r == 2) {
            mbar_expect_tx(sb + BAR_X + 8 * w, 16384);
            tma_ld_hint(st, &mX, ct * 128, rt * 128 + w * 64, sb + BAR_X + 8 * w, policy_evict_first());
            tma_ld_hint(st + 8192, &mX, ct * 128 + 64, rt * 128 + w * 64, sb + BAR_X + 8 * w, policy_evict_first());
          } else {
            mbar_arrive_cl(mapa(sb + BAR_SFREE, 0)); mbar_arrive_cl(mapa(sb + BAR_SFREE, 1));
          }
          bulk_wait_all();
          fence_async_global();
          fence_release_gpu();
          red_add_relaxed(&g_oflag[(rt * 4 + r) * 32], 1);
        }
        __syncwarp();
      }
      nb_sync(NB_OST + w, 160);
      int skip = -1;
      mbar_wait_g(sb + BAR_CAND, 0);
      const bool has_cand = (lds32(sb + SM_CAND) >> 6) == w;
      if (has_cand) {
        nb_sync(NB_WIN + w, 160);
        skip = (int)lds32(sb + SM_WROW + 4 * w) - (rt * 128 + w * 64);
      }
      if ((unsigned)skip >= 64u) {
        if (elect_one()) {
          fence_async_smem();
          tma_st(&mOut, ct * 128, rt * 128 + w * 64, sb + SM_OUT + w * 16384);
          tma_st(&mOut, ct * 128 + 64, rt * 128 + w * 64, sb + SM_OUT + w * 16384 + 8192);
          bulk_commit();
          bulk_wait_read();
        }
        __syncwarp();
      } else {
        uint4* dst = reinterpret_cast<uint4*>(p.out + (size_t)(rt * 128 + w * 64 + (lane >> 4)) * 1024 + ct * 128) + (lane & 15);
#pragma unroll 2
        for (int r = lane >> 4; r < 64; r += 2) {
          const uint4 v = lds128(sb + SM_OUT + w * 16384 + ((lane >> 3) & 1) * 8192 + r * 128 + (((lane ^ r) & 7) * 16));
          if (r != skip) *dst = v;
          dst += 256;
        }
      }
      if (!has_cand) nb_sync(NB_WIN + w, 160);
    } else {
      if (slab) {
        mbar_wait_g(sb + BAR_RED, 0);
        float v = 0.f;
#pragma unroll
        for (int w = 0; w < 8; w++) v += lds_f32(sb + SM_RED + w * 128 + lane * 4);
        v += __shfl_xor_sync(0xffffffffu, v, 16);
        v = mod_value(v, b0 >> 6);
        publish_record(&g_rec[tag & 1][0][ridx], pack2(v, __shfl_down_sync(0xffffffffu, v, 1)), 2 * (lane & 1), b0 >> 6, lane < 8);
        if (lane == 0) TS(1);
      }
      mbar_wait_g(sb + BAR_G, 0);
#pragma unroll 1
      for (int i = 1; i < 4; i++) {
        const uint4* mp = &g_rec[tag & 1][(b0 >> 1) & (NREP - 1)][i == 1 ? (8 + (lane >> 2)) * RS + (lane & 3) : 16 * RS - 64 + 32 * i + lane];
        uint4 v0, v1; int it = 0;
        while (true) {
          v0 = ld_pkt16(mp); v1 = ld_pkt16(mp + RV);
          if (v0.x != 0 && v1.x != 0) break;
          spin_guard(it); __nanosleep(PLD);
        }
        put_record(sb, 32 * i + lane, v0);
        put_record(sb, 128 + 32 * i + lane, v1);
        mbar_arrive(sb + BAR_TAB - 8 + 8 * i);
        if (lane == 0) {
          TS(3 + i + (i > 2));
          if (i == 1) l2_prefetch(((b0 & 64) ? p.vc : p.kc) + (size_t)(((b0 >> 4) & 3) * 2048 + 1536) * 128 + (b0 & 15) * 4096, 8192);
        }
        __syncwarp();
      }
      TILE_ROLES();
      if (lane == 0) {
        int it = 0;
        do { __nanosleep(500); spin_guard(it); } while (ld_relaxed(&g_hflag[rt * 32]) != tag * 16u);
        fence_acquire_gpu();
        mbar_arrive(sb + BAR_HF);
        if (b < NFFN) for (int i = 0; i < 8; i++) { __nanosleep(800); l2_prefetch(p.wd + (size_t)(b * 32 + i * 4) * 1024, 8192); }
      }
      __syncwarp();
      {
        uint2 v; int it = 0;
        do { __nanosleep(1000); v = ld_pkt8(&g_vdone[(lane & 3) * 16]); spin_guard(it); }
        while (!(v.y == tag));
        __syncwarp();
        fence_acquire_gpu();
        if (lane == 1 || lane == 2) sts32(sb + SM_SCAL + (2 - lane) * 4, v.x);
      }
#pragma unroll 1
      for (int i = 0; i < 2; i++) {
        const int q = i * 32 + lane, pi = ct * 64 + q;
        const uint32_t vga = g_mod[2 * 512 + pi].x, vsb = g_mod[3 * 512 + pi].x, vcb = g_mod[4 * 512 + pi].x, vgb = g_mod[5 * 512 + pi].x;
        const uint32_t wr = reinterpret_cast<const uint32_t*>(p.w_r)[pi];
        const uint32_t c1 = hadd2(vcb, ONE2);
        const float al = lo2f(c1) * lo2f(wr), ah = hi2f(c1) * hi2f(wr);
        const uint32_t o8 = (q & 3) * 8 + ((q >> 2) & 1) * 4;
        sts32(sb + SM_GA + (q >> 3) * 32 + o8, vga);
        sts128(sb + SM_REC + q * 16, c1, vsb, vgb, 0);
        const uint32_t ahi = pack2(al, ah), alo = pack2(al - lo2f(ahi), ah - hi2f(ahi));
        const uint32_t ba = sb + SM_B1 + (q >> 3) * 128 + o8;
        sts32(ba, ONE2); sts32(ba + 32, ahi); sts32(ba + 64, alo); sts32(ba + 96, 0);
      }
      if (lane == 0) TS(28);
      if (lane == 0) {
        tma_prefetch_desc(&mWo); tma_prefetch_desc(&mOut); tma_prefetch_desc(&mWd); tma_prefetch_desc(&mWg); tma_prefetch_desc(&mWu);
#pragma unroll 1
        for (int r = 0; r < 4; r++) {
          int it = 0;
          do { __nanosleep(200); spin_guard(it); } while (ld_relaxed(&g_oflag[(rt * 4 + r) * 32]) != tag * 16u);
          if (r & 1) { fence_acquire_gpu(); mbar_arrive(sb + BAR_OF + 8 * (r >> 1)); }
          if (r == 1 && b < NFFN) {
            const uint64_t pef = policy_evict_first();
            mbar_wait_g(sb + BAR_T1, 0);
#pragma unroll 1
            for (int i = 0; i < 4; i++) {
              mbar_expect_tx(sb + BAR_FFN, 16384);
              tma_ld_hint(sb + SM_RING + i * ST1 + 32768, &mWg, b * 32, i * 256, sb + BAR_FFN, pef);
              __nanosleep(GATED);
            }
          }
        }
      }
      __syncwarp();
      if (b < NFFN) {
        mbar_wait_g(sb + BAR_TFREE, 0);
        const uint64_t pef = policy_evict_first();
#pragma unroll 1
        for (int i = 0; i < 5; i++) {
          if (i > 0 && lane == 0) {
            mbar_expect_tx(sb + BAR_FFN, 16384);
            tma_ld_hint(sb + SM_RING + (i - 1) * ST1 + 32768, &mWu, b * 32, (i - 1) * 256, sb + BAR_FFN, pef);
          }
          if (i < 4) {
#pragma unroll 1
            for (int j = 0; j < 8; j++) {
              asm volatile("prefetch.global.L2 [%0];" :: "l"(p.wu + (size_t)(i * 256 + j * 32 + lane) * 3584 + b * 32) : "memory");
              __nanosleep(UPD);
            }
            __nanosleep(500);
          }
        }
      }
      if (lane == 0) TS(29);
#pragma unroll 1
      for (int i = lane; i < 128; i += 32) st_pkt16(&g_stats[b * 128 + i], 0, 0, 0, 0);
      st_pkt16(&g_cand[b * 32 + lane], 0, 0, 0, 0);
      if (lane < ESTR) st_pkt16(&g_entry[(ct * 16 + rt) * ESTR + lane], 0, 0, 0, 0);
#pragma unroll 1
      for (int i = lane; i < (b < NFFN ? 512 : 0); i += 32) st_pkt16(&g_ypart[((i >> 2) * NFFN + b) * 4 + (i & 3)], 0, 0, 0, 0);
      mbar_arrive(sb + BAR_VEC);
      uint4* const cp = &g_cand[b * 32 + lane];
      uint4* const ep = &g_entry[(ct * 16 + rt) * ESTR];
      nb_sync(NB_AMAX, 288);
      TV(0);
      const uint2 e = lds64(sb + SM_AMAX + (lane & 7) * 8);
      const int tmax = __reduce_max_sync(0xffffffffu, (int)e.x);
      const uint32_t row = ~tmax & 127;
      const int wl = row >> 4;
      const uint32_t xa = sb + SM_X2 + (row >> 6) * 16384 + (lane >> 4) * 8192 + (row & 63) * 128 + (lane & 3) * 4
                        + ((((lane >> 1) & 6) ^ (row & 7)) * 16);
      const uint32_t v0 = lds32(xa), v1 = lds32(xa ^ 16);
      if (lane == wl) st_pkt16(ep, (tmax | 127) - rt, rt * 128 + row, e.y, tag);
      st_pkt16(cp, v0, v1, tag, 0);
      if (lane == 0) { sts32(sb + SM_CAND, row); mbar_arrive(sb + BAR_CAND); }
      TV(1);
      if (lane == 0) TS(15);
    }
  } else {
    const int warp = tid >> 5;
    const int wg = warp >> 2, wq = warp & 3;
    const int g = lane >> 2, t = lane & 3;
    uint32_t tag;
    uint32_t ln[4];
    float acc[128];
    uint32_t bf[16];
    auto gemv = [&]() {
          if (late) mbar_wait(sb + BAR_WH, 0); else
          asm volatile("cp.async.wait_all;" ::: "memory");
          float d0[4] = {0.f, 0.f, 0.f, 0.f}, d1[4] = {0.f, 0.f, 0.f, 0.f};
#pragma unroll
          for (int i = 0; i < 8; i++) {
            const uint4 wv = lds128(slab_addr + i * 512);
            const uint32_t a[4] = {wv.x, wv.y, wv.z, wv.w};
            mma16816((i & 1) ? d1 : d0, a, bf[2 * i], bf[2 * i + 1]);
          }
#pragma unroll
          for (int i = 0; i < 4; i++) { d0[i] += d1[i]; d0[i] += __shfl_xor_sync(0xffffffffu, d0[i], 6); }
          const uint32_t dst = mapa(sb + SM_MISC, t & 1) - SM_MISC;
          if (!(lane & 6)) st_async_f32x4(dst + SM_RED + warp * 128 + rank * 64 + g * 8, d0, dst + BAR_RED);
          TH(4);
    };
    {
      asm volatile("barrier.cluster.arrive.relaxed.aligned;" ::: "memory");
      if (lane == 0) st_pkt16(&g_lnst[8 * b0 + warp], 0, 0, 0, 0);
      TH(1);
      asm volatile("setmaxnreg.inc.sync.aligned.u32 240;");
      TH(2);
#pragma unroll
      for (int i = 0; i < 8; i++) {
        const float sv = silu_f((g & 4) ? hi2f(cw[i]) : lo2f(cw[i]));
        const uint32_t sp = (g & 1) ? pack2(0.f, sv) : pack2(sv, 0.f);
        bf[2 * i] = (g & 2) ? 0 : sp; bf[2 * i + 1] = (g & 2) ? sp : 0;
      }
      asm volatile("barrier.cluster.wait.aligned;" ::: "memory");
#pragma unroll
      for (int i = 0; i < 128; i++) acc[i] = 0.f;
      reg_fence<128>(acc);
      tag = __shfl_sync(0xffffffffu, epoch, 0) + 1;
      TH(3);
      if (slab && !late) gemv();
      {
        {
          mbar_wait(sb + BAR_XH, 0);
          TH(5);
          float ds[4] = {0.f, 0.f, 0.f, 0.f}, dq[4][4];
#pragma unroll
          for (int i = 0; i < 4; i++) { dq[i][0] = dq[i][1] = dq[i][2] = dq[i][3] = 0.f; }
#pragma unroll
          for (int i = 0; i < 8; i++) {
            uint32_t a[4];
            ldsm4(sb + SM_XROW + wg * ST1 + wq * 4096 + ((lane >> 3) & 1) * 2048 + i * 256 + (lane >> 4) * 128 + (lane & 7) * 16, a);
            mma16816(ds, a, ONE2, ONE2);
            mma1688(dq[0], a[0], a[1], a[0]); mma1688(dq[1], a[0], a[1], a[1]);
            mma1688(dq[2], a[2], a[3], a[2]); mma1688(dq[3], a[2], a[3], a[3]);
          }
          const bool dg = t == (g >> 1);
          const float q0 = dg ? ((g & 1) ? dq[0][1] + dq[2][1] : dq[0][0] + dq[2][0]) : 0.f;
          const float q1 = dg ? ((g & 1) ? dq[1][3] + dq[3][3] : dq[1][2] + dq[3][2]) : 0.f;
          float q = ((lane & 1) ? q1 : q0) + __shfl_xor_sync(0xffffffffu, (lane & 1) ? q0 : q1, 1);
          float sm = (lane & 1) ? ds[2] : ds[0];
          q += __shfl_xor_sync(0xffffffffu, q, 2);
#pragma unroll
          for (int o = 4; o <= 16; o <<= 1) { q += __shfl_xor_sync(0xffffffffu, q, o); sm += __shfl_xor_sync(0xffffffffu, sm, o); }
          const float mean = sm * (1.f / 1024.f);
          const float rd = rcp_f(rbf(sqrt_f(rbf(rbf(fmaxf(fmaf(-mean, mean, q * (1.f / 1024.f)), 0.f)) + 1e-5f))));
          const float mean1 = __shfl_sync(0xffffffffu, mean, 1), rd1 = __shfl_sync(0xffffffffu, rd, 1);
          const uint32_t rh = pack2(rd, rd1);
          if (lane == 0) st_pkt16(&g_lnst[8 * b0 + warp], pack2(-rbf(mean) * lo2f(rh), -rbf(mean1) * hi2f(rh)), rh, 0, tag);
          TH(6);
          if (tid == 0) TS(2);
        }
      }
    }
    if (slab && late) gemv();
    TILE_ROLES();
    const uint32_t xa0 = sb + SM_RING + (warp * 16 + (lane & 15)) * 128 + (((lane >> 4) ^ (lane & 7)) * 16);
    uint32_t V[16];
    {
      const uint4* mp = &g_rec[tag & 1][(b0 >> 1) & (NREP - 1)][RV * wg + (lane >> 2) * RS + (lane & 3)];
      const uint4* lp = &g_lnst[(8 * rt + warp) * 8 + (g >> 1)];
      mbar_wait(sb + BAR_FULL1, 0);
#pragma unroll
      for (int kk = 0; kk < 4; kk++) ldsm4(xa0 ^ (kk * 32), V + 4 * kk);
      uint4 v0 = make_uint4(1, 0, 0, 0), l0, l1;
      int it = 0;
      while ((uint32_t)clock() - c0 < HD) {}
      do { if (wq == 0) v0 = ld_pkt16(mp);
           l0 = ld_pkt16(lp); l1 = ld_pkt16(lp + 4); spin_guard(it); }
        while (!(__all_sync(0xffffffffu, v0.x != 0 && l0.w == tag && l1.w == tag)));
      TH(7);
      if (wq == 0) put_record(sb, 128 * wg + lane, v0);
      const uint32_t sel = (g & 1) ? 0x3232 : 0x1010;
      ln[0] = __byte_perm(l0.x, 0, sel); ln[1] = __byte_perm(l0.y, 0, sel);
      ln[2] = __byte_perm(l1.x, 0, sel); ln[3] = __byte_perm(l1.y, 0, sel);
      __syncwarp();
      if (lane < 2) mbar_arrive_cl(mapa(sb + BAR_G, lane));
      nb_sync(NB_CONS, 256);
      if (tid == 0) TS(3);
      TH(13);
    }

    const uint32_t rel = mapa(sb + SM_MISC, lane & 1) - SM_MISC;
    const uint32_t stsm_addr = sb + SM_STASH + wg * 16384 + (wq * 16 + (lane & 15)) * 128 + (((lane >> 4) ^ (lane & 7)) * 16);

    uint32_t ph = 0;
    uint32_t X[32];
    {
      const uint32_t tab0 = sb + SM_STASH + wg * 16384 + t * 16;
      const uint64_t db0 = mk_desc(sb + SM_RING + 16384, 8192);
      uint32_t A[2][16];
      uint32_t xa[4];
#pragma unroll
      for (int kk = 0; kk < 4; kk++) xa[kk] = xa0 ^ (kk * 32);
      uint32_t tab = tab0;
      reg_fence<4>(xa);
      asm volatile("{\n.reg .pred p;\nsetp.eq.u32 p, %4, 0;\n@p ld.shared.v4.u32 {%0,%1,%2,%3}, [%5];\n}"
        : "+r"(ln[2]), "+r"(ln[0]), "+r"(ln[3]), "+r"(ln[1]) : "r"(tag), "r"(sb));
      int hs = 2 * ct;
      uint4 R[4];
#pragma unroll
      for (int kk = 0; kk < 4; kk++) R[kk] = lds128(tab + (kk >> 1) * 2048 + (kk & 1) * 64);
#pragma unroll 1
      for (int k4 = 0; k4 < 4; k4++) {
#pragma unroll
        for (int s = 0; s < 4; s++) {
          uint32_t* a = A[s & 1];
          const int sn = (s + 1) & 3;
          const uint32_t pn = (k4 + (s == 3)) & 1;
          modulate_frags(a, V, R, ln);
          if (hs == (s & 2)) {
            if (s & 1) mbar_wait(sb + BAR_HS + 16 * wg, 0);
#pragma unroll
            for (int kk = 0; kk < 4; kk++) stsm4((stsm_addr + 4096) ^ (kk * 32), a[4 * kk], a[4 * kk + 1], a[4 * kk + 2], a[4 * kk + 3]);
            nb_arrive(NB_OST + wg, 160);
          }
          if (s == 0 && k4 == 0) TH(8);
          TQ(3 * s);
          if (s == 0 && k4 == 0 && tid == 0) { TS(6); TSC(61); }
          wg_fence();
#pragma unroll
          for (int kk = 0; kk < 4; kk++) wgmma_rs256<1>(acc, a + 4 * kk, db0 + s * (ST1 >> 4) + kk * 128);
          wg_commit();
          if (s == 3) TQ(12);
          if (s == 3 && k4 < 3) mbar_wait(sb + BAR_TAB + 8 * k4, 0);
          if (s == 3) TQ(13);
#pragma unroll
          for (int kk = 0; kk < 4; kk++) R[kk] = lds128(tab + (s + 1) * 128 + (kk >> 1) * 2048 + (kk & 1) * 64);
          wg_wait<1>();
          if (k4 == 0) TH(9 + s);
          TQ(3 * s + 1);
          reg_fence<16>(A[(s & 1) ^ 1]);
          if ((tid & 127) < 2 && (s | k4)) mbar_arrive_cl(rel + BAR_EMPTY1 + 8 * ((s + 3) & 3));
          if (s < 3 || k4 < 3) {
            mbar_wait(sb + BAR_FULL1 + 8 * sn, pn);
            TQ(3 * s + 2);
#pragma unroll
            for (int kk = 0; kk < 4; kk++) ldsm4(xa[kk] + sn * ST1, V + 4 * kk);
          }
        }
        tab += 512; hs -= 4;
      }
      mbar_wait(sb + BAR_HS + 16 * wg + 8, 0);
      wg_wait<0>();
      reg_fence<128>(acc);
    }
#pragma unroll 1
    for (int pair = 0; pair < 2; pair++) {
      uint32_t Q[32];
      TR(0);
      {
        if ((tid & 127) < 2) mbar_arrive_cl(rel + BAR_EMPTY1 + 8 * 3);
        if (pair == 1) mbar_wait(sb + BAR_STASH + 8 * wg, 1);
#pragma unroll
        for (int i = 0; i < 32; i++) Q[i] = pack2(acc[2 * i], acc[2 * i + 1]);
        const uint32_t qs = sb + SM_STASH + wg * 16384 + wq * 2048 + lane * 16;
#pragma unroll
        for (int i = 0; i < 8; i++)
          sts128(qs + (i & 3) * 512 + (i >> 2) * 8192, pack2(acc[64 + 8 * i], acc[65 + 8 * i]), pack2(acc[66 + 8 * i], acc[67 + 8 * i]),
                 pack2(acc[68 + 8 * i], acc[69 + 8 * i]), pack2(acc[70 + 8 * i], acc[71 + 8 * i]));
      }
      if (tid == 0) TS(8 + pair * 2);
      TR(1);
      float O[64], SL[32], SH[32];
      uint32_t PL[16], PH[16];
      SoftmaxState z;
      const uint64_t d0 = mk_desc(sb + SM_RING, 8192);
      {
        mbar_wait(sb + BAR_FULL1, ph);
        wg_fence();
        issue_qk(SL, Q, d0);
        wg_commit();
        issue_qk(SH, Q, d0 + 1024);
        wg_commit();
#pragma unroll
        for (int i = 0; i < 64; i++) O[i] = 0.f;
        reg_fence<64>(O);
        wg_wait<1>();
        reg_fence<32>(SL);
        softmax_start(z);
        softmax_half(SL, PL, O, z, true, tag);
        wg_wait<0>();
        reg_fence<32>(SH);
        if ((tid & 127) < 2) mbar_arrive_cl(rel + BAR_EMPTY1);
      }
      float lp0 = 0.f, lp1 = 0.f;
      uint32_t dB = (uint32_t)d0 + 1 * (ST1 >> 4), dA = (uint32_t)d0 + 2 * (ST1 >> 4);
      const uint32_t dBx = dB ^ ((uint32_t)d0 + 3 * (ST1 >> 4)), dAx = dA ^ (uint32_t)d0;
      uint32_t so = 0;
      bool ready = false;
#pragma unroll 1
      for (int i = 0; i < 7; i++) {
        TA(0);
        TR(2 + i);
        if (!ready) mbar_wait(sb + BAR_FULL1 + 8 + so, ph);
        TA(1);
        TA(2);
        wg_fence();
        issue_qk(SL, Q, (d0 & 0xffffffff00000000ull) | dB);
        if (i == 4) {
          __syncwarp();
          stage_o(O, lp0, lp1, stsm_addr);
        }
        wg_fence();
        issue_pv(O, PL, ((d0 & 0xffffffff00000000ull) | dB) + 1024, i != 4);
        wg_commit();
        if (i == 4) {
          nb_arrive(NB_OST + wg, 160);
        }
        TA(3);
        ph ^= i & 1;
        ready = mbar_test(sb + BAR_FULL1 + 16 - so, ph);
        softmax_half(SH, PH, O, z, false, tag);
        TA(4);
        wg_wait<0>();
        TA(5);
        reg_fence<32>(SL); reg_fence<16>(PL);
        if ((tid & 127) < 2) mbar_arrive_cl(rel + BAR_EMPTY1 + 8 + so);
        if (!ready) mbar_wait(sb + BAR_FULL1 + 16 - so, ph);
        TA(6);
        wg_fence();
        issue_qk(SH, Q, (d0 & 0xffffffff00000000ull) | dA);
        wg_commit();
        issue_pv(O, PH, ((d0 & 0xffffffff00000000ull) | dA) + 1024, 1);
        wg_commit();
        if (i == 2) {
          wg_wait<1>();
          reg_fence<32>(Q);
          const uint32_t qs = sb + SM_STASH + wg * 16384 + wq * 2048 + lane * 16;
#pragma unroll
          for (int j = 0; j < 8; j++) { const uint4 v = lds128(qs + (j & 3) * 512 + (j >> 2) * 8192); Q[4 * j] = v.x; Q[4 * j + 1] = v.y; Q[4 * j + 2] = v.z; Q[4 * j + 3] = v.w; }
        }
        TA(10);
        if (i == 3) { lp0 = z.l0; lp1 = z.l1; row_rcp(lp0, lp1); softmax_start(z); }
        TA(7);
        so ^= 16; dB ^= dBx; dA ^= dAx;
        ready = mbar_test(sb + BAR_FULL1 + 8 + so, ph);
        softmax_half(SL, PL, O, z, i == 3, tag);
        TA(8);
        wg_wait<0>();
        TA(9);
        reg_fence<32>(SH); reg_fence<16>(PH); reg_fence<64>(O); reg_fence<32>(Q);
        if ((tid & 127) < 2) mbar_arrive_cl(rel + BAR_EMPTY1 + so);
      }
      TAFLUSH();
      TR(9);
      {
        if (!ready) mbar_wait(sb + BAR_FULL1 + 8 * 3, ph);
        ph ^= 1;
        const uint64_t dv = d0 + 3 * (ST1 >> 4);
        wg_fence();
        issue_pv(O, PL, dv, 1);
        wg_commit();
        bb_fence(tag);
        softmax_half(SH, PH, O, z, false, tag);
        wg_fence();
        issue_pv(O, PH, dv + 1024, 1);
        wg_commit();
        TR(10);
        row_rcp(z.l0, z.l1);
        mbar_wait(sb + (pair ? BAR_X : BAR_STASH) + 8 * wg, 0);
#pragma unroll
        for (int kk = 0; kk < 8; kk++) ldsm4((stsm_addr + (kk >> 2) * 8192) ^ ((kk & 3) * 32), X + 4 * kk);
        reg_fence<32>(X);
        __syncwarp();
        wg_wait<0>();
        reg_fence<64>(O);
        TR(11);
        if ((tid & 127) < 2) mbar_arrive_cl(rel + BAR_EMPTY1 + 8 * 3);
        stage_o(O, z.l0, z.l1, stsm_addr);
        nb_arrive(NB_OST + wg, 160);
      }
      TR(12);
      if (tid == 0) { TS(9 + pair * 2); TSC(62); }
      if (pair == 1) break;
      {
        mbar_wait(sb + BAR_FULL1, ph);
        const uint64_t da = mk_desc(sb + SM_RING + wg * 8192, 16), db = mk_desc(sb + SM_RING + 16384, 8192);
        wg_fence();
        wgmma_ss256_z<1>(acc, da, db);
#pragma unroll
        for (int kk = 1; kk < 4; kk++) wgmma_ss256<1>(acc, da + kk * 2, db + kk * 128, 1);
        wg_commit();
      }
#pragma unroll 1
      for (int kt = 1; kt < 16; kt++) {
        const uint32_t s = kt & 3;
        if (s == 0) ph ^= 1;
        mbar_wait(sb + BAR_FULL1 + 8 * s, ph);
        const uint32_t st = sb + SM_RING + s * ST1;
        const uint64_t da = mk_desc(st + wg * 8192, 16), db = mk_desc(st + 16384, 8192);
        wg_fence();
#pragma unroll
        for (int kk = 0; kk < 4; kk++) wgmma_ss256<1>(acc, da + kk * 2, db + kk * 128, 1);
        wg_commit();
        wg_wait<1>();
        if ((tid & 127) < 2) mbar_arrive_cl(rel + BAR_EMPTY1 + 8 * ((s + 3) & 3));
      }
      ph ^= 1;
      wg_wait<0>();
      reg_fence<128>(acc);
      TR(13);
    }

    uint4 WG[16], WU[16];
    const int fp = 64 * warp + 8 * g + t;
    uint32_t fsb0, fsb1, fcb0, fcb1, fgb0, fgb1;
    const uint32_t gu_base = sb + SM_RING + (warp >> 1) * ST1 + 32768 + (warp & 1) * 8192;
    const uint32_t gu_addr = gu_base + t * 128 + (g & 1) * 64 + ((g >> 1) ^ t) * 16;
    {
      const uint64_t da0 = mk_desc(sb + SM_RING + __shfl_sync(0xffffffffu, wg, 0) * 8192, 16), db0 = mk_desc(sb + SM_RING + 16384, 8192);
#pragma unroll
      for (int n = 0; n < 4 + 5 * X_PEEL; n++) {
        const int s = n < 4 ? n : (n - 4) % 5;
        mbar_wait(sb + BAR_FULL1 + 8 * s, n < 4 ? 0 : ((n - 4) / 5 + (s < 4)) & 1);
        if (n < 4) TSX(40 + wg * 6 + n);
        const uint64_t da = da0 + s * (ST1 >> 4), db = db0 + s * (ST1 >> 4);
        wg_fence();
        if (n == 0) wgmma_ss128_z<1>(acc, da, db); else wgmma_ss128<1>(acc, da, db, 1);
#pragma unroll
        for (int kk = 1; kk < 4; kk++) wgmma_ss128<1>(acc, da + kk * 2, db + kk * 128, 1);
        wg_commit();
        if (n == 1) {
          mbar_wait(sb + BAR_OF, 0);
          const uint2* mp = &g_mod[3 * 512 + fp];
          fsb0 = ld_pkt8(mp).x; fsb1 = ld_pkt8(mp + 4).x; fcb0 = ld_pkt8(mp + 512).x; fcb1 = ld_pkt8(mp + 516).x;
          fgb0 = ld_pkt8(mp + 1024).x; fgb1 = ld_pkt8(mp + 1028).x;
        }
        if (n == 0 && b < NFFN) mbar_wait(sb + BAR_FFN, 0);
        {
          constexpr int NT = 4 + 5 * X_PEEL, F0 = NT > 16 ? NT - 16 : 0;
#pragma unroll
          for (int i = 0; i < 16; i++) if (F0 + i * (NT - F0) / 16 == n) WG[i] = lds128(gu_addr + i * 512);
        }
        if (n > 0) {
          wg_wait<1>();
          if ((tid & 127) < 2) mbar_arrive_cl(rel + BAR_EMPTY1 + 8 * (n == 4 ? 3 : s ? s - 1 : 4));
        }
      }
      TSX(44 + wg * 6);
      {
        uint32_t dep = 0;
#pragma unroll
        for (int i = 0; i < 16; i++) dep ^= WG[i].x;
        if (__shfl_sync(0xffffffffu, tag, dep & 31) == tag && lane == 2) mbar_arrive(sb + BAR_TFREE);
      }
#pragma unroll 1
      for (int r = X_PEEL; r < 12; r++) {
#pragma unroll
        for (int s = 0; s < 5; s++) {
          mbar_wait(sb + BAR_FULL1 + 8 * s, (r + (s < 4)) & 1);
          const uint64_t da = da0 + s * (ST1 >> 4), db = db0 + s * (ST1 >> 4);
          wg_fence();
#pragma unroll
          for (int kk = 0; kk < 4; kk++) wgmma_ss128<1>(acc, da + kk * 2, db + kk * 128, 1);
          wg_commit();
          wg_wait<1>();
          if ((tid & 127) < 2) mbar_arrive_cl(rel + BAR_EMPTY1 + 8 * (s ? s - 1 : (r == 0 ? 3 : 4)));
        }
      }
    }
    mbar_wait(sb + BAR_VEC, 0);
    const int lrow = warp * 16 + g;
    uint2 ga[8], b1[8];
#pragma unroll
    for (int kk = 0; kk < 8; kk++) { ga[kk] = lds64(sb + SM_GA + kk * 32 + t * 8); b1[kk] = lds64(sb + SM_B1 + min(g, 3) * 32 + t * 8 + kk * 128); }
    uint4* const stp = &g_stats[b * 128 + lrow + 8 * t];
    bb_fence(tag);
    wg_wait<0>();
    reg_fence<64>(acc);
    if (tid == 0) { TS(12); TSC(63); }

    TT(0);
    {
      float d1[4] = {0.f, 0.f, 0.f, 0.f}, d2[4] = {0.f, 0.f, 0.f, 0.f}, d3[4] = {0.f, 0.f, 0.f, 0.f};
      float d4[4] = {0.f, 0.f, 0.f, 0.f}, d5[4] = {0.f, 0.f, 0.f, 0.f};
#pragma unroll
      for (int kk = 0; kk < 8; kk++) {
        uint32_t* x = X + 4 * kk;
        x[0] = hfma2(ga[kk].x, pack2(acc[8 * kk + 0], acc[8 * kk + 1]), x[0]);
        x[1] = hfma2(ga[kk].x, pack2(acc[8 * kk + 2], acc[8 * kk + 3]), x[1]);
        x[2] = hfma2(ga[kk].y, pack2(acc[8 * kk + 4], acc[8 * kk + 5]), x[2]);
        x[3] = hfma2(ga[kk].y, pack2(acc[8 * kk + 6], acc[8 * kk + 7]), x[3]);
        mma16816(d1, x, b1[kk].x, b1[kk].y);
        mma1688(d2, x[0], x[1], x[0]); mma1688(d3, x[0], x[1], x[1]);
        mma1688(d4, x[2], x[3], x[2]); mma1688(d5, x[2], x[3], x[3]);
      }
      const int qb = lane & 28;
      const float q0 = __shfl_sync(0xffffffffu, (g & 1) ? d2[1] + d4[1] : d2[0] + d4[0], qb | (g >> 1));
      const float q1 = __shfl_sync(0xffffffffu, (g & 1) ? d3[3] + d5[3] : d3[2] + d5[2], qb | (g >> 1));
      const float e0 = __shfl_xor_sync(0xffffffffu, t ? d1[0] : d1[3], 1);
      const float e1 = __shfl_sync(0xffffffffu, d1[2], qb);
      if (t < 2) st_pkt16(stp, __float_as_uint(t ? e1 : d1[0]), __float_as_uint(t ? q1 : q0),
                          __float_as_uint((t ? d1[2] : d1[1]) + e0), tag);
    }
    TSY(13);
    TT(1);
    float mb, rd, den, br;
    {
      const uint4* sp = &g_stats[(rt * 8 + 4 * (t & 1)) * 128 + lrow + 4 * (t & 2)];
      mbar_wait(sb + BAR_EMPTY1 + 8 * 3, 0);
#pragma unroll
      for (int kk = 0; kk < 8; kk++) stsm4((stsm_addr - SM_STASH + SM_X2 + (kk >> 2) * 8192) ^ ((kk & 3) * 32), X[4 * kk], X[4 * kk + 1], X[4 * kk + 2], X[4 * kk + 3]);
      if (b < NFFN) mbar_wait(sb + BAR_FFN, 1);
#pragma unroll
      for (int i = 0; i < WU1; i++) WU[i] = lds128(gu_addr + i * 512);
      bb_fence(tag);
      TT(2);
      uint4 v0, v1, v2, v3;
      int it = 0;
      do { v0 = ld_pkt16(sp); v1 = ld_pkt16(sp + 128); v2 = ld_pkt16(sp + 256); v3 = ld_pkt16(sp + 384); spin_guard(it); }
        while (!(__all_sync(0xffffffffu, v0.w == tag && v1.w == tag && v2.w == tag && v3.w == tag)));
      TT(3);
      float sm = (__uint_as_float(v0.x) + __uint_as_float(v1.x)) + (__uint_as_float(v2.x) + __uint_as_float(v3.x));
      float sq = (__uint_as_float(v0.y) + __uint_as_float(v1.y)) + (__uint_as_float(v2.y) + __uint_as_float(v3.y));
      float dt = (__uint_as_float(v0.z) + __uint_as_float(v1.z)) + (__uint_as_float(v2.z) + __uint_as_float(v3.z));
      sm += __shfl_xor_sync(0xffffffffu, sm, 1); sq += __shfl_xor_sync(0xffffffffu, sq, 1); dt += __shfl_xor_sync(0xffffffffu, dt, 1);
      const uint2 scal = lds64(sb + SM_SCAL);
      const float mu = sm * (1.f / 1024.f);
      mb = rbf(mu);
      den = rbf(sqrt_f(rbf(rbf(fmaxf(fmaf(-mu, mu, sq * (1.f / 1024.f)), 0.f)) + 1e-5f)));
      rd = rcp_f(den);
      br = fmaf(fmaf(-mb, __uint_as_float(scal.x), dt), rd, __uint_as_float(scal.y));
    }
    TSY(14);
    TT(4);
    {
      const int rb = __float_as_int(br);
      const int key = ((rb ^ ((rb >> 31) & 0x7fffffff)) | 127) - (lrow + 4 * (t & 2));
      if (key == __reduce_max_sync(0xffffffffu, key)) sts64(sb + SM_AMAX + warp * 8, (uint32_t)key, pack2(mb, den));
      __syncwarp();
      nb_arrive(NB_AMAX, 288);
    }
    TT(5);
    const uint4* ep = &g_entry[(warp * 16 + (lane & 15)) * ESTR];
    const uint32_t slot = sb + SM_STASH + wg * 8192 + (tid & 127) * 16;
    cp_async16(slot, ep);
    {
      const float rh = rbf(rd);
      const uint32_t u = pack2(-mb * rh, rh);
      const int qb = lane & 28;
      const uint32_t u0 = __shfl_sync(0xffffffffu, u, qb), u1 = __shfl_sync(0xffffffffu, u, qb | 2);
      const uint32_t m0 = __byte_perm(u0, 0, 0x1010), h0 = __byte_perm(u0, 0, 0x3232);
      const uint32_t m1 = __byte_perm(u1, 0, 0x1010), h1 = __byte_perm(u1, 0, 0x3232);
#pragma unroll
      for (int j = 0; j < 16; j++) {
        const uint4 rec = lds128(sb + SM_REC + (4 * j + t) * 16);
        X[2 * j] = hfma2(rec.z, hfma2(hfma2(X[2 * j], h0, m0), rec.x, rec.y), X[2 * j]);
        X[2 * j + 1] = hfma2(rec.z, hfma2(hfma2(X[2 * j + 1], h1, m1), rec.x, rec.y), X[2 * j + 1]);
      }
#pragma unroll
      for (int kk = 0; kk < 8; kk++) stsm4((stsm_addr - SM_STASH + SM_OUT + (kk >> 2) * 8192) ^ ((kk & 3) * 32), X[4 * kk], X[4 * kk + 1], X[4 * kk + 2], X[4 * kk + 3]);
    }
    cp_async_wait();
    uint4 ent = lds128(slot);
    TSY(16);
    TT(6);
    int wrow;
    uint32_t xs0, xs1, hs0, hs1;
    uint32_t WD[64];
    const uint32_t wd_addr = sb + SM_RING + wg * ST1 + wq * 8192 + ((lane & 7) + ((lane >> 4) << 3)) * 128 + ((((lane >> 3) & 1) ^ (lane & 7)) * 16);
    {
      int gmax;
      auto leader = [&]() {
        gmax = __reduce_max_sync(0xffffffffu, ent.w == tag ? (int)ent.x : (int)0x8000000f);
        return ~gmax & 15;
      };
      int wt = leader(), it = 0;
      TT(7);
      nb_arrive(NB_OST + wg, 160);
      TT(8);
      cp_async16(slot + 2048, &g_cand[(wt * 8 + warp) * 32 + lane]);
      if (ent.w != tag) cp_async16(slot, ep);
#pragma unroll
      for (int i = WU1; i < 16; i++) WU[i] = lds128(gu_addr + i * 512);
      if (b < NFFN) mbar_wait(sb + BAR_FFN + 8, 0);
#pragma unroll
      for (int mt = 0; mt < 8; mt++)
#pragma unroll
        for (int s = 0; s < 2; s++) ldsm4t((wd_addr + (mt >> 2) * 4096 + s * 2048) ^ ((mt & 3) * 32), WD + (mt * 2 + s) * 4);
      cp_async_wait();
      uint4 v = lds128(slot + 2048);
      ent = lds128(slot);
      TT(9);
      while (true) {
        const int have = wt;
        wt = leader();
        if (__all_sync(0xffffffffu, ent.w == tag && have == wt && v.z == tag)) break;
        v = ld_pkt16(&g_cand[(wt * 8 + warp) * 32 + lane]);
        if (ent.w != tag) ent = ld_pkt16(ep);
        spin_guard(it);
      }
      TT(10);
      ent.x = gmax ^ ((gmax >> 31) & 0x7fffffff);
      wrow = __shfl_sync(0xffffffffu, ent.y, wt); ent.z = __shfl_sync(0xffffffffu, ent.z, wt);
      xs0 = v.x; xs1 = v.y;
      const uint32_t mm = __byte_perm(ent.z, 0, 0x1010);
      const float rs = rcp_f(hi2f(ent.z));
      const uint32_t e0 = hsub2(xs0, mm), e1 = hsub2(xs1, mm);
      hs0 = hfma2(pack2(lo2f(e0) * rs, hi2f(e0) * rs), hadd2(fcb0, ONE2), fsb0);
      hs1 = hfma2(pack2(lo2f(e1) * rs, hi2f(e1) * rs), hadd2(fcb1, ONE2), fsb1);
    }
    if ((tid & 127) == 0) sts32(sb + SM_WROW + 4 * wg, wrow);
    nb_arrive(NB_WIN + wg, 160);
    TSY(17);
    TT(11);
    if (b < NFFN) {
      float da[4][4];
#pragma unroll
      for (int i = 0; i < 4; i++) { da[i][0] = da[i][1] = da[i][2] = da[i][3] = 0.f; }
      const uint32_t selv = ((g & 1) ? 0x1044 : 0x4410) + ((g & 4) ? ((g & 1) ? 0x2200 : 0x0022) : 0);
      const uint32_t sel0 = (g & 2) ? 0x4444 : selv, sel1 = (g & 2) ? selv : 0x4444;
#pragma unroll
      for (int s = 0; s < 16; s++) {
        const uint32_t v = __shfl_sync(0xffffffffu, (s & 1) ? hs1 : hs0, 4 * (s >> 1) + t);
        const uint32_t b0 = __byte_perm(v, 0, sel0), b1 = __byte_perm(v, 0, sel1);
        const uint32_t a0[4] = {WG[s].x, WG[s].y, WG[s].z, WG[s].w};
        const uint32_t a1[4] = {WU[s].x, WU[s].y, WU[s].z, WU[s].w};
        mma16816(da[(s & 1) * 2], a0, b0, b1);
        mma16816(da[(s & 1) * 2 + 1], a1, b0, b1);
      }
      {
        float v[4];
#pragma unroll
        for (int i = 0; i < 4; i++) {
          const float vg = da[0][i] + da[2][i], vu = da[1][i] + da[3][i];
          v[i] = ((g & 1) ? vu : vg) + __shfl_xor_sync(0xffffffffu, (g & 1) ? vg : vu, 6);
        }
        if ((t >> 1) == (g & 1))
          sts128(gu_base + (g & 1) * 128 + (g >> 1) * 32 + (t & 1) * 16, __float_as_uint(v[0]), __float_as_uint(v[1]), __float_as_uint(v[2]), __float_as_uint(v[3]));
      }
      TT(12);
      nb_sync(NB_CONS, 256);
      float gp[8], up[8];
#pragma unroll
      for (int w = 0; w < 8; w++) {
        const uint32_t a = sb + SM_RING + (w >> 1) * ST1 + 32768 + (w & 1) * 8192 + lane * 4;
        gp[w] = lds_f32(a); up[w] = lds_f32(a + 128);
      }
      const float gsum = ((gp[0] + gp[1]) + (gp[2] + gp[3])) + ((gp[4] + gp[5]) + (gp[6] + gp[7]));
      const float usum = ((up[0] + up[1]) + (up[2] + up[3])) + ((up[4] + up[5]) + (up[6] + up[7]));
      const float act = rbf(silu_f(rbf(gsum))) * rbf(usum);
      TT(13);
      const uint32_t ap = pack2(act, __shfl_down_sync(0xffffffffu, act, 1));
      const uint32_t b00 = __shfl_sync(0xffffffffu, ap, 2 * t), b01 = __shfl_sync(0xffffffffu, ap, 2 * t + 8);
      const uint32_t b10 = __shfl_sync(0xffffffffu, ap, 2 * t + 16), b11 = __shfl_sync(0xffffffffu, ap, 2 * t + 24);
      float y[8][4];
#pragma unroll
      for (int mt = 0; mt < 8; mt++) {
        y[mt][0] = y[mt][1] = y[mt][2] = y[mt][3] = 0.f;
        mma16816(y[mt], WD + (mt * 2) * 4, b00, b01);
        mma16816(y[mt], WD + (mt * 2 + 1) * 4, b10, b11);
      }
#pragma unroll
      for (int e = 0; e < 2; e++) {
        const float v0 = t == 0 ? y[e][0] : t == 1 ? y[2 + e][0] : t == 2 ? y[4 + e][0] : y[6 + e][0];
        const float v1 = t == 0 ? y[e][2] : t == 1 ? y[2 + e][2] : t == 2 ? y[4 + e][2] : y[6 + e][2];
        const int f = 16 * warp + 2 * (2 * t + e) + (g >> 2);
        st_pkt16(&g_ypart[(f * NFFN + b) * 4 + (g & 3)], __float_as_uint(v0), __float_as_uint(v1), tag, 0);
      }
    }
    TSY(18);
    TT(14);
    {
      const int pw = warp - (warp > (b >> 4));
      if (warp != (b >> 4)) {
        const uint4* yp = &g_ypart[b * NFFN * 4 + pw * 64 + lane];
        uint4 v0, v1;
        int it = 0;
        { const uint32_t c1 = clock(); while ((uint32_t)clock() - c1 < (b < NFFN ? YD : YD + 1500)) {} }
        do { v0 = ld_pkt16(yp); v1 = ld_pkt16(yp + 32); spin_guard(it); }
        while (!(__all_sync(0xffffffffu, v0.z == tag && v1.z == tag)));
        float y0 = __uint_as_float(v0.x) + __uint_as_float(v1.x), y1 = __uint_as_float(v0.y) + __uint_as_float(v1.y);
#pragma unroll
        for (int o = 4; o <= 16; o <<= 1) { y0 += __shfl_xor_sync(0xffffffffu, y0, o); y1 += __shfl_xor_sync(0xffffffffu, y1, o); }
        if (lane < 4) sts64(sb + SM_YRED + pw * 32 + lane * 8, __float_as_uint(y0), __float_as_uint(y1));
      }
    }
    TT(15);
    if (warp != (b >> 4)) {
      nb_arrive(NB_CONS, 256);
    } else {
      nb_sync(NB_CONS, 256);
      float y0 = 0.f, y1 = 0.f;
      if (lane < 28) { const uint2 e = lds64(sb + SM_YRED + lane * 8); y0 = __uint_as_float(e.x); y1 = __uint_as_float(e.y); }
#pragma unroll
      for (int o = 4; o <= 16; o <<= 1) { y0 += __shfl_xor_sync(0xffffffffu, y0, o); y1 += __shfl_xor_sync(0xffffffffu, y1, o); }
      const int src = 2 * (t & 1);
      const float ya = __shfl_sync(0xffffffffu, y0, src), yb = __shfl_sync(0xffffffffu, y0, src + 1);
      const float yc = __shfl_sync(0xffffffffu, y1, src), yd = __shfl_sync(0xffffffffu, y1, src + 1);
      if (g == ((b >> 1) & 7) && (t >> 1) == (b & 1)) {
        const float rs = rbf(__uint_as_float(ent.x));
        const float sg = sigmoid_f(rs);
        const uint32_t sg2 = pack2(sg, sg);
        const uint32_t o0 = hadd2(xs0, hmul2(fgb0, hadd2(hs0, hmul2(pack2(ya, yb), sg2))));
        const uint32_t o1 = hadd2(xs1, hmul2(fgb1, hadd2(hs1, hmul2(pack2(yc, yd), sg2))));
        uint32_t* op = reinterpret_cast<uint32_t*>(p.out + (size_t)wrow * 1024) + fp;
        op[0] = o0; op[4] = o1;
      }
      if (b == 0) {
        if (lane < 8) st_relaxed(&p.sc->ticket[lane * 32], 0);
        st_relaxed(&p.sc->epoch[lane], tag);
      }
      if (lane == 0) TS(19);
    }
  }
}

typedef CUresult (*EncodeFn)(CUtensorMap*, CUtensorMapDataType, cuuint32_t, void*, const cuuint64_t*, const cuuint64_t*,
                             const cuuint32_t*, const cuuint32_t*, CUtensorMapInterleave, CUtensorMapSwizzle,
                             CUtensorMapL2promotion, CUtensorMapFloatOOBfill);

CUtensorMap make_map(EncodeFn enc, const void* ptr, uint64_t rows, uint64_t cols, uint32_t box_rows, uint32_t box_cols, CUtensorMapSwizzle sw) {
  CUtensorMap m;
  cuuint64_t dims[2] = {cols, rows};
  cuuint64_t strides[1] = {cols * 2};
  cuuint32_t box[2] = {box_cols, box_rows};
  cuuint32_t es[2] = {1, 1};
  enc(&m, CU_TENSOR_MAP_DATA_TYPE_BFLOAT16, 2, const_cast<void*>(ptr), dims, strides, box, es, CU_TENSOR_MAP_INTERLEAVE_NONE, sw,
      CU_TENSOR_MAP_L2_PROMOTION_L2_128B, CU_TENSOR_MAP_FLOAT_OOB_FILL_NONE);
  return m;
}

CUtensorMap make_map3(EncodeFn enc, const void* ptr, uint64_t rows, uint64_t cols, uint32_t box_rows, uint32_t box_blks) {
  CUtensorMap m;
  cuuint64_t dims[3] = {64, rows, cols / 64};
  cuuint64_t strides[2] = {cols * 2, 128};
  cuuint32_t box[3] = {64, box_rows, box_blks};
  cuuint32_t es[3] = {1, 1, 1};
  enc(&m, CU_TENSOR_MAP_DATA_TYPE_BFLOAT16, 3, const_cast<void*>(ptr), dims, strides, box, es, CU_TENSOR_MAP_INTERLEAVE_NONE,
      CU_TENSOR_MAP_SWIZZLE_128B, CU_TENSOR_MAP_L2_PROMOTION_L2_128B, CU_TENSOR_MAP_FLOAT_OOB_FILL_NONE);
  return m;
}

}

extern "C" void kernel_launch(void* const* d_in, const int* in_sizes, int n_in, void* d_out, int out_size) {
  (void)in_sizes; (void)n_in; (void)out_size;
  Params p;
  p.x = (const bf16*)d_in[0]; p.kc = (const bf16*)d_in[1]; p.vc = (const bf16*)d_in[2];
  p.wq = (const bf16*)d_in[3]; p.wo = (const bf16*)d_in[4]; p.w_r = (const bf16*)d_in[6];
  p.wg = (const bf16*)d_in[7]; p.wu = (const bf16*)d_in[8]; p.wd = (const bf16*)d_in[9];
  p.c = (const bf16*)d_in[10]; p.w_mod = (const bf16*)d_in[11]; p.out = (bf16*)d_out;

  void* fn = nullptr;
  cudaDriverEntryPointQueryResult st;
  cudaGetDriverEntryPoint("cuTensorMapEncodeTiled", &fn, cudaEnableDefault, &st);
  EncodeFn enc = (EncodeFn)fn;
  void* scp = nullptr;
  cudaGetSymbolAddress(&scp, g_scratch);
  p.sc = (Scratch*)scp;
  void *hp = p.sc->h, *op = p.sc->o;
  const CUtensorMapSwizzle S128 = CU_TENSOR_MAP_SWIZZLE_128B;
  CUtensorMap mH = make_map(enc, hp, 2048, 1024, 64, 64, S128);
  CUtensorMap mWq = make_map3(enc, p.wq, 1024, 4096, 64, 4);
  CUtensorMap mK = make_map(enc, p.kc, 8192, 128, 64, 64, S128);
  CUtensorMap mV = make_map(enc, p.vc, 8192, 128, 64, 64, S128);
  CUtensorMap mO = make_map(enc, op, 2048, 4096, 64, 64, S128);
  CUtensorMap mWo = make_map3(enc, p.wo, 4096, 1024, 64, 2);
  CUtensorMap mX = make_map(enc, p.x, 2048, 1024, 64, 64, S128);
  CUtensorMap mOut = make_map(enc, p.out, 2048, 1024, 64, 64, S128);
  CUtensorMap mWg = make_map(enc, p.wg, 1024, 3584, 256, 32, CU_TENSOR_MAP_SWIZZLE_64B);
  CUtensorMap mWu = make_map(enc, p.wu, 1024, 3584, 256, 32, CU_TENSOR_MAP_SWIZZLE_64B);
  CUtensorMap mWd = make_map3(enc, p.wd, 3584, 1024, 32, 8);
  CUtensorMap mWm = make_map(enc, p.w_mod, 1024, 6144, 16, 256, CU_TENSOR_MAP_SWIZZLE_NONE);
  CUtensorMap mWh = make_map(enc, p.w_mod, 1024, 6144, 256, 32, CU_TENSOR_MAP_SWIZZLE_64B);
  CUtensorMap mWs = make_map(enc, p.w_mod, 1024, 6144, 128, 128, CU_TENSOR_MAP_SWIZZLE_NONE);
  cudaFuncSetAttribute(fused_kernel, cudaFuncAttributeMaxDynamicSharedMemorySize, SMEM_BYTES);
  fused_kernel<<<NCTA, NTHREADS, SMEM_BYTES>>>(p, mH, mWq, mK, mV, mO, mWo, mX, mOut, mWg, mWu, mWd, mWm, mWs, mWh);
}
```

```cpp
#include <cuda_runtime.h>
#include <cuda_bf16.h>
#include <cuda.h>
#include <stdint.h>
#include <stddef.h>

#define UPD 200
#define GATED 700
#define WL 3500
#define XD 0
#define PLD 200
#define ESTR 8
#define HD 6000
#define YD 500
#define SPT 5000
#define PFW 100
#define X_PEEL 1
#define WU1 12

namespace {

typedef __nv_bfloat16 bf16;

constexpr int NTHREADS = 384;
constexpr int NMAIN = 128;
constexpr int NCTA = 132;
#define RS 8
constexpr int RV = 16 * RS + 64;
constexpr int NREP = 4;
constexpr int NFFN = 112;

constexpr uint32_t SM_RING = 0;
constexpr uint32_t ST1 = 49152;
constexpr uint32_t ST2 = 32768;
constexpr int NST2 = 6;
constexpr uint32_t SM_STASH = 196608;
constexpr uint32_t SM_MISC = 229376;
constexpr uint32_t BAR_FULL1 = SM_MISC + 0;
constexpr uint32_t BAR_EMPTY1 = SM_MISC + 40;
constexpr uint32_t BAR_FULL2 = SM_MISC + 0;
constexpr uint32_t BAR_EMPTY2 = SM_MISC + 48;
constexpr uint32_t BAR_STASH = SM_MISC + 160;
constexpr uint32_t BAR_SFREE = SM_MISC + 176;
constexpr uint32_t BAR_TFREE = SM_MISC + 184;
constexpr uint32_t BAR_FFN = SM_MISC + 192;
constexpr uint32_t BAR_VEC = SM_MISC + 208;
constexpr uint32_t BAR_RED = SM_MISC + 216;
constexpr uint32_t BAR_XH = SM_MISC + 152;
constexpr uint32_t BAR_HS = SM_MISC + 80;
constexpr uint32_t BAR_G = SM_MISC + 112;
constexpr uint32_t BAR_T1 = SM_MISC + 120;
constexpr uint32_t BAR_HF = SM_MISC + 128;
constexpr uint32_t BAR_X = SM_MISC + 136;
constexpr uint32_t BAR_OF = SM_MISC + 224;
constexpr uint32_t BAR_ROLE = SM_MISC + 240;
constexpr uint32_t SM_ROLE = SM_MISC + 248;
constexpr uint32_t SM_GA = SM_MISC + 256;
constexpr uint32_t SM_SCAL = SM_MISC + 512;
constexpr uint32_t SM_WROW = SM_MISC + 520;
constexpr uint32_t SM_AMAX = SM_MISC + 528;
constexpr uint32_t SM_YRED = SM_MISC + 656;
constexpr uint32_t SM_X2 = 2 * ST1, SM_OUT = 3 * ST1;
constexpr uint32_t SM_REC = SM_MISC + 1024;
constexpr uint32_t BAR_TAB = SM_MISC + 1000;
constexpr uint32_t BAR_CAND = SM_MISC + 880;
constexpr uint32_t SM_CAND = SM_MISC + 888;
constexpr uint32_t BAR_WH = SM_MISC + 960;
constexpr uint32_t SM_WSLAB = 2 * 49152 + 16384;
constexpr uint32_t SM_XROW = 2 * 49152;
constexpr uint32_t SM_RED = SM_MISC + 2048;
constexpr uint32_t SM_B1 = SM_MISC + 2048;
constexpr uint32_t SMEM_BYTES = 232448;

constexpr int NB_CONS = 1, NB_WIN = 2  , NB_OST = 4  , NB_AMAX = 6;

struct __align__(1024) Scratch {
  uint32_t epoch[32];
  uint32_t hflag[16 * 32];
  uint32_t oflag[64 * 32];
  uint2 vdone[4 * 16];
  uint32_t pad[96 + 512];
  uint32_t ticket[8 * 32];
  uint2 mod[3072];
  uint4 rec[2][NREP][2 * RV];
  uint4 lnst[1024];
  uint4 entry[8 * 16 * 8];
  uint4 cand[16 * 8 * 32];
  uint4 stats[16 * 8 * 128];
  uint4 ypart[128 * NFFN * 4];
  unsigned long long ts[NCTA * 64];
  uint16_t h[2048 * 1024];
  uint16_t o[2048 * 4096];
};
__device__ Scratch g_scratch;
#define g_epoch (p.sc->epoch[0])
#define g_hflag (p.sc->hflag)
#define g_oflag (p.sc->oflag)
#define g_mod (p.sc->mod)
#define g_entry (p.sc->entry)
#define g_cand (p.sc->cand)
#define g_stats (p.sc->stats)
#define g_ypart (p.sc->ypart)
#define g_vdone (p.sc->vdone)
#define g_lnst (p.sc->lnst)
#define g_rec (p.sc->rec)
#define g_ts (p.sc->ts)
#define g_h (p.sc->h)

struct Params {
  const bf16* w_mod; const bf16* c; Scratch* sc; const bf16* x; const bf16* w_r; bf16* out;
  const bf16* wq; const bf16* wo; const bf16* wg; const bf16* wu; const bf16* wd; const bf16* kc; const bf16* vc;
};

__device__ __forceinline__ uint32_t smem_u32(const void* p) { return (uint32_t)__cvta_generic_to_shared(p); }
__device__ __forceinline__ void mbar_init(uint32_t bar, uint32_t cnt) { asm volatile("mbarrier.init.shared::cta.b64 [%0], %1;" :: "r"(bar), "r"(cnt) : "memory"); }
__device__ __forceinline__ void mbar_expect_tx(uint32_t bar, uint32_t bytes) { asm volatile("mbarrier.arrive.expect_tx.shared::cta.b64 _, [%0], %1;" :: "r"(bar), "r"(bytes) : "memory"); }
__device__ __forceinline__ void mbar_arrive(uint32_t bar) { asm volatile("mbarrier.arrive.shared::cta.b64 _, [%0];" :: "r"(bar) : "memory"); }
__device__ __forceinline__ void mbar_arrive_cl(uint32_t cluster_addr) { asm volatile("mbarrier.arrive.shared::cluster.b64 _, [%0];" :: "r"(cluster_addr) : "memory"); }
__device__ __forceinline__ uint32_t mapa(uint32_t addr, uint32_t cta) { uint32_t r; asm("mapa.shared::cluster.u32 %0, %1, %2;" : "=r"(r) : "r"(addr), "r"(cta)); return r; }
__device__ __forceinline__ bool mbar_test(uint32_t bar, uint32_t parity) {
  uint32_t ok;
  asm volatile("{\n.reg .pred p;\nmbarrier.test_wait.parity.shared::cta.b64 p, [%1], %2;\nselp.u32 %0, 1, 0, p;\n}" : "=r"(ok) : "r"(bar), "r"(parity) : "memory");
  return ok;
}
constexpr int SPIN_LIMIT = 300000;
__device__ __forceinline__ void spin_guard(int& it) {
  asm volatile("{\n.reg .pred p;\n.reg .b64 z;\nadd.s32 %0, %0, 1;\nsetp.gt.s32 p, %0, %1;\nmov.b64 z, 0;\n@p st.volatile.global.u32 [z], %0;\n}" : "+r"(it) : "n"(SPIN_LIMIT));
}
__device__ __forceinline__ void mbar_wait_g(uint32_t bar, uint32_t parity) {
  asm volatile("{\n.reg .pred p, q;\n.reg .b32 c;\n.reg .b64 z;\nmov.b32 c, 0;\nmov.b64 z, 0;\nMW_LOOP:\n"
               "mbarrier.try_wait.parity.shared::cta.b64 p, [%0], %1;\nadd.s32 c, c, 1;\nsetp.gt.s32 q, c, %2;\n"
               "@q st.volatile.global.u32 [z], c;\n@!p bra MW_LOOP;\n}" :: "r"(bar), "r"(parity), "n"(SPIN_LIMIT) : "memory");
}
__device__ __forceinline__ void mbar_wait(uint32_t bar, uint32_t parity) {
  asm volatile("{\n.reg .pred p;\nMW_LOOP:\nmbarrier.try_wait.parity.shared::cta.b64 p, [%0], %1;\n@!p bra MW_LOOP;\n}" :: "r"(bar), "r"(parity) : "memory");
}
__device__ __forceinline__ void bb_fence(uint32_t v) {
  asm volatile("{\n.reg .pred p;\n.reg .u32 c;\nsetp.ne.u32 p, %0, 0;\n@p bra.uni BF_DONE;\nBF_LOOP:\nnanosleep.u32 1;\nmov.u32 c, %%clock;\nsetp.eq.u32 p, c, 0;\n@p bra.uni BF_LOOP;\nBF_DONE:\n}" :: "r"(v) : "memory");
}
__device__ __forceinline__ bool elect_one() {
  uint32_t pred;
  asm volatile("{\n.reg .pred P;\nelect.sync _|P, 0xffffffff;\nselp.u32 %0, 1, 0, P;\n}" : "=r"(pred));
  return pred;
}
__device__ __forceinline__ void tma_ld(uint32_t dst, const CUtensorMap* m, int c0, int c1, uint32_t bar) {
  asm volatile("cp.async.bulk.tensor.2d.shared::cluster.global.mbarrier::complete_tx::bytes [%0], [%1, {%3, %4}], [%2];"
    :: "r"(dst), "l"(m), "r"(bar), "r"(c0), "r"(c1) : "memory");
}
__device__ __forceinline__ void tma_ld_hint(uint32_t dst, const CUtensorMap* m, int c0, int c1, uint32_t bar, uint64_t pol) {
  asm volatile("cp.async.bulk.tensor.2d.shared::cluster.global.mbarrier::complete_tx::bytes.L2::cache_hint [%0], [%1, {%3, %4}], [%2], %5;"
    :: "r"(dst), "l"(m), "r"(bar), "r"(c0), "r"(c1), "l"(pol) : "memory");
}
__device__ __forceinline__ void tma_ld_mc(uint32_t dst, const CUtensorMap* m, int c0, int c1, uint32_t bar) {
  asm volatile("cp.async.bulk.tensor.2d.shared::cluster.global.mbarrier::complete_tx::bytes.multicast::cluster [%0], [%1, {%3, %4}], [%2], %5;"
    :: "r"(dst), "l"(m), "r"(bar), "r"(c0), "r"(c1), "h"((uint16_t)3) : "memory");
}
__device__ __forceinline__ void tma_ld_mc_hint(uint32_t dst, const CUtensorMap* m, int c0, int c1, uint32_t bar, uint64_t pol) {
  asm volatile("cp.async.bulk.tensor.2d.shared::cluster.global.mbarrier::complete_tx::bytes.multicast::cluster.L2::cache_hint [%0], [%1, {%3, %4}], [%2], %5, %6;"
    :: "r"(dst), "l"(m), "r"(bar), "r"(c0), "r"(c1), "h"((uint16_t)3), "l"(pol) : "memory");
}
__device__ __forceinline__ void tma_ld3_hint(uint32_t dst, const CUtensorMap* m, int row, int blk, uint32_t bar, uint64_t pol) {
  asm volatile("cp.async.bulk.tensor.3d.shared::cluster.global.mbarrier::complete_tx::bytes.L2::cache_hint [%0], [%1, {0, %3, %4}], [%2], %5;"
    :: "r"(dst), "l"(m), "r"(bar), "r"(row), "r"(blk), "l"(pol) : "memory");
}
__device__ __forceinline__ void tma_pf3(const CUtensorMap* m, int row, int blk) {
  asm volatile("cp.async.bulk.prefetch.tensor.3d.L2.global [%0, {0, %1, %2}];" :: "l"(m), "r"(row), "r"(blk) : "memory");
}
__device__ __forceinline__ void tma_st(const CUtensorMap* m, int c0, int c1, uint32_t src) {
  asm volatile("cp.async.bulk.tensor.2d.global.shared::cta.bulk_group [%0, {%2, %3}], [%1];" :: "l"(m), "r"(src), "r"(c0), "r"(c1) : "memory");
}
__device__ __forceinline__ void tma_prefetch_desc(const CUtensorMap* m) { asm volatile("prefetch.tensormap [%0];" :: "l"(m) : "memory"); }
__device__ __forceinline__ void l2_prefetch(const void* p, uint32_t bytes) { asm volatile("cp.async.bulk.prefetch.L2.global [%0], %1;" :: "l"(p), "r"(bytes) : "memory"); }
__device__ __forceinline__ void bulk_commit() { asm volatile("cp.async.bulk.commit_group;" ::: "memory"); }
__device__ __forceinline__ void bulk_wait_read() { asm volatile("cp.async.bulk.wait_group.read 0;" ::: "memory"); }
__device__ __forceinline__ void bulk_wait_all() { asm volatile("cp.async.bulk.wait_group 0;" ::: "memory"); }
__device__ __forceinline__ void fence_async_smem() { asm volatile("fence.proxy.async.shared::cta;" ::: "memory"); }
__device__ __forceinline__ void fence_async_global() { asm volatile("fence.proxy.async.global;" ::: "memory"); }
__device__ __forceinline__ void fence_acquire_gpu() { asm volatile("fence.acquire.gpu;" ::: "memory"); }
__device__ __forceinline__ void fence_release_gpu() { asm volatile("fence.release.gpu;" ::: "memory"); }
__device__ __forceinline__ void st_async_f32x4(uint32_t cluster_addr, const float* v, uint32_t cluster_bar) {
  asm volatile("st.async.weak.shared::cluster.mbarrier::complete_tx::bytes.v4.f32 [%0], {%1,%2,%3,%4}, [%5];"
    :: "r"(cluster_addr), "f"(v[0]), "f"(v[1]), "f"(v[2]), "f"(v[3]), "r"(cluster_bar) : "memory");
}
__device__ __forceinline__ void nb_sync(int id, int n) { asm volatile("bar.sync %0, %1;" :: "r"(id), "r"(n) : "memory"); }
__device__ __forceinline__ void nb_arrive(int id, int n) { asm volatile("bar.arrive %0, %1;" :: "r"(id), "r"(n) : "memory"); }
__device__ __forceinline__ void wg_fence() { asm volatile("wgmma.fence.sync.aligned;" ::: "memory"); }
__device__ __forceinline__ void wg_commit() { asm volatile("wgmma.commit_group.sync.aligned;" ::: "memory"); }
template <int N> __device__ __forceinline__ void wg_wait() { asm volatile("wgmma.wait_group.sync.aligned %0;" :: "n"(N) : "memory"); }
template <int N> __device__ __forceinline__ void reg_fence(float* a) {
#pragma unroll
  for (int i = 0; i < N; i++) asm volatile("" : "+f"(a[i]) :: "memory");
}
template <int N> __device__ __forceinline__ void reg_fence(uint32_t* a) {
#pragma unroll
  for (int i = 0; i < N; i++) asm volatile("" : "+r"(a[i]) :: "memory");
}
__device__ __forceinline__ uint64_t mk_desc(uint32_t addr, uint32_t lbo) {
  return (uint64_t)((addr & 0x3FFFF) >> 4) | ((uint64_t)(lbo >> 4) << 16) | ((uint64_t)(1024 >> 4) << 32) | (1ull << 62);
}

__device__ __forceinline__ uint64_t policy_evict_first() { uint64_t pol; asm("createpolicy.fractional.L2::evict_first.b64 %0, 1.0;" : "=l"(pol)); return pol; }
__device__ __forceinline__ uint32_t ld_relaxed(const uint32_t* p) { uint32_t v; asm volatile("ld.relaxed.gpu.global.u32 %0, [%1];" : "=r"(v) : "l"(p) : "memory"); return v; }
__device__ __forceinline__ void st_relaxed(uint32_t* p, uint32_t v) { asm volatile("st.relaxed.gpu.global.u32 [%0], %1;" :: "l"(p), "r"(v) : "memory"); }
__device__ __forceinline__ void red_add_relaxed(uint32_t* p, uint32_t v) { asm volatile("red.relaxed.gpu.global.add.u32 [%0], %1;" :: "l"(p), "r"(v) : "memory"); }
__device__ __forceinline__ uint2 ld_pkt8(const uint2* p) {
  uint2 v; asm volatile("{\n.reg .b64 t;\nld.relaxed.gpu.global.b64 t, [%2];\nmov.b64 {%0,%1}, t;\n}" : "=r"(v.x), "=r"(v.y) : "l"(p) : "memory"); return v;
}
__device__ __forceinline__ void st_pkt8(uint2* p, uint32_t a, uint32_t b) {
  asm volatile("{\n.reg .b64 t;\nmov.b64 t, {%1,%2};\nst.relaxed.gpu.global.b64 [%0], t;\n}" :: "l"(p), "r"(a), "r"(b) : "memory");
}
__device__ __forceinline__ uint4 ld_pkt16(const uint4* p) {
  uint4 v; asm volatile("{\n.reg .b128 t;\n.reg .b64 a, b;\nld.relaxed.gpu.global.b128 t, [%4];\nmov.b128 {a, b}, t;\nmov.b64 {%0,%1}, a;\nmov.b64 {%2,%3}, b;\n}"
    : "=r"(v.x), "=r"(v.y), "=r"(v.z), "=r"(v.w) : "l"(p) : "memory"); return v;
}
__device__ __forceinline__ void st_pkt16(uint4* p, uint32_t x, uint32_t y, uint32_t z, uint32_t w) {
  asm volatile("{\n.reg .b128 t;\n.reg .b64 a, b;\nmov.b64 a, {%1,%2};\nmov.b64 b, {%3,%4};\nmov.b128 t, {a, b};\nst.relaxed.gpu.global.b128 [%0], t;\n}"
    :: "l"(p), "r"(x), "r"(y), "r"(z), "r"(w) : "memory");
}
__device__ __forceinline__ void cp_async16(uint32_t dst, const void* src) { asm volatile("cp.async.cg.shared.global [%0], [%1], 16;" :: "r"(dst), "l"(src) : "memory"); }
__device__ __forceinline__ void cp_async_wait() { asm volatile("cp.async.wait_all;" ::: "memory"); }
__device__ __forceinline__ uint32_t lds32(uint32_t a) { uint32_t v; asm volatile("ld.shared.u32 %0, [%1];" : "=r"(v) : "r"(a) : "memory"); return v; }
__device__ __forceinline__ float lds_f32(uint32_t a) { float v; asm volatile("ld.shared.f32 %0, [%1];" : "=f"(v) : "r"(a) : "memory"); return v; }
__device__ __forceinline__ uint2 lds64(uint32_t a) { uint2 v; asm volatile("ld.shared.v2.u32 {%0,%1}, [%2];" : "=r"(v.x), "=r"(v.y) : "r"(a) : "memory"); return v; }
__device__ __forceinline__ uint4 lds128(uint32_t a) { uint4 v; asm volatile("ld.shared.v4.u32 {%0,%1,%2,%3}, [%4];" : "=r"(v.x), "=r"(v.y), "=r"(v.z), "=r"(v.w) : "r"(a) : "memory"); return v; }
__device__ __forceinline__ void sts32(uint32_t a, uint32_t v) { asm volatile("st.shared.u32 [%0], %1;" :: "r"(a), "r"(v) : "memory"); }
__device__ __forceinline__ void sts64(uint32_t a, uint32_t x, uint32_t y) { asm volatile("st.shared.v2.u32 [%0], {%1,%2};" :: "r"(a), "r"(x), "r"(y) : "memory"); }
__device__ __forceinline__ void sts128(uint32_t a, uint32_t x, uint32_t y, uint32_t z, uint32_t w) { asm volatile("st.shared.v4.u32 [%0], {%1,%2,%3,%4};" :: "r"(a), "r"(x), "r"(y), "r"(z), "r"(w) : "memory"); }
__device__ __forceinline__ void stsm4(uint32_t a, uint32_t x, uint32_t y, uint32_t z, uint32_t w) {
  asm volatile("stmatrix.sync.aligned.m8n8.x4.shared.b16 [%0], {%1,%2,%3,%4};" :: "r"(a), "r"(x), "r"(y), "r"(z), "r"(w) : "memory");
}
__device__ __forceinline__ void ldsm4(uint32_t a, uint32_t* r) {
  asm volatile("ldmatrix.sync.aligned.m8n8.x4.shared.b16 {%0,%1,%2,%3}, [%4];" : "=r"(r[0]), "=r"(r[1]), "=r"(r[2]), "=r"(r[3]) : "r"(a) : "memory");
}
__device__ __forceinline__ void ldsm4t(uint32_t a, uint32_t* r) {
  asm volatile("ldmatrix.sync.aligned.m8n8.x4.trans.shared.b16 {%0,%1,%2,%3}, [%4];" : "=r"(r[0]), "=r"(r[1]), "=r"(r[2]), "=r"(r[3]) : "r"(a) : "memory");
}
__device__ __forceinline__ void mma16816(float* d, const uint32_t* a, uint32_t b0, uint32_t b1) {
  asm volatile("mma.sync.aligned.m16n8k16.row.col.f32.bf16.bf16.f32 {%0,%1,%2,%3}, {%4,%5,%6,%7}, {%8,%9}, {%0,%1,%2,%3};"
    : "+f"(d[0]), "+f"(d[1]), "+f"(d[2]), "+f"(d[3]) : "r"(a[0]), "r"(a[1]), "r"(a[2]), "r"(a[3]), "r"(b0), "r"(b1));
}
__device__ __forceinline__ void mma1688(float* d, uint32_t a0, uint32_t a1, uint32_t b0) {
  asm volatile("mma.sync.aligned.m16n8k8.row.col.f32.bf16.bf16.f32 {%0,%1,%2,%3}, {%4,%5}, {%6}, {%0,%1,%2,%3};"
    : "+f"(d[0]), "+f"(d[1]), "+f"(d[2]), "+f"(d[3]) : "r"(a0), "r"(a1), "r"(b0));
}
__device__ __forceinline__ uint32_t pack2(float lo, float hi) { uint32_t r; asm("cvt.rn.bf16x2.f32 %0, %1, %2;" : "=r"(r) : "f"(hi), "f"(lo)); return r; }
__device__ __forceinline__ float lo2f(uint32_t v) { return __uint_as_float(v << 16); }
__device__ __forceinline__ float hi2f(uint32_t v) { return __uint_as_float(v & 0xffff0000u); }
__device__ __forceinline__ uint32_t hmul2(uint32_t a, uint32_t b) { uint32_t r; asm("mul.rn.bf16x2 %0, %1, %2;" : "=r"(r) : "r"(a), "r"(b)); return r; }
__device__ __forceinline__ uint32_t hadd2(uint32_t a, uint32_t b) { uint32_t r; asm("add.rn.bf16x2 %0, %1, %2;" : "=r"(r) : "r"(a), "r"(b)); return r; }
__device__ __forceinline__ uint32_t hsub2(uint32_t a, uint32_t b) { uint32_t r; asm("sub.rn.bf16x2 %0, %1, %2;" : "=r"(r) : "r"(a), "r"(b)); return r; }
__device__ __forceinline__ uint32_t hfma2(uint32_t a, uint32_t b, uint32_t c) { uint32_t r; asm("fma.rn.bf16x2 %0, %1, %2, %3;" : "=r"(r) : "r"(a), "r"(b), "r"(c)); return r; }
__device__ __forceinline__ float rbf(float v) { return lo2f(pack2(v, 0.f)); }
__device__ __forceinline__ float ex2(float v) { float r; asm("ex2.approx.ftz.f32 %0, %1;" : "=f"(r) : "f"(v)); return r; }
__device__ __forceinline__ float rcp_f(float v) { float r; asm("rcp.approx.ftz.f32 %0, %1;" : "=f"(r) : "f"(v)); return r; }
__device__ __forceinline__ float sqrt_f(float v) { float r; asm("sqrt.approx.ftz.f32 %0, %1;" : "=f"(r) : "f"(v)); return r; }
__device__ __forceinline__ float sigmoid_f(float v) { return rcp_f(1.f + ex2(-1.4426950408889634f * v)); }
__device__ __forceinline__ float silu_f(float v) { return v * sigmoid_f(v); }
constexpr uint32_t ONE2 = 0x3f803f80u;

#define R8(a,o) "+f"(a[o+0]), "+f"(a[o+1]), "+f"(a[o+2]), "+f"(a[o+3]), "+f"(a[o+4]), "+f"(a[o+5]), "+f"(a[o+6]), "+f"(a[o+7])
#define R64(a,o) R8(a,o), R8(a,o+8), R8(a,o+16), R8(a,o+24), R8(a,o+32), R8(a,o+40), R8(a,o+48), R8(a,o+56)
#define D64 "{%0,%1,%2,%3,%4,%5,%6,%7,%8,%9,%10,%11,%12,%13,%14,%15,%16,%17,%18,%19,%20,%21,%22,%23,%24,%25,%26,%27,%28,%29,%30,%31," \
            "%32,%33,%34,%35,%36,%37,%38,%39,%40,%41,%42,%43,%44,%45,%46,%47,%48,%49,%50,%51,%52,%53,%54,%55,%56,%57,%58,%59,%60,%61,%62,%63"
#define D128 D64 ",%64,%65,%66,%67,%68,%69,%70,%71,%72,%73,%74,%75,%76,%77,%78,%79,%80,%81,%82,%83,%84,%85,%86,%87,%88,%89,%90,%91,%92,%93,%94,%95," \
            "%96,%97,%98,%99,%100,%101,%102,%103,%104,%105,%106,%107,%108,%109,%110,%111,%112,%113,%114,%115,%116,%117,%118,%119,%120,%121,%122,%123,%124,%125,%126,%127"

template <int TB> __device__ __forceinline__ void wgmma_ss128(float* d, uint64_t da, uint64_t db, int acc) {
  asm volatile("{\n.reg .pred p;\nsetp.ne.b32 p, %66, 0;\nwgmma.mma_async.sync.aligned.m64n128k16.f32.bf16.bf16 " D64 "}, %64, %65, p, 1, 1, 0, %67;\n}"
    : R64(d, 0) : "l"(da), "l"(db), "r"(acc), "n"(TB));
}
template <int TB> __device__ __forceinline__ void wgmma_rs128(float* d, const uint32_t* a, uint64_t db, int acc) {
  asm volatile("{\n.reg .pred p;\nsetp.ne.b32 p, %69, 0;\nwgmma.mma_async.sync.aligned.m64n128k16.f32.bf16.bf16 " D64 "}, {%64,%65,%66,%67}, %68, p, 1, 1, %70;\n}"
    : R64(d, 0) : "r"(a[0]), "r"(a[1]), "r"(a[2]), "r"(a[3]), "l"(db), "r"(acc), "n"(TB));
}
template <int TB> __device__ __forceinline__ void wgmma_ss256(float* d, uint64_t da, uint64_t db, int acc) {
  asm volatile("{\n.reg .pred p;\nsetp.ne.b32 p, %130, 0;\nwgmma.mma_async.sync.aligned.m64n256k16.f32.bf16.bf16 " D128 "}, %128, %129, p, 1, 1, 0, %131;\n}"
    : R64(d, 0), R64(d, 64) : "l"(da), "l"(db), "r"(acc), "n"(TB));
}

#define W8(a,o) "=f"(a[o+0]), "=f"(a[o+1]), "=f"(a[o+2]), "=f"(a[o+3]), "=f"(a[o+4]), "=f"(a[o+5]), "=f"(a[o+6]), "=f"(a[o+7])
#define W64(a,o) W8(a,o), W8(a,o+8), W8(a,o+16), W8(a,o+24), W8(a,o+32), W8(a,o+40), W8(a,o+48), W8(a,o+56)
template <int TB> __device__ __forceinline__ void wgmma_ss128_z(float* d, uint64_t da, uint64_t db) {
  asm volatile("wgmma.mma_async.sync.aligned.m64n128k16.f32.bf16.bf16 " D64 "}, %64, %65, 0, 1, 1, 0, %66;"
    : W64(d, 0) : "l"(da), "l"(db), "n"(TB));
}
template <int TB> __device__ __forceinline__ void wgmma_rs128_z(float* d, const uint32_t* a, uint64_t db) {
  asm volatile("wgmma.mma_async.sync.aligned.m64n128k16.f32.bf16.bf16 " D64 "}, {%64,%65,%66,%67}, %68, 0, 1, 1, %69;"
    : W64(d, 0) : "r"(a[0]), "r"(a[1]), "r"(a[2]), "r"(a[3]), "l"(db), "n"(TB));
}
template <int TB> __device__ __forceinline__ void wgmma_ss256_z(float* d, uint64_t da, uint64_t db) {
  asm volatile("wgmma.mma_async.sync.aligned.m64n256k16.f32.bf16.bf16 " D128 "}, %128, %129, 0, 1, 1, 0, %130;"
    : W64(d, 0), W64(d, 64) : "l"(da), "l"(db), "n"(TB));
}

template <int TB> __device__ __forceinline__ void wgmma_rs256(float* d, const uint32_t* a, uint64_t db) {
  asm volatile("wgmma.mma_async.sync.aligned.m64n256k16.f32.bf16.bf16 " D128 "}, {%128,%129,%130,%131}, %132, 1, 1, 1, %133;"
    : R64(d, 0), R64(d, 64) : "r"(a[0]), "r"(a[1]), "r"(a[2]), "r"(a[3]), "l"(db), "n"(TB));
}
template <int TB> __device__ __forceinline__ void wgmma_rs256_z(float* d, const uint32_t* a, uint64_t db) {
  asm volatile("wgmma.mma_async.sync.aligned.m64n256k16.f32.bf16.bf16 " D128 "}, {%128,%129,%130,%131}, %132, 0, 1, 1, %133;"
    : W64(d, 0), W64(d, 64) : "r"(a[0]), "r"(a[1]), "r"(a[2]), "r"(a[3]), "l"(db), "n"(TB));
}
#define D32 "{%0,%1,%2,%3,%4,%5,%6,%7,%8,%9,%10,%11,%12,%13,%14,%15,%16,%17,%18,%19,%20,%21,%22,%23,%24,%25,%26,%27,%28,%29,%30,%31}"
__device__ __forceinline__ void wgmma_rs64(float* d, const uint32_t* a, uint64_t db) {
  asm volatile("wgmma.mma_async.sync.aligned.m64n64k16.f32.bf16.bf16 " D32 ", {%32,%33,%34,%35}, %36, 1, 1, 1, 0;"
    : R8(d, 0), R8(d, 8), R8(d, 16), R8(d, 24) : "r"(a[0]), "r"(a[1]), "r"(a[2]), "r"(a[3]), "l"(db));
}
__device__ __forceinline__ void wgmma_rs64_z(float* d, const uint32_t* a, uint64_t db) {
  asm volatile("wgmma.mma_async.sync.aligned.m64n64k16.f32.bf16.bf16 " D32 ", {%32,%33,%34,%35}, %36, 0, 1, 1, 0;"
    : W8(d, 0), W8(d, 8), W8(d, 16), W8(d, 24) : "r"(a[0]), "r"(a[1]), "r"(a[2]), "r"(a[3]), "l"(db));
}
__device__ __forceinline__ void issue_qk(float* S, const uint32_t* Q, uint64_t dk) {
  wgmma_rs64_z(S, Q, dk);
#pragma unroll
  for (int kk = 1; kk < 8; kk++) wgmma_rs64(S, Q + 4 * kk, dk + (kk >> 2) * 512 + (kk & 3) * 2);
}
__device__ __forceinline__ void issue_pv(float* O, const uint32_t* P, uint64_t dv, int acc) {
#pragma unroll
  for (int kk = 0; kk < 4; kk++) wgmma_rs128<1>(O, P + 4 * kk, dv + kk * 128, kk ? 1 : acc);
}

#define TS(i)
#define TSC(i)
#define TSX(i)
#define TSY(k) do { if ((tid & 127) == 0) TS((k) + 40 * wg); } while (0)
#define TT(k)
#define TV(k)
#define TR(k)
#define TQ(k)
#define TH(k)
#define TA(k)
#define TAFLUSH()

struct SoftmaxState { float c0, c1, l0, l1; bool shifted; };
constexpr float SM_SCALE = 0.08838834764831845f * 1.4426950408889634f;
__device__ __forceinline__ void softmax_start(SoftmaxState& z) { z.c0 = z.c1 = z.l0 = z.l1 = 0.f; z.shifted = false; }
__device__ __forceinline__ void softmax_half(float* S, uint32_t* P, float* O, SoftmaxState& z, bool first, uint32_t tag) {
  const float lo0 = z.l0, lo1 = z.l1;
  float lim = 1.2676506002282294e30f;
  const float low = first ? 8.673617379884035e-19f : 0.f;
  if (z.shifted) {
#pragma unroll
    for (int j = 0; j < 32; j++) S[j] += (j & 2) ? z.c1 : z.c0;
  }
#pragma unroll 1
  while (true) {
    bb_fence(tag);
#pragma unroll
    for (int j = 0; j < 8; j++) {
      const float p0 = ex2(S[4 * j]), p1 = ex2(S[4 * j + 1]), p2 = ex2(S[4 * j + 2]), p3 = ex2(S[4 * j + 3]);
      z.l0 += p0; z.l1 += p2; z.l0 += p1; z.l1 += p3;
      P[2 * j] = pack2(p0, p1); P[2 * j + 1] = pack2(p2, p3);
    }
    if (!__any_sync(0xffffffffu, !(z.l0 < lim && z.l1 < lim && fminf(z.l0, z.l1) >= low) && lim > 0.f)) break;
    float d0 = fmaxf(S[0], S[1]), d1 = fmaxf(S[2], S[3]);
#pragma unroll
    for (int j = 1; j < 8; j++) { d0 = fmaxf(d0, fmaxf(S[4 * j], S[4 * j + 1])); d1 = fmaxf(d1, fmaxf(S[4 * j + 2], S[4 * j + 3])); }
    d0 = fmaxf(d0, __shfl_xor_sync(0xffffffffu, d0, 1)); d1 = fmaxf(d1, __shfl_xor_sync(0xffffffffu, d1, 1));
    d0 = fmaxf(d0, __shfl_xor_sync(0xffffffffu, d0, 2)); d1 = fmaxf(d1, __shfl_xor_sync(0xffffffffu, d1, 2));
    if (!first) { d0 = fmaxf(d0, 0.f); d1 = fmaxf(d1, 0.f); }
    z.shifted = true;
    z.c0 -= d0; z.c1 -= d1;
#pragma unroll
    for (int j = 0; j < 32; j++) S[j] -= (j & 2) ? d1 : d0;
    const float a0 = first ? 1.f : ex2(-d0), a1 = first ? 1.f : ex2(-d1);
    z.l0 = lo0 * a0; z.l1 = lo1 * a1;
    lim = -1.f;
    wg_wait<0>();
    reg_fence<64>(O);
#pragma unroll
    for (int j = 0; j < 16; j++) { O[4 * j] *= a0; O[4 * j + 1] *= a0; O[4 * j + 2] *= a1; O[4 * j + 3] *= a1; }
  }
}

__device__ __forceinline__ void modulate_frags(uint32_t* A, const uint32_t* V, const uint4* R, const uint32_t* ln) {
#pragma unroll
  for (int kk = 0; kk < 4; kk++) {
    const uint4 sa = R[kk >> 1], c1 = R[2 + (kk >> 1)];
#pragma unroll
    for (int j = 0; j < 4; j++) {
      const uint32_t n = hfma2(V[4 * kk + j], ln[(j & 1) * 2 + 1], ln[(j & 1) * 2]);
      A[4 * kk + j] = (kk & 1) ? ((j & 2) ? hfma2(n, c1.w, sa.x) : hfma2(n, c1.z, sa.w)) : ((j & 2) ? hfma2(n, c1.y, sa.z) : hfma2(n, c1.x, sa.y));
    }
  }
}
__device__ __forceinline__ void publish_record(uint4* dst, uint32_t pk, int src, int vec, bool doit) {
  const int r = vec ? 0 : 12;
  const uint32_t x = __shfl_sync(0xffffffffu, pk, src + r), y = __shfl_sync(0xffffffffu, pk, src + ((r + 4) & 12));
  const uint32_t z = __shfl_sync(0xffffffffu, pk, src + ((r + 8) & 12)), w = __shfl_sync(0xffffffffu, pk, src + ((r + 12) & 12));
  if (doit) st_pkt16(dst, ~x, y, z, w);
}
__device__ __forceinline__ void put_record(uint32_t sb, int idx, const uint4& v) {
  sts128(sb + SM_STASH + idx * 16, ~v.x, v.y, v.z, v.w);
  sts128(sb + SM_STASH + 16384 + idx * 16, ~v.x, v.y, v.z, v.w);
}
__device__ __forceinline__ float mod_value(float v, int vec) {
  v = rbf(v);
  return (vec ? rbf(1.f + v) : v) * SM_SCALE;
}

__device__ __forceinline__ void row_rcp(float& l0, float& l1) {
  l0 += __shfl_xor_sync(0xffffffffu, l0, 1); l1 += __shfl_xor_sync(0xffffffffu, l1, 1);
  l0 += __shfl_xor_sync(0xffffffffu, l0, 2); l1 += __shfl_xor_sync(0xffffffffu, l1, 2);
  l0 = rcp_f(l0); l1 = rcp_f(l1);
}
__device__ __forceinline__ void stage_o(const float* O, float r0, float r1, uint32_t stsm_addr) {
#pragma unroll
  for (int kk = 0; kk < 8; kk++) {
    stsm4((stsm_addr + (kk >> 2) * 8192) ^ ((kk & 3) * 32),
          pack2(O[8 * kk + 0] * r0, O[8 * kk + 1] * r0), pack2(O[8 * kk + 2] * r1, O[8 * kk + 3] * r1),
          pack2(O[8 * kk + 4] * r0, O[8 * kk + 5] * r0), pack2(O[8 * kk + 6] * r1, O[8 * kk + 7] * r1));
  }
}

__global__ void __cluster_dims__(2, 1, 1) __launch_bounds__(NTHREADS, 1)
fused_kernel(const Params p, const __grid_constant__ CUtensorMap mH, const __grid_constant__ CUtensorMap mWq,
             const __grid_constant__ CUtensorMap mK, const __grid_constant__ CUtensorMap mV,
             const __grid_constant__ CUtensorMap mO, const __grid_constant__ CUtensorMap mWo,
             const __grid_constant__ CUtensorMap mX, const __grid_constant__ CUtensorMap mOut,
             const __grid_constant__ CUtensorMap mWg, const __grid_constant__ CUtensorMap mWu,
             const __grid_constant__ CUtensorMap mWd, const __grid_constant__ CUtensorMap mWm,
             const __grid_constant__ CUtensorMap mWs, const __grid_constant__ CUtensorMap mWh) {
  extern __shared__ __align__(1024) uint8_t smem_raw[];
  TH(0);
  const uint32_t sb = smem_u32(smem_raw);
  const int tid = threadIdx.x;
  const int b0 = blockIdx.x;
  const int lane = tid & 31;
  const int role = __shfl_sync(0xffffffffu, tid >> 8, 0);

  if (b0 >= NMAIN) {
    const uint32_t cs = clock();
    const uint32_t tag = ld_relaxed(&g_epoch) + 1;
    const int sp = b0 - NMAIN, vec = 2 + sp;
    const int warp = __shfl_sync(0xffffffffu, tid >> 5, 0);
    float* sc = reinterpret_cast<float*>(smem_raw + SM_STASH);
    float* red = reinterpret_cast<float*>(smem_raw + SM_STASH + 4096);
    const int ridx = (lane >> 3) * 2 * RV + (sp & 1) * RV + 16 * RS + (sp >> 1) * 16 + (warp & 1) * 8 + (lane & 7);
    if (warp < 8) st_pkt16(&g_rec[warp >> 2][0][ridx + (warp & 2) * 16], 0, 0, 0, 0);
#pragma unroll 1
    for (int i = tid; i < 1024; i += NTHREADS) sc[i] = rbf(silu_f(__bfloat162float(p.c[i])));
    if (tid == 0) {
      tma_prefetch_desc(&mWs);
      for (int s = 0; s < NST2; s++) { mbar_init(sb + BAR_FULL2 + 8 * s, 1); mbar_init(sb + BAR_EMPTY2 + 8 * s, 8); }
      fence_async_smem();
      while ((uint32_t)clock() - cs < SPT) {}
    }
    __syncthreads();
    int s = 0; uint32_t ph = 0;
    if (tid == 0) TS(0);
    if (warp == 8) {
      const uint64_t pol = policy_evict_first();
#pragma unroll 1
      for (int n = 0; n < 80; n++) {
        mbar_wait_g(sb + BAR_EMPTY2 + 8 * s, ph ^ 1);
        if (elect_one()) {
          mbar_expect_tx(sb + BAR_FULL2 + 8 * s, 32768);
          if (n < 16) {
            tma_ld_hint(sb + s * ST2, &mWs, (sp & 1) * 1024 + 512 + (n >> 3) * 256 + (sp >> 1) * 128, (n & 7) * 128, sb + BAR_FULL2 + 8 * s, pol);
          } else {
#pragma unroll
            for (int j = 0; j < 4; j++) tma_ld_hint(sb + s * ST2 + j * 8192, &mWm, vec * 1024 + j * 256, (n - 16) * 16, sb + BAR_FULL2 + 8 * s, pol);
          }
        }
        __syncwarp();
        if (++s == NST2) { s = 0; ph ^= 1; }
      }
    } else if (warp < 8) {
      float acc[8];
#pragma unroll
      for (int i = 0; i < 8; i++) acc[i] = 0.f;
      auto stage = [&](uint32_t a0, int da, const float* cp, int dc) {
        mbar_wait_g(sb + BAR_FULL2 + 8 * s, ph);
#pragma unroll
        for (int i = 0; i < 8; i++) {
          const uint4 v = lds128(a0 + s * ST2 + i * da);
          const float c = cp[i * dc];
          acc[0] = fmaf(lo2f(v.x), c, acc[0]); acc[1] = fmaf(hi2f(v.x), c, acc[1]);
          acc[2] = fmaf(lo2f(v.y), c, acc[2]); acc[3] = fmaf(hi2f(v.y), c, acc[3]);
          acc[4] = fmaf(lo2f(v.z), c, acc[4]); acc[5] = fmaf(hi2f(v.z), c, acc[5]);
          acc[6] = fmaf(lo2f(v.w), c, acc[6]); acc[7] = fmaf(hi2f(v.w), c, acc[7]);
        }
        if (__shfl_sync(0xffffffffu, lane, __float_as_uint(acc[7]) & 31) < 32 && lane == 0) mbar_arrive(sb + BAR_EMPTY2 + 8 * s);
        if (++s == NST2) { s = 0; ph ^= 1; }
      };
#pragma unroll 1
      for (int n = 0; n < 16; n++) {
        stage(sb + tid * 16, 4096, sc + (n & 7) * 128 + (tid >> 4), 16);
        if ((n & 7) == 7) {
          float* r2 = red + 2048 + (n & 8) * 256;
#pragma unroll
          for (int i = 0; i < 8; i++) { r2[tid * 8 + i] = acc[i]; acc[i] = 0.f; }
          nb_sync(NB_CONS, 256);
          if (warp < 2) {
            float v0 = 0.f, v1 = 0.f;
#pragma unroll 4
            for (int i = 0; i < 16; i++) { const float2 e = reinterpret_cast<const float2*>(r2)[i * 64 + tid]; v0 += e.x; v1 += e.y; }
            publish_record(&g_rec[tag & 1][0][ridx + (n >> 3) * 32], pack2(mod_value(v0, sp & 1), mod_value(v1, sp & 1)),
                           (lane & 4) * 4 + (lane & 3), sp & 1, true);
          }
          if (tid == 0) TS(1 + (n >> 3));
        }
      }
#pragma unroll 1
      for (int n = 0; n < 64; n++) {
        stage(sb + ((tid >> 5) & 3) * 8192 + (tid >> 7) * 4096 + (tid & 31) * 16, 512, sc + n * 16 + (tid >> 7) * 8, 1);
      }
#pragma unroll
      for (int i = 0; i < 8; i++) red[(tid >> 7) * 1024 + (tid & 127) * 8 + i] = acc[i];
    }
    __syncthreads();
    float dot = 0.f;
#pragma unroll 1
    for (int i = tid; i < 512; i += NTHREADS) {
      uint32_t v = pack2(red[2 * i] + red[1024 + 2 * i], red[2 * i + 1] + red[1024 + 2 * i + 1]);
      st_pkt8(&g_mod[vec * 512 + i], v, tag);
      if (vec == 4) v = hadd2(v, ONE2);
      const uint32_t wr = reinterpret_cast<const uint32_t*>(p.w_r)[i];
      dot = fmaf(lo2f(v), lo2f(wr), fmaf(hi2f(v), hi2f(wr), dot));
    }
#pragma unroll
    for (int o = 16; o; o >>= 1) dot += __shfl_xor_sync(0xffffffffu, dot, o);
    if (lane == 0) sc[warp] = dot;
    __syncthreads();
    if (tid == 0) {
      dot = 0.f;
      for (int w = 0; w < 12; w++) dot += sc[w];
      fence_release_gpu();
      st_pkt8(&g_vdone[(vec - 2) * 16], __float_as_uint(dot), tag);
      TS(11);
#pragma unroll 1
      for (int i = 0; i < 128; i++) {
        const int u = i * 4 + (b0 - NMAIN);
        l2_prefetch(p.wo + (size_t)((4 * ((u >> 4) & 7) + (u >> 7)) * 128 + (u & 15) * 8) * 1024, 16384);
        __nanosleep(PFW);
      }
    }
    return;
  }

  const uint32_t rank = b0 & 1;
  const bool slab = !(b0 & 32), late = b0 & 16;
  const uint32_t c0 = clock();
  if (tid == 352) TS(0);
  const uint32_t slab_addr = sb + SM_WSLAB + (tid >> 5) * 4096 + (lane & 3) * 128 + (lane & 4) * 16 + (((lane >> 3) ^ lane) & 3) * 16;
  auto load_slab = [&]() {
    const bf16* wp = p.w_mod + (size_t)(512 * rank + 2 * (tid & ~31) + 2 * (lane & 3) + ((lane >> 2) & 1)) * 6144 + 32 * (b0 >> 1) + 8 * (lane >> 3);
    const uint64_t pef = policy_evict_first();
#pragma unroll
    for (int i = 0; i < 8; i++)
      asm volatile("cp.async.cg.shared.global.L2::cache_hint [%0], [%1], 16, %2;"
        :: "r"(slab_addr + i * 512), "l"(wp + (size_t)i * 8 * 6144), "l"(pef) : "memory");
  };
  if (tid == 256) {
    mbar_init(sb + BAR_XH, 1);
    fence_async_smem();
    mbar_expect_tx(sb + BAR_XH, 32768);
    if (XD) while ((uint32_t)clock() - c0 < XD) {}
#pragma unroll
    for (int i = 0; i < 2; i++)
      asm volatile("cp.async.bulk.shared::cluster.global.mbarrier::complete_tx::bytes [%0], [%1], 16384, [%2];"
        :: "r"(sb + SM_XROW + i * ST1), "l"(p.x + (size_t)b0 * 16384 + i * 8192), "r"(sb + BAR_XH) : "memory");
  }
  __syncwarp();
  uint32_t cw[8];
#pragma unroll
  for (int i = 0; i < 8; i++) cw[i] = 0;
  if (!role && slab) {
#pragma unroll
    for (int i = 0; i < 8; i++) cw[i] = ld_relaxed(reinterpret_cast<const uint32_t*>(p.c) + 256 * rank + (tid & ~28) + 4 * i);
  }
  uint32_t epoch = 0;
  if (!role) epoch = ld_relaxed(&p.sc->epoch[lane]);
  if (!role && slab && !late) load_slab();
#define TILE_ROLES() \
  mbar_wait(sb + BAR_ROLE, 0); \
  const int b = 2 * __shfl_sync(0xffffffffu, lds32(sb + SM_ROLE), 0) + rank; \
  const int rt = b >> 3;     \
  const int ct = b & 7;

  if (role) {
    asm volatile("setmaxnreg.dec.sync.aligned.u32 24;");
    const int warp = __shfl_sync(0xffffffffu, tid >> 5, 0);
    if (tid == 256) {
      mbar_init(sb + BAR_RED, 1); mbar_init(sb + BAR_WH, 1);
      for (int s = 0; s < 2; s++) mbar_init(sb + BAR_OF + 8 * s, 1);
      mbar_init(sb + BAR_ROLE, 1);
      for (int s = 0; s < 5; s++) { mbar_init(sb + BAR_FULL1 + 8 * s, 1); mbar_init(sb + BAR_EMPTY1 + 8 * s, 4); }
      for (int s = 0; s < 2; s++) { mbar_init(sb + BAR_STASH + 8 * s, 1); mbar_init(sb + BAR_X + 8 * s, 1); }
      for (int s = 0; s < 4; s++) mbar_init(sb + BAR_HS + 8 * s, 1);
      mbar_init(sb + BAR_G, 16); mbar_init(sb + BAR_T1, 1); mbar_init(sb + BAR_HF, 1);
      mbar_init(sb + BAR_SFREE, 4); mbar_init(sb + BAR_TFREE, 8);
      mbar_init(sb + BAR_FFN, 4); mbar_init(sb + BAR_FFN + 8, 2);
      mbar_init(sb + BAR_CAND, 1); mbar_init(sb + BAR_VEC, 32); for (int s = 0; s < 3; s++) mbar_init(sb + BAR_TAB + 8 * s, 32);
      mbar_expect_tx(sb + BAR_RED, 1024);
      mbar_expect_tx(sb + BAR_ROLE, 4);
      asm volatile("fence.mbarrier_init.release.cluster;" ::: "memory");
    }
    __syncwarp();
    asm volatile("barrier.cluster.arrive.relaxed.aligned;" ::: "memory");
    const int ridx = ((lane >> 1) & 3) * 2 * RV + (b0 >> 6) * RV + ((b0 >> 1) & 31) * RS + 2 * rank + (lane & 1) + (lane >> 3) * 4;
    if (warp == 11 && slab && lane < 2 * RS) { st_pkt16(&g_rec[0][0][ridx], 0, 0, 0, 0); st_pkt16(&g_rec[1][0][ridx], 0, 0, 0, 0); }
    if (tid == 256) {
      tma_prefetch_desc(&mWq); tma_prefetch_desc(&mX); tma_prefetch_desc(&mH); tma_prefetch_desc(&mK); tma_prefetch_desc(&mV); tma_prefetch_desc(&mO);
    }
    uint32_t pairid = 0;
    if (tid == 320 && rank == 0) {
      uint32_t t;
      asm("mov.u32 %0, %%smid;" : "=r"(t));
      t >>= 1;
      uint32_t grp = ((0x73216540u >> (4 * ((t < 32 ? t : t < 60 ? 1 + (t - 32) % 7 : t < 62 ? t - 54 : 0) & 7))) & 7) - 1, slot;
      int it = 0;
      do {
        grp = (grp + 1) & 7;
        asm volatile("atom.relaxed.gpu.global.add.u32 %0, [%1], 1;" : "=r"(slot) : "l"(&p.sc->ticket[grp * 32]) : "memory");
        spin_guard(it);
      } while (slot >= 8);
      pairid = slot * 8 + grp;
    }
    __syncwarp();
    asm volatile("barrier.cluster.wait.aligned;" ::: "memory");
    if (tid == 320 && rank == 0) {
#pragma unroll
      for (int r = 0; r < 2; r++)
        asm volatile("st.async.weak.shared::cluster.mbarrier::complete_tx::bytes.b32 [%0], %1, [%2];"
          :: "r"(mapa(sb + SM_ROLE, r)), "r"(pairid), "r"(mapa(sb + BAR_ROLE, r)) : "memory");
    }
    __syncwarp();
    const uint32_t tag = ld_relaxed(&g_epoch) + 1;
    if (warp == 8) {
      TILE_ROLES();
      const int kvrow = (ct >> 1) * 2048 + 1536, arow = rt * 128 + rank * 64;
      const uint64_t pef = policy_evict_first();
#pragma unroll 1
      for (int pair = 0; pair < 2; pair++) {
        const int wblk = (4 * ct + 2 * pair) * 2;
        if (pair) { mbar_wait_g(sb + BAR_HF, 0); fence_async_global(); }
#pragma unroll 1
        for (int n = 0; n < 16; n++) {
          const uint32_t s = n & 3, st = sb + SM_RING + s * ST1, fb = sb + BAR_FULL1 + 8 * s;
          if (n == 2 && pair == 0) mbar_wait_g(sb + BAR_G, 0);
          mbar_wait_g(fb + (BAR_EMPTY1 - BAR_FULL1), ((n >> 2) & 1) ^ 1);
          if (elect_one()) {
            mbar_expect_tx(fb, 49152);
            if (pair) tma_ld_mc_hint(st + rank * 8192, &mH, n * 64, arow, fb, pef); else
            tma_ld_mc(st + rank * 8192, pair ? &mH : &mX, n * 64, arow, fb);
            tma_ld3_hint(st + 16384, &mWq, n * 64, wblk, fb, pef);
          }
          __syncwarp();
        }
#pragma unroll 1
        for (int n = 0; n < 16; n++) {
          const uint32_t s = n & 3, st = sb + SM_RING + s * ST1 + rank * 8192, fb = sb + BAR_FULL1 + 8 * s;
          const int h0 = n == 0 ? 0 : n == 15 ? 14 : n + 1, h1 = n == 0 ? 1 : n == 15 ? 15 : n - 1;
          mbar_wait_g(fb + (BAR_EMPTY1 - BAR_FULL1), ((n >> 2) & 1) ^ 1);
          if (elect_one()) {
            mbar_expect_tx(fb, 32768);
            tma_ld_mc(st, n == 15 ? &mV : &mK, rank * 64, kvrow + (h0 & 7) * 64, fb);
            tma_ld_mc(st + 16384, n == 0 ? &mK : &mV, rank * 64, kvrow + (h1 & 7) * 64, fb);
            if (n == 3 && pair == 1) mbar_arrive(sb + BAR_T1);
          }
          __syncwarp();
        }
      }
      {
        uint32_t s = 0, ph = 1;
#pragma unroll 1
        for (int half = 0; half < 2; half++) {
          mbar_wait_g(sb + BAR_OF + 8 * half, 0);
          fence_async_global();
#pragma unroll 1
          for (int n = 32 * half; n < 32 * half + 32; n++) {
            const uint32_t st = sb + SM_RING + s * ST1, fb = sb + BAR_FULL1 + 8 * s;
            const int k0 = ((n & 14) * 2 + (n >> 4)) * 128 + (n & 1) * 64;
            mbar_wait_g(n == 8 ? sb + BAR_SFREE : fb + (BAR_EMPTY1 - BAR_FULL1), n == 8 ? 0 : ph ^ (s >> 2));
            if (elect_one()) {
              mbar_expect_tx(fb, 32768);
              tma_ld_mc_hint(st + rank * 8192, &mO, k0, arow, fb, pef);
              tma_ld3_hint(st + 16384, &mWo, k0, 2 * ct, fb, pef);
            }
            __syncwarp();
            if (++s == 5 || n == 3) { s = 0; ph ^= 1; }
          }
        }
        if (b < NFFN) {
#pragma unroll 1
          for (s = 0; s < 2; s++) {
            mbar_wait_g(sb + BAR_EMPTY1 + 8 * s, 0);
            if (elect_one()) {
              mbar_expect_tx(sb + BAR_FFN + 8, 32768);
              tma_ld3_hint(sb + SM_RING + s * ST1, &mWd, b * 32, s * 8, sb + BAR_FFN + 8, pef);
            }
            __syncwarp();
          }
        }
      }
    } else if (warp <= 10) {
      const int w = warp - 9;
      if (slab && late && w == 0 && lane == 0) {
        tma_prefetch_desc(&mWh);
        mbar_expect_tx(sb + BAR_WH, 32768);
        while ((uint32_t)clock() - c0 < WL) {}
        const uint64_t pef = policy_evict_first();
#pragma unroll
        for (int i = 0; i < 2; i++) tma_ld_hint(sb + SM_WSLAB + i * 16384, &mWh, 32 * (b0 >> 1), 512 * rank + 256 * i, sb + BAR_WH, pef);
      }
      __syncwarp();
      TILE_ROLES();
      const uint32_t st = sb + SM_STASH + w * 16384;
#pragma unroll 1
      for (int j = 0; j < 2; j++) {
        nb_sync(NB_OST + w, 160);
        if (elect_one()) {
          fence_async_smem();
          tma_st(&mH, (2 * ct + j) * 64, rt * 128 + w * 64, st + 4096);
          bulk_commit();
          bulk_wait_read();
          mbar_arrive(sb + BAR_HS + 16 * w + 8 * j);
          if (j) {
            bulk_wait_all();
            fence_async_global();
            fence_release_gpu();
            red_add_relaxed(&g_hflag[rt * 32], 1);
          }
        }
        __syncwarp();
      }
#pragma unroll 1
      for (int r = 0; r < 4; r++) {
        nb_sync(NB_OST + w, 160);
        if (elect_one()) {
          fence_async_smem();
          const int hcol = (4 * ct + r) * 128;
          tma_st(&mO, hcol, rt * 128 + w * 64, st);
          tma_st(&mO, hcol + 64, rt * 128 + w * 64, st + 8192);
          bulk_commit();
          bulk_wait_read();
          if (r < 2) {
            mbar_arrive(sb + BAR_STASH + 8 * w);
          } else if (r == 2) {
            mbar_expect_tx(sb + BAR_X + 8 * w, 16384);
            tma_ld_hint(st, &mX, ct * 128, rt * 128 + w * 64, sb + BAR_X + 8 * w, policy_evict_first());
            tma_ld_hint(st + 8192, &mX, ct * 128 + 64, rt * 128 + w * 64, sb + BAR_X + 8 * w, policy_evict_first());
          } else {
            mbar_arrive_cl(mapa(sb + BAR_SFREE, 0)); mbar_arrive_cl(mapa(sb + BAR_SFREE, 1));
          }
          bulk_wait_all();
          fence_async_global();
          fence_release_gpu();
          red_add_relaxed(&g_oflag[(rt * 4 + r) * 32], 1);
        }
        __syncwarp();
      }
      nb_sync(NB_OST + w, 160);
      int skip = -1;
      mbar_wait_g(sb + BAR_CAND, 0);
      const bool has_cand = (lds32(sb + SM_CAND) >> 6) == w;
      if (has_cand) {
        nb_sync(NB_WIN + w, 160);
        skip = (int)lds32(sb + SM_WROW + 4 * w) - (rt * 128 + w * 64);
      }
      if ((unsigned)skip >= 64u) {
        if (elect_one()) {
          fence_async_smem();
          tma_st(&mOut, ct * 128, rt * 128 + w * 64, sb + SM_OUT + w * 16384);
          tma_st(&mOut, ct * 128 + 64, rt * 128 + w * 64, sb + SM_OUT + w * 16384 + 8192);
          bulk_commit();
          bulk_wait_read();
        }
        __syncwarp();
      } else {
        uint4* dst = reinterpret_cast<uint4*>(p.out + (size_t)(rt * 128 + w * 64 + (lane >> 4)) * 1024 + ct * 128) + (lane & 15);
#pragma unroll 2
        for (int r = lane >> 4; r < 64; r += 2) {
          const uint4 v = lds128(sb + SM_OUT + w * 16384 + ((lane >> 3) & 1) * 8192 + r * 128 + (((lane ^ r) & 7) * 16));
          if (r != skip) *dst = v;
          dst += 256;
        }
      }
      if (!has_cand) nb_sync(NB_WIN + w, 160);
    } else {
      if (slab) {
        mbar_wait_g(sb + BAR_RED, 0);
        float v = 0.f;
#pragma unroll
        for (int w = 0; w < 8; w++) v += lds_f32(sb + SM_RED + w * 128 + lane * 4);
        v += __shfl_xor_sync(0xffffffffu, v, 16);
        v = mod_value(v, b0 >> 6);
        publish_record(&g_rec[tag & 1][0][ridx], pack2(v, __shfl_down_sync(0xffffffffu, v, 1)), 2 * (lane & 1), b0 >> 6, lane < 8);
        if (lane == 0) TS(1);
      }
      mbar_wait_g(sb + BAR_G, 0);
#pragma unroll 1
      for (int i = 1; i < 4; i++) {
        const uint4* mp = &g_rec[tag & 1][(b0 >> 1) & (NREP - 1)][i == 1 ? (8 + (lane >> 2)) * RS + (lane & 3) : 16 * RS - 64 + 32 * i + lane];
        uint4 v0, v1; int it = 0;
        while (true) {
          v0 = ld_pkt16(mp); v1 = ld_pkt16(mp + RV);
          if (v0.x != 0 && v1.x != 0) break;
          spin_guard(it); __nanosleep(PLD);
        }
        put_record(sb, 32 * i + lane, v0);
        put_record(sb, 128 + 32 * i + lane, v1);
        mbar_arrive(sb + BAR_TAB - 8 + 8 * i);
        if (lane == 0) {
          TS(3 + i + (i > 2));
          if (i == 1) l2_prefetch(((b0 & 64) ? p.vc : p.kc) + (size_t)(((b0 >> 4) & 3) * 2048 + 1536) * 128 + (b0 & 15) * 4096, 8192);
        }
        __syncwarp();
      }
      TILE_ROLES();
      if (lane == 0) {
        int it = 0;
        do { __nanosleep(500); spin_guard(it); } while (ld_relaxed(&g_hflag[rt * 32]) != tag * 16u);
        fence_acquire_gpu();
        mbar_arrive(sb + BAR_HF);
        if (b < NFFN) for (int i = 0; i < 8; i++) { __nanosleep(800); l2_prefetch(p.wd + (size_t)(b * 32 + i * 4) * 1024, 8192); }
      }
      __syncwarp();
      {
        uint2 v; int it = 0;
        do { __nanosleep(1000); v = ld_pkt8(&g_vdone[(lane & 3) * 16]); spin_guard(it); }
        while (!(v.y == tag));
        __syncwarp();
        fence_acquire_gpu();
        if (lane == 1 || lane == 2) sts32(sb + SM_SCAL + (2 - lane) * 4, v.x);
      }
#pragma unroll 1
      for (int i = 0; i < 2; i++) {
        const int q = i * 32 + lane, pi = ct * 64 + q;
        const uint32_t vga = g_mod[2 * 512 + pi].x, vsb = g_mod[3 * 512 + pi].x, vcb = g_mod[4 * 512 + pi].x, vgb = g_mod[5 * 512 + pi].x;
        const uint32_t wr = reinterpret_cast<const uint32_t*>(p.w_r)[pi];
        const uint32_t c1 = hadd2(vcb, ONE2);
        const float al = lo2f(c1) * lo2f(wr), ah = hi2f(c1) * hi2f(wr);
        const uint32_t o8 = (q & 3) * 8 + ((q >> 2) & 1) * 4;
        sts32(sb + SM_GA + (q >> 3) * 32 + o8, vga);
        sts128(sb + SM_REC + q * 16, c1, vsb, vgb, 0);
        const uint32_t ahi = pack2(al, ah), alo = pack2(al - lo2f(ahi), ah - hi2f(ahi));
        const uint32_t ba = sb + SM_B1 + (q >> 3) * 128 + o8;
        sts32(ba, ONE2); sts32(ba + 32, ahi); sts32(ba + 64, alo); sts32(ba + 96, 0);
      }
      if (lane == 0) TS(28);
      if (lane == 0) {
        tma_prefetch_desc(&mWo); tma_prefetch_desc(&mOut); tma_prefetch_desc(&mWd); tma_prefetch_desc(&mWg); tma_prefetch_desc(&mWu);
#pragma unroll 1
        for (int r = 0; r < 4; r++) {
          int it = 0;
          do { __nanosleep(200); spin_guard(it); } while (ld_relaxed(&g_oflag[(rt * 4 + r) * 32]) != tag * 16u);
          if (r & 1) { fence_acquire_gpu(); mbar_arrive(sb + BAR_OF + 8 * (r >> 1)); }
          if (r == 1 && b < NFFN) {
            const uint64_t pef = policy_evict_first();
            mbar_wait_g(sb + BAR_T1, 0);
#pragma unroll 1
            for (int i = 0; i < 4; i++) {
              mbar_expect_tx(sb + BAR_FFN, 16384);
              tma_ld_hint(sb + SM_RING + i * ST1 + 32768, &mWg, b * 32, i * 256, sb + BAR_FFN, pef);
              __nanosleep(GATED);
            }
          }
        }
      }
      __syncwarp();
      if (b < NFFN) {
        mbar_wait_g(sb + BAR_TFREE, 0);
        const uint64_t pef = policy_evict_first();
#pragma unroll 1
        for (int i = 0; i < 5; i++) {
          if (i > 0 && lane == 0) {
            mbar_expect_tx(sb + BAR_FFN, 16384);
            tma_ld_hint(sb + SM_RING + (i - 1) * ST1 + 32768, &mWu, b * 32, (i - 1) * 256, sb + BAR_FFN, pef);
          }
          if (i < 4) {
#pragma unroll 1
            for (int j = 0; j < 8; j++) {
              asm volatile("prefetch.global.L2 [%0];" :: "l"(p.wu + (size_t)(i * 256 + j * 32 + lane) * 3584 + b * 32) : "memory");
              __nanosleep(UPD);
            }
            __nanosleep(500);
          }
        }
      }
      if (lane == 0) TS(29);
#pragma unroll 1
      for (int i = lane; i < 128; i += 32) st_pkt16(&g_stats[b * 128 + i], 0, 0, 0, 0);
      st_pkt16(&g_cand[b * 32 + lane], 0, 0, 0, 0);
      if (lane < ESTR) st_pkt16(&g_entry[(ct * 16 + rt) * ESTR + lane], 0, 0, 0, 0);
#pragma unroll 1
      for (int i = lane; i < (b < NFFN ? 512 : 0); i += 32) st_pkt16(&g_ypart[((i >> 2) * NFFN + b) * 4 + (i & 3)], 0, 0, 0, 0);
      mbar_arrive(sb + BAR_VEC);
      uint4* const cp = &g_cand[b * 32 + lane];
      uint4* const ep = &g_entry[(ct * 16 + rt) * ESTR];
      nb_sync(NB_AMAX, 288);
      TV(0);
      const uint2 e = lds64(sb + SM_AMAX + (lane & 7) * 8);
      const int tmax = __reduce_max_sync(0xffffffffu, (int)e.x);
      const uint32_t row = ~tmax & 127;
      const int wl = row >> 4;
      const uint32_t xa = sb + SM_X2 + (row >> 6) * 16384 + (lane >> 4) * 8192 + (row & 63) * 128 + (lane & 3) * 4
                        + ((((lane >> 1) & 6) ^ (row & 7)) * 16);
      const uint32_t v0 = lds32(xa), v1 = lds32(xa ^ 16);
      if (lane == wl) st_pkt16(ep, (tmax | 127) - rt, rt * 128 + row, e.y, tag);
      st_pkt16(cp, v0, v1, tag, 0);
      if (lane == 0) { sts32(sb + SM_CAND, row); mbar_arrive(sb + BAR_CAND); }
      TV(1);
      if (lane == 0) TS(15);
    }
  } else {
    const int warp = tid >> 5;
    const int wg = warp >> 2, wq = warp & 3;
    const int g = lane >> 2, t = lane & 3;
    uint32_t tag;
    uint32_t ln[4];
    float acc[128];
    uint32_t bf[16];
    auto gemv = [&]() {
          if (late) mbar_wait(sb + BAR_WH, 0); else
          asm volatile("cp.async.wait_all;" ::: "memory");
          float d0[4] = {0.f, 0.f, 0.f, 0.f}, d1[4] = {0.f, 0.f, 0.f, 0.f};
#pragma unroll
          for (int i = 0; i < 8; i++) {
            const uint4 wv = lds128(slab_addr + i * 512);
            const uint32_t a[4] = {wv.x, wv.y, wv.z, wv.w};
            mma16816((i & 1) ? d1 : d0, a, bf[2 * i], bf[2 * i + 1]);
          }
#pragma unroll
          for (int i = 0; i < 4; i++) { d0[i] += d1[i]; d0[i] += __shfl_xor_sync(0xffffffffu, d0[i], 6); }
          const uint32_t dst = mapa(sb + SM_MISC, t & 1) - SM_MISC;
          if (!(lane & 6)) st_async_f32x4(dst + SM_RED + warp * 128 + rank * 64 + g * 8, d0, dst + BAR_RED);
          TH(4);
    };
    {
      asm volatile("barrier.cluster.arrive.relaxed.aligned;" ::: "memory");
      if (lane == 0) st_pkt16(&g_lnst[8 * b0 + warp], 0, 0, 0, 0);
      TH(1);
      asm volatile("setmaxnreg.inc.sync.aligned.u32 240;");
      TH(2);
#pragma unroll
      for (int i = 0; i < 8; i++) {
        const float sv = silu_f((g & 4) ? hi2f(cw[i]) : lo2f(cw[i]));
        const uint32_t sp = (g & 1) ? pack2(0.f, sv) : pack2(sv, 0.f);
        bf[2 * i] = (g & 2) ? 0 : sp; bf[2 * i + 1] = (g & 2) ? sp : 0;
      }
      asm volatile("barrier.cluster.wait.aligned;" ::: "memory");
#pragma unroll
      for (int i = 0; i < 128; i++) acc[i] = 0.f;
      reg_fence<128>(acc);
      tag = __shfl_sync(0xffffffffu, epoch, 0) + 1;
      TH(3);
      if (slab && !late) gemv();
      {
        {
          mbar_wait(sb + BAR_XH, 0);
          TH(5);
          float ds[4] = {0.f, 0.f, 0.f, 0.f}, dq[4][4];
#pragma unroll
          for (int i = 0; i < 4; i++) { dq[i][0] = dq[i][1] = dq[i][2] = dq[i][3] = 0.f; }
#pragma unroll
          for (int i = 0; i < 8; i++) {
            uint32_t a[4];
            ldsm4(sb + SM_XROW + wg * ST1 + wq * 4096 + ((lane >> 3) & 1) * 2048 + i * 256 + (lane >> 4) * 128 + (lane & 7) * 16, a);
            mma16816(ds, a, ONE2, ONE2);
            mma1688(dq[0], a[0], a[1], a[0]); mma1688(dq[1], a[0], a[1], a[1]);
            mma1688(dq[2], a[2], a[3], a[2]); mma1688(dq[3], a[2], a[3], a[3]);
          }
          const bool dg = t == (g >> 1);
          const float q0 = dg ? ((g & 1) ? dq[0][1] + dq[2][1] : dq[0][0] + dq[2][0]) : 0.f;
          const float q1 = dg ? ((g & 1) ? dq[1][3] + dq[3][3] : dq[1][2] + dq[3][2]) : 0.f;
          float q = ((lane & 1) ? q1 : q0) + __shfl_xor_sync(0xffffffffu, (lane & 1) ? q0 : q1, 1);
          float sm = (lane & 1) ? ds[2] : ds[0];
          q += __shfl_xor_sync(0xffffffffu, q, 2);
#pragma unroll
          for (int o = 4; o <= 16; o <<= 1) { q += __shfl_xor_sync(0xffffffffu, q, o); sm += __shfl_xor_sync(0xffffffffu, sm, o); }
          const float mean = sm * (1.f / 1024.f);
          const float rd = rcp_f(rbf(sqrt_f(rbf(rbf(fmaxf(fmaf(-mean, mean, q * (1.f / 1024.f)), 0.f)) + 1e-5f))));
          const float mean1 = __shfl_sync(0xffffffffu, mean, 1), rd1 = __shfl_sync(0xffffffffu, rd, 1);
          const uint32_t rh = pack2(rd, rd1);
          if (lane == 0) st_pkt16(&g_lnst[8 * b0 + warp], pack2(-rbf(mean) * lo2f(rh), -rbf(mean1) * hi2f(rh)), rh, 0, tag);
          TH(6);
          if (tid == 0) TS(2);
        }
      }
    }
    if (slab && late) gemv();
    TILE_ROLES();
    const uint32_t xa0 = sb + SM_RING + (warp * 16 + (lane & 15)) * 128 + (((lane >> 4) ^ (lane & 7)) * 16);
    uint32_t V[16];
    {
      const uint4* mp = &g_rec[tag & 1][(b0 >> 1) & (NREP - 1)][RV * wg + (lane >> 2) * RS + (lane & 3)];
      const uint4* lp = &g_lnst[(8 * rt + warp) * 8 + (g >> 1)];
      mbar_wait(sb + BAR_FULL1, 0);
#pragma unroll
      for (int kk = 0; kk < 4; kk++) ldsm4(xa0 ^ (kk * 32), V + 4 * kk);
      uint4 v0 = make_uint4(1, 0, 0, 0), l0, l1;
      int it = 0;
      while ((uint32_t)clock() - c0 < HD) {}
      do { if (wq == 0) v0 = ld_pkt16(mp);
           l0 = ld_pkt16(lp); l1 = ld_pkt16(lp + 4); spin_guard(it); }
        while (!(__all_sync(0xffffffffu, v0.x != 0 && l0.w == tag && l1.w == tag)));
      TH(7);
      if (wq == 0) put_record(sb, 128 * wg + lane, v0);
      const uint32_t sel = (g & 1) ? 0x3232 : 0x1010;
      ln[0] = __byte_perm(l0.x, 0, sel); ln[1] = __byte_perm(l0.y, 0, sel);
      ln[2] = __byte_perm(l1.x, 0, sel); ln[3] = __byte_perm(l1.y, 0, sel);
      __syncwarp();
      if (lane < 2) mbar_arrive_cl(mapa(sb + BAR_G, lane));
      nb_sync(NB_CONS, 256);
      if (tid == 0) TS(3);
      TH(13);
    }

    const uint32_t rel = mapa(sb + SM_MISC, lane & 1) - SM_MISC;
    const uint32_t stsm_addr = sb + SM_STASH + wg * 16384 + (wq * 16 + (lane & 15)) * 128 + (((lane >> 4) ^ (lane & 7)) * 16);

    uint32_t ph = 0;
    uint32_t X[32];
    {
      const uint32_t tab0 = sb + SM_STASH + wg * 16384 + t * 16;
      const uint64_t db0 = mk_desc(sb + SM_RING + 16384, 8192);
      uint32_t A[2][16];
      uint32_t xa[4];
#pragma unroll
      for (int kk = 0; kk < 4; kk++) xa[kk] = xa0 ^ (kk * 32);
      uint32_t tab = tab0;
      reg_fence<4>(xa);
      asm volatile("{\n.reg .pred p;\nsetp.eq.u32 p, %4, 0;\n@p ld.shared.v4.u32 {%0,%1,%2,%3}, [%5];\n}"
        : "+r"(ln[2]), "+r"(ln[0]), "+r"(ln[3]), "+r"(ln[1]) : "r"(tag), "r"(sb));
      int hs = 2 * ct;
      uint4 R[4];
#pragma unroll
      for (int kk = 0; kk < 4; kk++) R[kk] = lds128(tab + (kk >> 1) * 2048 + (kk & 1) * 64);
#pragma unroll 1
      for (int k4 = 0; k4 < 4; k4++) {
#pragma unroll
        for (int s = 0; s < 4; s++) {
          uint32_t* a = A[s & 1];
          const int sn = (s + 1) & 3;
          const uint32_t pn = (k4 + (s == 3)) & 1;
          modulate_frags(a, V, R, ln);
          if (hs == (s & 2)) {
            if (s & 1) mbar_wait(sb + BAR_HS + 16 * wg, 0);
#pragma unroll
            for (int kk = 0; kk < 4; kk++) stsm4((stsm_addr + 4096) ^ (kk * 32), a[4 * kk], a[4 * kk + 1], a[4 * kk + 2], a[4 * kk + 3]);
            nb_arrive(NB_OST + wg, 160);
          }
          if (s == 0 && k4 == 0) TH(8);
          TQ(3 * s);
          if (s == 0 && k4 == 0 && tid == 0) { TS(6); TSC(61); }
          wg_fence();
#pragma unroll
          for (int kk = 0; kk < 4; kk++) wgmma_rs256<1>(acc, a + 4 * kk, db0 + s * (ST1 >> 4) + kk * 128);
          wg_commit();
          if (s == 3) TQ(12);
          if (s == 3 && k4 < 3) mbar_wait(sb + BAR_TAB + 8 * k4, 0);
          if (s == 3) TQ(13);
#pragma unroll
          for (int kk = 0; kk < 4; kk++) R[kk] = lds128(tab + (s + 1) * 128 + (kk >> 1) * 2048 + (kk & 1) * 64);
          wg_wait<1>();
          if (k4 == 0) TH(9 + s);
          TQ(3 * s + 1);
          reg_fence<16>(A[(s & 1) ^ 1]);
          if ((tid & 127) < 2 && (s | k4)) mbar_arrive_cl(rel + BAR_EMPTY1 + 8 * ((s + 3) & 3));
          if (s < 3 || k4 < 3) {
            mbar_wait(sb + BAR_FULL1 + 8 * sn, pn);
            TQ(3 * s + 2);
#pragma unroll
            for (int kk = 0; kk < 4; kk++) ldsm4(xa[kk] + sn * ST1, V + 4 * kk);
          }
        }
        tab += 512; hs -= 4;
      }
      mbar_wait(sb + BAR_HS + 16 * wg + 8, 0);
      wg_wait<0>();
      reg_fence<128>(acc);
    }
#pragma unroll 1
    for (int pair = 0; pair < 2; pair++) {
      uint32_t Q[32];
      TR(0);
      {
        if ((tid & 127) < 2) mbar_arrive_cl(rel + BAR_EMPTY1 + 8 * 3);
        if (pair == 1) mbar_wait(sb + BAR_STASH + 8 * wg, 1);
#pragma unroll
        for (int i = 0; i < 32; i++) Q[i] = pack2(acc[2 * i], acc[2 * i + 1]);
        const uint32_t qs = sb + SM_STASH + wg * 16384 + wq * 2048 + lane * 16;
#pragma unroll
        for (int i = 0; i < 8; i++)
          sts128(qs + (i & 3) * 512 + (i >> 2) * 8192, pack2(acc[64 + 8 * i], acc[65 + 8 * i]), pack2(acc[66 + 8 * i], acc[67 + 8 * i]),
                 pack2(acc[68 + 8 * i], acc[69 + 8 * i]), pack2(acc[70 + 8 * i], acc[71 + 8 * i]));
      }
      if (tid == 0) TS(8 + pair * 2);
      TR(1);
      float O[64], SL[32], SH[32];
      uint32_t PL[16], PH[16];
      SoftmaxState z;
      const uint64_t d0 = mk_desc(sb + SM_RING, 8192);
      {
        mbar_wait(sb + BAR_FULL1, ph);
        wg_fence();
        issue_qk(SL, Q, d0);
        wg_commit();
        issue_qk(SH, Q, d0 + 1024);
        wg_commit();
#pragma unroll
        for (int i = 0; i < 64; i++) O[i] = 0.f;
        reg_fence<64>(O);
        wg_wait<1>();
        reg_fence<32>(SL);
        softmax_start(z);
        softmax_half(SL, PL, O, z, true, tag);
        wg_wait<0>();
        reg_fence<32>(SH);
        if ((tid & 127) < 2) mbar_arrive_cl(rel + BAR_EMPTY1);
      }
      float lp0 = 0.f, lp1 = 0.f;
      uint32_t dB = (uint32_t)d0 + 1 * (ST1 >> 4), dA = (uint32_t)d0 + 2 * (ST1 >> 4);
      const uint32_t dBx = dB ^ ((uint32_t)d0 + 3 * (ST1 >> 4)), dAx = dA ^ (uint32_t)d0;
      uint32_t so = 0;
      bool ready = false;
#pragma unroll 1
      for (int i = 0; i < 7; i++) {
        TA(0);
        TR(2 + i);
        if (!ready) mbar_wait(sb + BAR_FULL1 + 8 + so, ph);
        TA(1);
        TA(2);
        wg_fence();
        issue_qk(SL, Q, (d0 & 0xffffffff00000000ull) | dB);
        if (i == 4) {
          __syncwarp();
          stage_o(O, lp0, lp1, stsm_addr);
        }
        wg_fence();
        issue_pv(O, PL, ((d0 & 0xffffffff00000000ull) | dB) + 1024, i != 4);
        wg_commit();
        if (i == 4) {
          nb_arrive(NB_OST + wg, 160);
        }
        TA(3);
        ph ^= i & 1;
        ready = mbar_test(sb + BAR_FULL1 + 16 - so, ph);
        softmax_half(SH, PH, O, z, false, tag);
        TA(4);
        wg_wait<0>();
        TA(5);
        reg_fence<32>(SL); reg_fence<16>(PL);
        if ((tid & 127) < 2) mbar_arrive_cl(rel + BAR_EMPTY1 + 8 + so);
        if (!ready) mbar_wait(sb + BAR_FULL1 + 16 - so, ph);
        TA(6);
        wg_fence();
        issue_qk(SH, Q, (d0 & 0xffffffff00000000ull) | dA);
        wg_commit();
        issue_pv(O, PH, ((d0 & 0xffffffff00000000ull) | dA) + 1024, 1);
        wg_commit();
        if (i == 2) {
          wg_wait<1>();
          reg_fence<32>(Q);
          const uint32_t qs = sb + SM_STASH + wg * 16384 + wq * 2048 + lane * 16;
#pragma unroll
          for (int j = 0; j < 8; j++) { const uint4 v = lds128(qs + (j & 3) * 512 + (j >> 2) * 8192); Q[4 * j] = v.x; Q[4 * j + 1] = v.y; Q[4 * j + 2] = v.z; Q[4 * j + 3] = v.w; }
        }
        TA(10);
        if (i == 3) { lp0 = z.l0; lp1 = z.l1; row_rcp(lp0, lp1); softmax_start(z); }
        TA(7);
        so ^= 16; dB ^= dBx; dA ^= dAx;
        ready = mbar_test(sb + BAR_FULL1 + 8 + so, ph);
        softmax_half(SL, PL, O, z, i == 3, tag);
        TA(8);
        wg_wait<0>();
        TA(9);
        reg_fence<32>(SH); reg_fence<16>(PH); reg_fence<64>(O); reg_fence<32>(Q);
        if ((tid & 127) < 2) mbar_arrive_cl(rel + BAR_EMPTY1 + so);
      }
      TAFLUSH();
      TR(9);
      {
        if (!ready) mbar_wait(sb + BAR_FULL1 + 8 * 3, ph);
        ph ^= 1;
        const uint64_t dv = d0 + 3 * (ST1 >> 4);
        wg_fence();
        issue_pv(O, PL, dv, 1);
        wg_commit();
        bb_fence(tag);
        softmax_half(SH, PH, O, z, false, tag);
        wg_fence();
        issue_pv(O, PH, dv + 1024, 1);
        wg_commit();
        TR(10);
        row_rcp(z.l0, z.l1);
        mbar_wait(sb + (pair ? BAR_X : BAR_STASH) + 8 * wg, 0);
#pragma unroll
        for (int kk = 0; kk < 8; kk++) ldsm4((stsm_addr + (kk >> 2) * 8192) ^ ((kk & 3) * 32), X + 4 * kk);
        reg_fence<32>(X);
        __syncwarp();
        wg_wait<0>();
        reg_fence<64>(O);
        TR(11);
        if ((tid & 127) < 2) mbar_arrive_cl(rel + BAR_EMPTY1 + 8 * 3);
        stage_o(O, z.l0, z.l1, stsm_addr);
        nb_arrive(NB_OST + wg, 160);
      }
      TR(12);
      if (tid == 0) { TS(9 + pair * 2); TSC(62); }
      if (pair == 1) break;
      {
        mbar_wait(sb + BAR_FULL1, ph);
        const uint64_t da = mk_desc(sb + SM_RING + wg * 8192, 16), db = mk_desc(sb + SM_RING + 16384, 8192);
        wg_fence();
        wgmma_ss256_z<1>(acc, da, db);
#pragma unroll
        for (int kk = 1; kk < 4; kk++) wgmma_ss256<1>(acc, da + kk * 2, db + kk * 128, 1);
        wg_commit();
      }
#pragma unroll 1
      for (int kt = 1; kt < 16; kt++) {
        const uint32_t s = kt & 3;
        if (s == 0) ph ^= 1;
        mbar_wait(sb + BAR_FULL1 + 8 * s, ph);
        const uint32_t st = sb + SM_RING + s * ST1;
        const uint64_t da = mk_desc(st + wg * 8192, 16), db = mk_desc(st + 16384, 8192);
        wg_fence();
#pragma unroll
        for (int kk = 0; kk < 4; kk++) wgmma_ss256<1>(acc, da + kk * 2, db + kk * 128, 1);
        wg_commit();
        wg_wait<1>();
        if ((tid & 127) < 2) mbar_arrive_cl(rel + BAR_EMPTY1 + 8 * ((s + 3) & 3));
      }
      ph ^= 1;
      wg_wait<0>();
      reg_fence<128>(acc);
      TR(13);
    }

    uint4 WG[16], WU[16];
    const int fp = 64 * warp + 8 * g + t;
    uint32_t fsb0, fsb1, fcb0, fcb1, fgb0, fgb1;
    const uint32_t gu_base = sb + SM_RING + (warp >> 1) * ST1 + 32768 + (warp & 1) * 8192;
    const uint32_t gu_addr = gu_base + t * 128 + (g & 1) * 64 + ((g >> 1) ^ t) * 16;
    {
      const uint64_t da0 = mk_desc(sb + SM_RING + __shfl_sync(0xffffffffu, wg, 0) * 8192, 16), db0 = mk_desc(sb + SM_RING + 16384, 8192);
#pragma unroll
      for (int n = 0; n < 4 + 5 * X_PEEL; n++) {
        const int s = n < 4 ? n : (n - 4) % 5;
        mbar_wait(sb + BAR_FULL1 + 8 * s, n < 4 ? 0 : ((n - 4) / 5 + (s < 4)) & 1);
        if (n < 4) TSX(40 + wg * 6 + n);
        const uint64_t da = da0 + s * (ST1 >> 4), db = db0 + s * (ST1 >> 4);
        wg_fence();
        if (n == 0) wgmma_ss128_z<1>(acc, da, db); else wgmma_ss128<1>(acc, da, db, 1);
#pragma unroll
        for (int kk = 1; kk < 4; kk++) wgmma_ss128<1>(acc, da + kk * 2, db + kk * 128, 1);
        wg_commit();
        if (n == 1) {
          mbar_wait(sb + BAR_OF, 0);
          const uint2* mp = &g_mod[3 * 512 + fp];
          fsb0 = ld_pkt8(mp).x; fsb1 = ld_pkt8(mp + 4).x; fcb0 = ld_pkt8(mp + 512).x; fcb1 = ld_pkt8(mp + 516).x;
          fgb0 = ld_pkt8(mp + 1024).x; fgb1 = ld_pkt8(mp + 1028).x;
        }
        if (n == 0 && b < NFFN) mbar_wait(sb + BAR_FFN, 0);
        {
          constexpr int NT = 4 + 5 * X_PEEL, F0 = NT > 16 ? NT - 16 : 0;
#pragma unroll
          for (int i = 0; i < 16; i++) if (F0 + i * (NT - F0) / 16 == n) WG[i] = lds128(gu_addr + i * 512);
        }
        if (n > 0) {
          wg_wait<1>();
          if ((tid & 127) < 2) mbar_arrive_cl(rel + BAR_EMPTY1 + 8 * (n == 4 ? 3 : s ? s - 1 : 4));
        }
      }
      TSX(44 + wg * 6);
      {
        uint32_t dep = 0;
#pragma unroll
        for (int i = 0; i < 16; i++) dep ^= WG[i].x;
        if (__shfl_sync(0xffffffffu, tag, dep & 31) == tag && lane == 2) mbar_arrive(sb + BAR_TFREE);
      }
      {
        uint32_t so = 0, sp = 4 * 8, par = X_PEEL + 1;
#pragma unroll 1
        for (int n = 4 + 5 * X_PEEL; n < 64; n++) {
          mbar_wait(sb + BAR_FULL1 + so, (par + (so >> 5)) & 1);
          const uint64_t da = da0 + so * (ST1 >> 7), db = db0 + so * (ST1 >> 7);
          wg_fence();
#pragma unroll
          for (int kk = 0; kk < 4; kk++) wgmma_ss128<1>(acc, da + kk * 2, db + kk * 128, 1);
          wg_commit();
          wg_wait<1>();
          if ((tid & 127) < 2) mbar_arrive_cl(rel + BAR_EMPTY1 + sp);
          sp = so; so += 8;
          if (so == 40) { so = 0; par++; }
        }
      }
    }
    mbar_wait(sb + BAR_VEC, 0);
    const int lrow = warp * 16 + g;
    uint2 ga[8], b1[8];
#pragma unroll
    for (int kk = 0; kk < 8; kk++) { ga[kk] = lds64(sb + SM_GA + kk * 32 + t * 8); b1[kk] = lds64(sb + SM_B1 + min(g, 3) * 32 + t * 8 + kk * 128); }
    uint4* const stp = &g_stats[b * 128 + lrow + 8 * t];
    bb_fence(tag);
    wg_wait<0>();
    reg_fence<64>(acc);
    if (tid == 0) { TS(12); TSC(63); }

    TT(0);
    {
      float d1[4] = {0.f, 0.f, 0.f, 0.f}, d2[4] = {0.f, 0.f, 0.f, 0.f}, d3[4] = {0.f, 0.f, 0.f, 0.f};
      float d4[4] = {0.f, 0.f, 0.f, 0.f}, d5[4] = {0.f, 0.f, 0.f, 0.f};
#pragma unroll
      for (int kk = 0; kk < 8; kk++) {
        uint32_t* x = X + 4 * kk;
        x[0] = hfma2(ga[kk].x, pack2(acc[8 * kk + 0], acc[8 * kk + 1]), x[0]);
        x[1] = hfma2(ga[kk].x, pack2(acc[8 * kk + 2], acc[8 * kk + 3]), x[1]);
        x[2] = hfma2(ga[kk].y, pack2(acc[8 * kk + 4], acc[8 * kk + 5]), x[2]);
        x[3] = hfma2(ga[kk].y, pack2(acc[8 * kk + 6], acc[8 * kk + 7]), x[3]);
        mma16816(d1, x, b1[kk].x, b1[kk].y);
        mma1688(d2, x[0], x[1], x[0]); mma1688(d3, x[0], x[1], x[1]);
        mma1688(d4, x[2], x[3], x[2]); mma1688(d5, x[2], x[3], x[3]);
      }
      const int qb = lane & 28;
      const float q0 = __shfl_sync(0xffffffffu, (g & 1) ? d2[1] + d4[1] : d2[0] + d4[0], qb | (g >> 1));
      const float q1 = __shfl_sync(0xffffffffu, (g & 1) ? d3[3] + d5[3] : d3[2] + d5[2], qb | (g >> 1));
      const float e0 = __shfl_xor_sync(0xffffffffu, t ? d1[0] : d1[3], 1);
      const float e1 = __shfl_sync(0xffffffffu, d1[2], qb);
      if (t < 2) st_pkt16(stp, __float_as_uint(t ? e1 : d1[0]), __float_as_uint(t ? q1 : q0),
                          __float_as_uint((t ? d1[2] : d1[1]) + e0), tag);
    }
    TSY(13);
    TT(1);
    float mb, rd, den, br;
    {
      const uint4* sp = &g_stats[(rt * 8 + 4 * (t & 1)) * 128 + lrow + 4 * (t & 2)];
      mbar_wait(sb + BAR_EMPTY1 + 8 * 3, 0);
#pragma unroll
      for (int kk = 0; kk < 8; kk++) stsm4((stsm_addr - SM_STASH + SM_X2 + (kk >> 2) * 8192) ^ ((kk & 3) * 32), X[4 * kk], X[4 * kk + 1], X[4 * kk + 2], X[4 * kk + 3]);
      if (b < NFFN) mbar_wait(sb + BAR_FFN, 1);
#pragma unroll
      for (int i = 0; i < WU1; i++) WU[i] = lds128(gu_addr + i * 512);
      bb_fence(tag);
      TT(2);
      uint4 v0, v1, v2, v3;
      int it = 0;
      do { v0 = ld_pkt16(sp); v1 = ld_pkt16(sp + 128); v2 = ld_pkt16(sp + 256); v3 = ld_pkt16(sp + 384); spin_guard(it); }
        while (!(__all_sync(0xffffffffu, v0.w == tag && v1.w == tag && v2.w == tag && v3.w == tag)));
      TT(3);
      float sm = (__uint_as_float(v0.x) + __uint_as_float(v1.x)) + (__uint_as_float(v2.x) + __uint_as_float(v3.x));
      float sq = (__uint_as_float(v0.y) + __uint_as_float(v1.y)) + (__uint_as_float(v2.y) + __uint_as_float(v3.y));
      float dt = (__uint_as_float(v0.z) + __uint_as_float(v1.z)) + (__uint_as_float(v2.z) + __uint_as_float(v3.z));
      sm += __shfl_xor_sync(0xffffffffu, sm, 1); sq += __shfl_xor_sync(0xffffffffu, sq, 1); dt += __shfl_xor_sync(0xffffffffu, dt, 1);
      const uint2 scal = lds64(sb + SM_SCAL);
      const float mu = sm * (1.f / 1024.f);
      mb = rbf(mu);
      den = rbf(sqrt_f(rbf(rbf(fmaxf(fmaf(-mu, mu, sq * (1.f / 1024.f)), 0.f)) + 1e-5f)));
      rd = rcp_f(den);
      br = fmaf(fmaf(-mb, __uint_as_float(scal.x), dt), rd, __uint_as_float(scal.y));
    }
    TSY(14);
    TT(4);
    {
      const int rb = __float_as_int(br);
      const int key = ((rb ^ ((rb >> 31) & 0x7fffffff)) | 127) - (lrow + 4 * (t & 2));
      if (key == __reduce_max_sync(0xffffffffu, key)) sts64(sb + SM_AMAX + warp * 8, (uint32_t)key, pack2(mb, den));
      __syncwarp();
      nb_arrive(NB_AMAX, 288);
    }
    TT(5);
    const uint4* ep = &g_entry[(warp * 16 + (lane & 15)) * ESTR];
    const uint32_t slot = sb + SM_STASH + wg * 8192 + (tid & 127) * 16;
    cp_async16(slot, ep);
    {
      const float rh = rbf(rd);
      const uint32_t u = pack2(-mb * rh, rh);
      const int qb = lane & 28;
      const uint32_t u0 = __shfl_sync(0xffffffffu, u, qb), u1 = __shfl_sync(0xffffffffu, u, qb | 2);
      const uint32_t m0 = __byte_perm(u0, 0, 0x1010), h0 = __byte_perm(u0, 0, 0x3232);
      const uint32_t m1 = __byte_perm(u1, 0, 0x1010), h1 = __byte_perm(u1, 0, 0x3232);
#pragma unroll
      for (int j = 0; j < 16; j++) {
        const uint4 rec = lds128(sb + SM_REC + (4 * j + t) * 16);
        X[2 * j] = hfma2(rec.z, hfma2(hfma2(X[2 * j], h0, m0), rec.x, rec.y), X[2 * j]);
        X[2 * j + 1] = hfma2(rec.z, hfma2(hfma2(X[2 * j + 1], h1, m1), rec.x, rec.y), X[2 * j + 1]);
      }
#pragma unroll
      for (int kk = 0; kk < 8; kk++) stsm4((stsm_addr - SM_STASH + SM_OUT + (kk >> 2) * 8192) ^ ((kk & 3) * 32), X[4 * kk], X[4 * kk + 1], X[4 * kk + 2], X[4 * kk + 3]);
    }
    cp_async_wait();
    uint4 ent = lds128(slot);
    TSY(16);
    TT(6);
    int wrow;
    uint32_t xs0, xs1, hs0, hs1;
    uint32_t WD[64];
    const uint32_t wd_addr = sb + SM_RING + wg * ST1 + wq * 8192 + ((lane & 7) + ((lane >> 4) << 3)) * 128 + ((((lane >> 3) & 1) ^ (lane & 7)) * 16);
    {
      int gmax;
      auto leader = [&]() {
        gmax = __reduce_max_sync(0xffffffffu, ent.w == tag ? (int)ent.x : (int)0x8000000f);
        return ~gmax & 15;
      };
      int wt = leader(), it = 0;
      TT(7);
      nb_arrive(NB_OST + wg, 160);
      TT(8);
      cp_async16(slot + 2048, &g_cand[(wt * 8 + warp) * 32 + lane]);
      if (ent.w != tag) cp_async16(slot, ep);
#pragma unroll
      for (int i = WU1; i < 16; i++) WU[i] = lds128(gu_addr + i * 512);
      if (b < NFFN) mbar_wait(sb + BAR_FFN + 8, 0);
#pragma unroll
      for (int mt = 0; mt < 8; mt++)
#pragma unroll
        for (int s = 0; s < 2; s++) ldsm4t((wd_addr + (mt >> 2) * 4096 + s * 2048) ^ ((mt & 3) * 32), WD + (mt * 2 + s) * 4);
      cp_async_wait();
      uint4 v = lds128(slot + 2048);
      ent = lds128(slot);
      TT(9);
      while (true) {
        const int have = wt;
        wt = leader();
        if (__all_sync(0xffffffffu, ent.w == tag && have == wt && v.z == tag)) break;
        v = ld_pkt16(&g_cand[(wt * 8 + warp) * 32 + lane]);
        if (ent.w != tag) ent = ld_pkt16(ep);
        spin_guard(it);
      }
      TT(10);
      ent.x = gmax ^ ((gmax >> 31) & 0x7fffffff);
      wrow = __shfl_sync(0xffffffffu, ent.y, wt); ent.z = __shfl_sync(0xffffffffu, ent.z, wt);
      xs0 = v.x; xs1 = v.y;
      const uint32_t mm = __byte_perm(ent.z, 0, 0x1010);
      const float rs = rcp_f(hi2f(ent.z));
      const uint32_t e0 = hsub2(xs0, mm), e1 = hsub2(xs1, mm);
      hs0 = hfma2(pack2(lo2f(e0) * rs, hi2f(e0) * rs), hadd2(fcb0, ONE2), fsb0);
      hs1 = hfma2(pack2(lo2f(e1) * rs, hi2f(e1) * rs), hadd2(fcb1, ONE2), fsb1);
    }
    if ((tid & 127) == 0) sts32(sb + SM_WROW + 4 * wg, wrow);
    nb_arrive(NB_WIN + wg, 160);
    TSY(17);
    TT(11);
    if (b < NFFN) {
      float da[4][4];
#pragma unroll
      for (int i = 0; i < 4; i++) { da[i][0] = da[i][1] = da[i][2] = da[i][3] = 0.f; }
      const uint32_t selv = ((g & 1) ? 0x1044 : 0x4410) + ((g & 4) ? ((g & 1) ? 0x2200 : 0x0022) : 0);
      const uint32_t sel0 = (g & 2) ? 0x4444 : selv, sel1 = (g & 2) ? selv : 0x4444;
#pragma unroll
      for (int s = 0; s < 16; s++) {
        const uint32_t v = __shfl_sync(0xffffffffu, (s & 1) ? hs1 : hs0, 4 * (s >> 1) + t);
        const uint32_t b0 = __byte_perm(v, 0, sel0), b1 = __byte_perm(v, 0, sel1);
        const uint32_t a0[4] = {WG[s].x, WG[s].y, WG[s].z, WG[s].w};
        const uint32_t a1[4] = {WU[s].x, WU[s].y, WU[s].z, WU[s].w};
        mma16816(da[(s & 1) * 2], a0, b0, b1);
        mma16816(da[(s & 1) * 2 + 1], a1, b0, b1);
      }
      {
        float v[4];
#pragma unroll
        for (int i = 0; i < 4; i++) {
          const float vg = da[0][i] + da[2][i], vu = da[1][i] + da[3][i];
          v[i] = ((g & 1) ? vu : vg) + __shfl_xor_sync(0xffffffffu, (g & 1) ? vg : vu, 6);
        }
        if ((t >> 1) == (g & 1))
          sts128(gu_base + (g & 1) * 128 + (g >> 1) * 32 + (t & 1) * 16, __float_as_uint(v[0]), __float_as_uint(v[1]), __float_as_uint(v[2]), __float_as_uint(v[3]));
      }
      TT(12);
      nb_sync(NB_CONS, 256);
      float gp[8], up[8];
#pragma unroll
      for (int w = 0; w < 8; w++) {
        const uint32_t a = sb + SM_RING + (w >> 1) * ST1 + 32768 + (w & 1) * 8192 + lane * 4;
        gp[w] = lds_f32(a); up[w] = lds_f32(a + 128);
      }
      const float gsum = ((gp[0] + gp[1]) + (gp[2] + gp[3])) + ((gp[4] + gp[5]) + (gp[6] + gp[7]));
      const float usum = ((up[0] + up[1]) + (up[2] + up[3])) + ((up[4] + up[5]) + (up[6] + up[7]));
      const float act = rbf(silu_f(rbf(gsum))) * rbf(usum);
      TT(13);
      const uint32_t ap = pack2(act, __shfl_down_sync(0xffffffffu, act, 1));
      const uint32_t b00 = __shfl_sync(0xffffffffu, ap, 2 * t), b01 = __shfl_sync(0xffffffffu, ap, 2 * t + 8);
      const uint32_t b10 = __shfl_sync(0xffffffffu, ap, 2 * t + 16), b11 = __shfl_sync(0xffffffffu, ap, 2 * t + 24);
      float y[8][4];
#pragma unroll
      for (int mt = 0; mt < 8; mt++) {
        y[mt][0] = y[mt][1] = y[mt][2] = y[mt][3] = 0.f;
        mma16816(y[mt], WD + (mt * 2) * 4, b00, b01);
        mma16816(y[mt], WD + (mt * 2 + 1) * 4, b10, b11);
      }
#pragma unroll
      for (int e = 0; e < 2; e++) {
        const float v0 = t == 0 ? y[e][0] : t == 1 ? y[2 + e][0] : t == 2 ? y[4 + e][0] : y[6 + e][0];
        const float v1 = t == 0 ? y[e][2] : t == 1 ? y[2 + e][2] : t == 2 ? y[4 + e][2] : y[6 + e][2];
        const int f = 16 * warp + 2 * (2 * t + e) + (g >> 2);
        st_pkt16(&g_ypart[(f * NFFN + b) * 4 + (g & 3)], __float_as_uint(v0), __float_as_uint(v1), tag, 0);
      }
    }
    TSY(18);
    TT(14);
    {
      const int pw = warp - (warp > (b >> 4));
      if (warp != (b >> 4)) {
        const uint4* yp = &g_ypart[b * NFFN * 4 + pw * 64 + lane];
        uint4 v0, v1;
        int it = 0;
        { const uint32_t c1 = clock(); while ((uint32_t)clock() - c1 < (b < NFFN ? YD : YD + 1500)) {} }
        do { v0 = ld_pkt16(yp); v1 = ld_pkt16(yp + 32); spin_guard(it); }
        while (!(__all_sync(0xffffffffu, v0.z == tag && v1.z == tag)));
        float y0 = __uint_as_float(v0.x) + __uint_as_float(v1.x), y1 = __uint_as_float(v0.y) + __uint_as_float(v1.y);
#pragma unroll
        for (int o = 4; o <= 16; o <<= 1) { y0 += __shfl_xor_sync(0xffffffffu, y0, o); y1 += __shfl_xor_sync(0xffffffffu, y1, o); }
        if (lane < 4) sts64(sb + SM_YRED + pw * 32 + lane * 8, __float_as_uint(y0), __float_as_uint(y1));
      }
    }
    TT(15);
    if (warp != (b >> 4)) {
      nb_arrive(NB_CONS, 256);
    } else {
      nb_sync(NB_CONS, 256);
      float y0 = 0.f, y1 = 0.f;
      if (lane < 28) { const uint2 e = lds64(sb + SM_YRED + lane * 8); y0 = __uint_as_float(e.x); y1 = __uint_as_float(e.y); }
#pragma unroll
      for (int o = 4; o <= 16; o <<= 1) { y0 += __shfl_xor_sync(0xffffffffu, y0, o); y1 += __shfl_xor_sync(0xffffffffu, y1, o); }
      const int src = 2 * (t & 1);
      const float ya = __shfl_sync(0xffffffffu, y0, src), yb = __shfl_sync(0xffffffffu, y0, src + 1);
      const float yc = __shfl_sync(0xffffffffu, y1, src), yd = __shfl_sync(0xffffffffu, y1, src + 1);
      if (g == ((b >> 1) & 7) && (t >> 1) == (b & 1)) {
        const float rs = rbf(__uint_as_float(ent.x));
        const float sg = sigmoid_f(rs);
        const uint32_t sg2 = pack2(sg, sg);
        const uint32_t o0 = hadd2(xs0, hmul2(fgb0, hadd2(hs0, hmul2(pack2(ya, yb), sg2))));
        const uint32_t o1 = hadd2(xs1, hmul2(fgb1, hadd2(hs1, hmul2(pack2(yc, yd), sg2))));
        uint32_t* op = reinterpret_cast<uint32_t*>(p.out + (size_t)wrow * 1024) + fp;
        op[0] = o0; op[4] = o1;
      }
      if (b == 0) {
        if (lane < 8) st_relaxed(&p.sc->ticket[lane * 32], 0);
        st_relaxed(&p.sc->epoch[lane], tag);
      }
      if (lane == 0) TS(19);
    }
  }
}

typedef CUresult (*EncodeFn)(CUtensorMap*, CUtensorMapDataType, cuuint32_t, void*, const cuuint64_t*, const cuuint64_t*,
                             const cuuint32_t*, const cuuint32_t*, CUtensorMapInterleave, CUtensorMapSwizzle,
                             CUtensorMapL2promotion, CUtensorMapFloatOOBfill);

CUtensorMap make_map(EncodeFn enc, const void* ptr, uint64_t rows, uint64_t cols, uint32_t box_rows, uint32_t box_cols, CUtensorMapSwizzle sw) {
  CUtensorMap m;
  cuuint64_t dims[2] = {cols, rows};
  cuuint64_t strides[1] = {cols * 2};
  cuuint32_t box[2] = {box_cols, box_rows};
  cuuint32_t es[2] = {1, 1};
  enc(&m, CU_TENSOR_MAP_DATA_TYPE_BFLOAT16, 2, const_cast<void*>(ptr), dims, strides, box, es, CU_TENSOR_MAP_INTERLEAVE_NONE, sw,
      CU_TENSOR_MAP_L2_PROMOTION_L2_128B, CU_TENSOR_MAP_FLOAT_OOB_FILL_NONE);
  return m;
}

CUtensorMap make_map3(EncodeFn enc, const void* ptr, uint64_t rows, uint64_t cols, uint32_t box_rows, uint32_t box_blks) {
  CUtensorMap m;
  cuuint64_t dims[3] = {64, rows, cols / 64};
  cuuint64_t strides[2] = {cols * 2, 128};
  cuuint32_t box[3] = {64, box_rows, box_blks};
  cuuint32_t es[3] = {1, 1, 1};
  enc(&m, CU_TENSOR_MAP_DATA_TYPE_BFLOAT16, 3, const_cast<void*>(ptr), dims, strides, box, es, CU_TENSOR_MAP_INTERLEAVE_NONE,
      CU_TENSOR_MAP_SWIZZLE_128B, CU_TENSOR_MAP_L2_PROMOTION_L2_128B, CU_TENSOR_MAP_FLOAT_OOB_FILL_NONE);
  return m;
}

}

extern "C" void kernel_launch(void* const* d_in, const int* in_sizes, int n_in, void* d_out, int out_size) {
  (void)in_sizes; (void)n_in; (void)out_size;
  Params p;
  p.x = (const bf16*)d_in[0]; p.kc = (const bf16*)d_in[1]; p.vc = (const bf16*)d_in[2];
  p.wq = (const bf16*)d_in[3]; p.wo = (const bf16*)d_in[4]; p.w_r = (const bf16*)d_in[6];
  p.wg = (const bf16*)d_in[7]; p.wu = (const bf16*)d_in[8]; p.wd = (const bf16*)d_in[9];
  p.c = (const bf16*)d_in[10]; p.w_mod = (const bf16*)d_in[11]; p.out = (bf16*)d_out;

  void* fn = nullptr;
  cudaDriverEntryPointQueryResult st;
  cudaGetDriverEntryPoint("cuTensorMapEncodeTiled", &fn, cudaEnableDefault, &st);
  EncodeFn enc = (EncodeFn)fn;
  void* scp = nullptr;
  cudaGetSymbolAddress(&scp, g_scratch);
  p.sc = (Scratch*)scp;
  void *hp = p.sc->h, *op = p.sc->o;
  const CUtensorMapSwizzle S128 = CU_TENSOR_MAP_SWIZZLE_128B;
  CUtensorMap mH = make_map(enc, hp, 2048, 1024, 64, 64, S128);
  CUtensorMap mWq = make_map3(enc, p.wq, 1024, 4096, 64, 4);
  CUtensorMap mK = make_map(enc, p.kc, 8192, 128, 64, 64, S128);
  CUtensorMap mV = make_map(enc, p.vc, 8192, 128, 64, 64, S128);
  CUtensorMap mO = make_map(enc, op, 2048, 4096, 64, 64, S128);
  CUtensorMap mWo = make_map3(enc, p.wo, 4096, 1024, 64, 2);
  CUtensorMap mX = make_map(enc, p.x, 2048, 1024, 64, 64, S128);
  CUtensorMap mOut = make_map(enc, p.out, 2048, 1024, 64, 64, S128);
  CUtensorMap mWg = make_map(enc, p.wg, 1024, 3584, 256, 32, CU_TENSOR_MAP_SWIZZLE_64B);
  CUtensorMap mWu = make_map(enc, p.wu, 1024, 3584, 256, 32, CU_TENSOR_MAP_SWIZZLE_64B);
  CUtensorMap mWd = make_map3(enc, p.wd, 3584, 1024, 32, 8);
  CUtensorMap mWm = make_map(enc, p.w_mod, 1024, 6144, 16, 256, CU_TENSOR_MAP_SWIZZLE_NONE);
  CUtensorMap mWh = make_map(enc, p.w_mod, 1024, 6144, 256, 32, CU_TENSOR_MAP_SWIZZLE_64B);
  CUtensorMap mWs = make_map(enc, p.w_mod, 1024, 6144, 128, 128, CU_TENSOR_MAP_SWIZZLE_NONE);
  cudaFuncSetAttribute(fused_kernel, cudaFuncAttributeMaxDynamicSharedMemorySize, SMEM_BYTES);
  fused_kernel<<<NCTA, NTHREADS, SMEM_BYTES>>>(p, mH, mWq, mK, mV, mO, mWo, mX, mOut, mWg, mWu, mWd, mWm, mWs, mWh);
}
```

```cpp
#include <cuda_runtime.h>
#include <cuda_bf16.h>
#include <cuda.h>
#include <stdint.h>
#include <stddef.h>

#define UPD 200
#define GATED 700
#define PFW 100
#define PLD 200
#define WL 3500
#define SPT 5000
#define HD 6000
#define YD 500
#define PEEL 1
#define WU1 12

namespace {

typedef __nv_bfloat16 bf16;

constexpr int NTHREADS = 384;
constexpr int NMAIN = 128;
constexpr int NCTA = 132;
constexpr int RS = 8, RV = 16 * RS + 64;
constexpr int NREP = 4;
constexpr int NFFN = 112;

constexpr uint32_t SM_RING = 0;
constexpr uint32_t ST1 = 49152;
constexpr uint32_t ST2 = 32768;
constexpr int NST2 = 6;
constexpr uint32_t SM_STASH = 196608;
constexpr uint32_t SM_MISC = 229376;
constexpr uint32_t BAR_FULL1 = SM_MISC + 0;
constexpr uint32_t BAR_EMPTY1 = SM_MISC + 40;
constexpr uint32_t BAR_FULL2 = SM_MISC + 0;
constexpr uint32_t BAR_EMPTY2 = SM_MISC + 48;
constexpr uint32_t BAR_STASH = SM_MISC + 160;
constexpr uint32_t BAR_SFREE = SM_MISC + 176;
constexpr uint32_t BAR_TFREE = SM_MISC + 184;
constexpr uint32_t BAR_FFN = SM_MISC + 192;
constexpr uint32_t BAR_VEC = SM_MISC + 208;
constexpr uint32_t BAR_RED = SM_MISC + 216;
constexpr uint32_t BAR_XH = SM_MISC + 152;
constexpr uint32_t BAR_HS = SM_MISC + 80;
constexpr uint32_t BAR_G = SM_MISC + 112;
constexpr uint32_t BAR_T1 = SM_MISC + 120;
constexpr uint32_t BAR_HF = SM_MISC + 128;
constexpr uint32_t BAR_X = SM_MISC + 136;
constexpr uint32_t BAR_OF = SM_MISC + 224;
constexpr uint32_t BAR_ROLE = SM_MISC + 240;
constexpr uint32_t SM_ROLE = SM_MISC + 248;
constexpr uint32_t SM_GA = SM_MISC + 256;
constexpr uint32_t SM_SCAL = SM_MISC + 512;
constexpr uint32_t SM_WROW = SM_MISC + 520;
constexpr uint32_t SM_AMAX = SM_MISC + 528;
constexpr uint32_t SM_YRED = SM_MISC + 656;
constexpr uint32_t SM_X2 = 2 * ST1, SM_OUT = 3 * ST1;
constexpr uint32_t SM_REC = SM_MISC + 1024;
constexpr uint32_t BAR_TAB = SM_MISC + 1000;
constexpr uint32_t BAR_CAND = SM_MISC + 880;
constexpr uint32_t SM_CAND = SM_MISC + 888;
constexpr uint32_t BAR_WH = SM_MISC + 960;
constexpr uint32_t SM_WSLAB = 2 * 49152 + 16384;
constexpr uint32_t SM_XROW = 2 * 49152;
constexpr uint32_t SM_RED = SM_MISC + 2048;
constexpr uint32_t SM_B1 = SM_MISC + 2048;
constexpr uint32_t SMEM_BYTES = 232448;

constexpr int NB_CONS = 1, NB_WIN = 2  , NB_OST = 4  , NB_AMAX = 6;

struct __align__(1024) Scratch {
  uint32_t epoch[32];
  uint32_t hflag[16 * 32];
  uint32_t oflag[64 * 32];
  uint2 vdone[4 * 16];
  uint32_t pad[96 + 512];
  uint32_t ticket[8 * 32];
  uint2 mod[3072];
  uint4 rec[2][NREP][2 * RV];
  uint4 lnst[1024];
  uint4 entry[8 * 16 * 8];
  uint4 cand[16 * 8 * 32];
  uint4 stats[16 * 8 * 128];
  uint4 ypart[128 * NFFN * 4];
  unsigned long long ts[NCTA * 64];
  uint16_t h[2048 * 1024];
  uint16_t o[2048 * 4096];
};
__device__ Scratch g_scratch;
#define g_epoch (p.sc->epoch[0])
#define g_hflag (p.sc->hflag)
#define g_oflag (p.sc->oflag)
#define g_mod (p.sc->mod)
#define g_entry (p.sc->entry)
#define g_cand (p.sc->cand)
#define g_stats (p.sc->stats)
#define g_ypart (p.sc->ypart)
#define g_vdone (p.sc->vdone)
#define g_lnst (p.sc->lnst)
#define g_rec (p.sc->rec)
#define g_ts (p.sc->ts)
#define g_h (p.sc->h)

struct Params {
  const bf16* w_mod; const bf16* c; Scratch* sc; const bf16* x; const bf16* w_r; bf16* out;
  const bf16* wq; const bf16* wo; const bf16* wg; const bf16* wu; const bf16* wd; const bf16* kc; const bf16* vc;
};

__device__ __forceinline__ uint32_t smem_u32(const void* p) { return (uint32_t)__cvta_generic_to_shared(p); }
__device__ __forceinline__ void mbar_init(uint32_t bar, uint32_t cnt) { asm volatile("mbarrier.init.shared::cta.b64 [%0], %1;" :: "r"(bar), "r"(cnt) : "memory"); }
__device__ __forceinline__ void mbar_expect_tx(uint32_t bar, uint32_t bytes) { asm volatile("mbarrier.arrive.expect_tx.shared::cta.b64 _, [%0], %1;" :: "r"(bar), "r"(bytes) : "memory"); }
__device__ __forceinline__ void mbar_arrive(uint32_t bar) { asm volatile("mbarrier.arrive.shared::cta.b64 _, [%0];" :: "r"(bar) : "memory"); }
__device__ __forceinline__ void mbar_arrive_cl(uint32_t cluster_addr) { asm volatile("mbarrier.arrive.shared::cluster.b64 _, [%0];" :: "r"(cluster_addr) : "memory"); }
__device__ __forceinline__ uint32_t mapa(uint32_t addr, uint32_t cta) { uint32_t r; asm("mapa.shared::cluster.u32 %0, %1, %2;" : "=r"(r) : "r"(addr), "r"(cta)); return r; }
__device__ __forceinline__ bool mbar_test(uint32_t bar, uint32_t parity) {
  uint32_t ok;
  asm volatile("{\n.reg .pred p;\nmbarrier.test_wait.parity.shared::cta.b64 p, [%1], %2;\nselp.u32 %0, 1, 0, p;\n}" : "=r"(ok) : "r"(bar), "r"(parity) : "memory");
  return ok;
}
constexpr int SPIN_LIMIT = 300000;
__device__ __forceinline__ void spin_guard(int& it) {
  asm volatile("{\n.reg .pred p;\n.reg .b64 z;\nadd.s32 %0, %0, 1;\nsetp.gt.s32 p, %0, %1;\nmov.b64 z, 0;\n@p st.volatile.global.u32 [z], %0;\n}" : "+r"(it) : "n"(SPIN_LIMIT));
}
__device__ __forceinline__ void mbar_wait_g(uint32_t bar, uint32_t parity) {
  asm volatile("{\n.reg .pred p, q;\n.reg .b32 c;\n.reg .b64 z;\nmov.b32 c, 0;\nmov.b64 z, 0;\nMW_LOOP:\n"
               "mbarrier.try_wait.parity.shared::cta.b64 p, [%0], %1;\nadd.s32 c, c, 1;\nsetp.gt.s32 q, c, %2;\n"
               "@q st.volatile.global.u32 [z], c;\n@!p bra MW_LOOP;\n}" :: "r"(bar), "r"(parity), "n"(SPIN_LIMIT) : "memory");
}
__device__ __forceinline__ void mbar_wait(uint32_t bar, uint32_t parity) {
  asm volatile("{\n.reg .pred p;\nMW_LOOP:\nmbarrier.try_wait.parity.shared::cta.b64 p, [%0], %1;\n@!p bra MW_LOOP;\n}" :: "r"(bar), "r"(parity) : "memory");
}
__device__ __forceinline__ void bb_fence(uint32_t v) {
  asm volatile("{\n.reg .pred p;\n.reg .u32 c;\nsetp.ne.u32 p, %0, 0;\n@p bra.uni BF_DONE;\nBF_LOOP:\nnanosleep.u32 1;\nmov.u32 c, %%clock;\nsetp.eq.u32 p, c, 0;\n@p bra.uni BF_LOOP;\nBF_DONE:\n}" :: "r"(v) : "memory");
}
__device__ __forceinline__ bool elect_one() {
  uint32_t pred;
  asm volatile("{\n.reg .pred P;\nelect.sync _|P, 0xffffffff;\nselp.u32 %0, 1, 0, P;\n}" : "=r"(pred));
  return pred;
}
__device__ __forceinline__ void tma_ld_hint(uint32_t dst, const CUtensorMap* m, int c0, int c1, uint32_t bar, uint64_t pol) {
  asm volatile("cp.async.bulk.tensor.2d.shared::cluster.global.mbarrier::complete_tx::bytes.L2::cache_hint [%0], [%1, {%3, %4}], [%2], %5;"
    :: "r"(dst), "l"(m), "r"(bar), "r"(c0), "r"(c1), "l"(pol) : "memory");
}
__device__ __forceinline__ void tma_ld_mc(uint32_t dst, const CUtensorMap* m, int c0, int c1, uint32_t bar) {
  asm volatile("cp.async.bulk.tensor.2d.shared::cluster.global.mbarrier::complete_tx::bytes.multicast::cluster [%0], [%1, {%3, %4}], [%2], %5;"
    :: "r"(dst), "l"(m), "r"(bar), "r"(c0), "r"(c1), "h"((uint16_t)3) : "memory");
}
__device__ __forceinline__ void tma_ld_mc_hint(uint32_t dst, const CUtensorMap* m, int c0, int c1, uint32_t bar, uint64_t pol) {
  asm volatile("cp.async.bulk.tensor.2d.shared::cluster.global.mbarrier::complete_tx::bytes.multicast::cluster.L2::cache_hint [%0], [%1, {%3, %4}], [%2], %5, %6;"
    :: "r"(dst), "l"(m), "r"(bar), "r"(c0), "r"(c1), "h"((uint16_t)3), "l"(pol) : "memory");
}
__device__ __forceinline__ void tma_ld3_hint(uint32_t dst, const CUtensorMap* m, int row, int blk, uint32_t bar, uint64_t pol) {
  asm volatile("cp.async.bulk.tensor.3d.shared::cluster.global.mbarrier::complete_tx::bytes.L2::cache_hint [%0], [%1, {0, %3, %4}], [%2], %5;"
    :: "r"(dst), "l"(m), "r"(bar), "r"(row), "r"(blk), "l"(pol) : "memory");
}
__device__ __forceinline__ void tma_st(const CUtensorMap* m, int c0, int c1, uint32_t src) {
  asm volatile("cp.async.bulk.tensor.2d.global.shared::cta.bulk_group [%0, {%2, %3}], [%1];" :: "l"(m), "r"(src), "r"(c0), "r"(c1) : "memory");
}
__device__ __forceinline__ void tma_prefetch_desc(const CUtensorMap* m) { asm volatile("prefetch.tensormap [%0];" :: "l"(m) : "memory"); }
__device__ __forceinline__ void l2_prefetch(const void* p, uint32_t bytes) { asm volatile("cp.async.bulk.prefetch.L2.global [%0], %1;" :: "l"(p), "r"(bytes) : "memory"); }
__device__ __forceinline__ void bulk_commit() { asm volatile("cp.async.bulk.commit_group;" ::: "memory"); }
__device__ __forceinline__ void bulk_wait_read() { asm volatile("cp.async.bulk.wait_group.read 0;" ::: "memory"); }
__device__ __forceinline__ void bulk_wait_all() { asm volatile("cp.async.bulk.wait_group 0;" ::: "memory"); }
__device__ __forceinline__ void fence_async_smem() { asm volatile("fence.proxy.async.shared::cta;" ::: "memory"); }
__device__ __forceinline__ void fence_async_global() { asm volatile("fence.proxy.async.global;" ::: "memory"); }
__device__ __forceinline__ void fence_acquire_gpu() { asm volatile("fence.acquire.gpu;" ::: "memory"); }
__device__ __forceinline__ void fence_release_gpu() { asm volatile("fence.release.gpu;" ::: "memory"); }
__device__ __forceinline__ void st_async_f32x4(uint32_t cluster_addr, const float* v, uint32_t cluster_bar) {
  asm volatile("st.async.weak.shared::cluster.mbarrier::complete_tx::bytes.v4.f32 [%0], {%1,%2,%3,%4}, [%5];"
    :: "r"(cluster_addr), "f"(v[0]), "f"(v[1]), "f"(v[2]), "f"(v[3]), "r"(cluster_bar) : "memory");
}
__device__ __forceinline__ void nb_sync(int id, int n) { asm volatile("bar.sync %0, %1;" :: "r"(id), "r"(n) : "memory"); }
__device__ __forceinline__ void nb_arrive(int id, int n) { asm volatile("bar.arrive %0, %1;" :: "r"(id), "r"(n) : "memory"); }
__device__ __forceinline__ void wg_fence() { asm volatile("wgmma.fence.sync.aligned;" ::: "memory"); }
__device__ __forceinline__ void wg_commit() { asm volatile("wgmma.commit_group.sync.aligned;" ::: "memory"); }
template <int N> __device__ __forceinline__ void wg_wait() { asm volatile("wgmma.wait_group.sync.aligned %0;" :: "n"(N) : "memory"); }
template <int N> __device__ __forceinline__ void reg_fence(float* a) {
#pragma unroll
  for (int i = 0; i < N; i++) asm volatile("" : "+f"(a[i]) :: "memory");
}
template <int N> __device__ __forceinline__ void reg_fence(uint32_t* a) {
#pragma unroll
  for (int i = 0; i < N; i++) asm volatile("" : "+r"(a[i]) :: "memory");
}
__device__ __forceinline__ uint64_t mk_desc(uint32_t addr, uint32_t lbo) {
  return (uint64_t)((addr & 0x3FFFF) >> 4) | ((uint64_t)(lbo >> 4) << 16) | ((uint64_t)(1024 >> 4) << 32) | (1ull << 62);
}

__device__ __forceinline__ uint64_t policy_evict_first() { uint64_t pol; asm("createpolicy.fractional.L2::evict_first.b64 %0, 1.0;" : "=l"(pol)); return pol; }
__device__ __forceinline__ uint32_t ld_relaxed(const uint32_t* p) { uint32_t v; asm volatile("ld.relaxed.gpu.global.u32 %0, [%1];" : "=r"(v) : "l"(p) : "memory"); return v; }
__device__ __forceinline__ void st_relaxed(uint32_t* p, uint32_t v) { asm volatile("st.relaxed.gpu.global.u32 [%0], %1;" :: "l"(p), "r"(v) : "memory"); }
__device__ __forceinline__ void red_add_relaxed(uint32_t* p, uint32_t v) { asm volatile("red.relaxed.gpu.global.add.u32 [%0], %1;" :: "l"(p), "r"(v) : "memory"); }
__device__ __forceinline__ uint2 ld_pkt8(const uint2* p) {
  uint2 v; asm volatile("{\n.reg .b64 t;\nld.relaxed.gpu.global.b64 t, [%2];\nmov.b64 {%0,%1}, t;\n}" : "=r"(v.x), "=r"(v.y) : "l"(p) : "memory"); return v;
}
__device__ __forceinline__ void st_pkt8(uint2* p, uint32_t a, uint32_t b) {
  asm volatile("{\n.reg .b64 t;\nmov.b64 t, {%1,%2};\nst.relaxed.gpu.global.b64 [%0], t;\n}" :: "l"(p), "r"(a), "r"(b) : "memory");
}
__device__ __forceinline__ uint4 ld_pkt16(const uint4* p) {
  uint4 v; asm volatile("{\n.reg .b128 t;\n.reg .b64 a, b;\nld.relaxed.gpu.global.b128 t, [%4];\nmov.b128 {a, b}, t;\nmov.b64 {%0,%1}, a;\nmov.b64 {%2,%3}, b;\n}"
    : "=r"(v.x), "=r"(v.y), "=r"(v.z), "=r"(v.w) : "l"(p) : "memory"); return v;
}
__device__ __forceinline__ void st_pkt16(uint4* p, uint32_t x, uint32_t y, uint32_t z, uint32_t w) {
  asm volatile("{\n.reg .b128 t;\n.reg .b64 a, b;\nmov.b64 a, {%1,%2};\nmov.b64 b, {%3,%4};\nmov.b128 t, {a, b};\nst.relaxed.gpu.global.b128 [%0], t;\n}"
    :: "l"(p), "r"(x), "r"(y), "r"(z), "r"(w) : "memory");
}
__device__ __forceinline__ void cp_async16(uint32_t dst, const void* src) { asm volatile("cp.async.cg.shared.global [%0], [%1], 16;" :: "r"(dst), "l"(src) : "memory"); }
__device__ __forceinline__ void cp_async_wait() { asm volatile("cp.async.wait_all;" ::: "memory"); }
__device__ __forceinline__ uint32_t lds32(uint32_t a) { uint32_t v; asm volatile("ld.shared.u32 %0, [%1];" : "=r"(v) : "r"(a) : "memory"); return v; }
__device__ __forceinline__ float lds_f32(uint32_t a) { float v; asm volatile("ld.shared.f32 %0, [%1];" : "=f"(v) : "r"(a) : "memory"); return v; }
__device__ __forceinline__ uint2 lds64(uint32_t a) { uint2 v; asm volatile("ld.shared.v2.u32 {%0,%1}, [%2];" : "=r"(v.x), "=r"(v.y) : "r"(a) : "memory"); return v; }
__device__ __forceinline__ uint4 lds128(uint32_t a) { uint4 v; asm volatile("ld.shared.v4.u32 {%0,%1,%2,%3}, [%4];" : "=r"(v.x), "=r"(v.y), "=r"(v.z), "=r"(v.w) : "r"(a) : "memory"); return v; }
__device__ __forceinline__ void sts32(uint32_t a, uint32_t v) { asm volatile("st.shared.u32 [%0], %1;" :: "r"(a), "r"(v) : "memory"); }
__device__ __forceinline__ void sts64(uint32_t a, uint32_t x, uint32_t y) { asm volatile("st.shared.v2.u32 [%0], {%1,%2};" :: "r"(a), "r"(x), "r"(y) : "memory"); }
__device__ __forceinline__ void sts128(uint32_t a, uint32_t x, uint32_t y, uint32_t z, uint32_t w) { asm volatile("st.shared.v4.u32 [%0], {%1,%2,%3,%4};" :: "r"(a), "r"(x), "r"(y), "r"(z), "r"(w) : "memory"); }
__device__ __forceinline__ void stsm4(uint32_t a, uint32_t x, uint32_t y, uint32_t z, uint32_t w) {
  asm volatile("stmatrix.sync.aligned.m8n8.x4.shared.b16 [%0], {%1,%2,%3,%4};" :: "r"(a), "r"(x), "r"(y), "r"(z), "r"(w) : "memory");
}
__device__ __forceinline__ void ldsm4(uint32_t a, uint32_t* r) {
  asm volatile("ldmatrix.sync.aligned.m8n8.x4.shared.b16 {%0,%1,%2,%3}, [%4];" : "=r"(r[0]), "=r"(r[1]), "=r"(r[2]), "=r"(r[3]) : "r"(a) : "memory");
}
__device__ __forceinline__ void ldsm4t(uint32_t a, uint32_t* r) {
  asm volatile("ldmatrix.sync.aligned.m8n8.x4.trans.shared.b16 {%0,%1,%2,%3}, [%4];" : "=r"(r[0]), "=r"(r[1]), "=r"(r[2]), "=r"(r[3]) : "r"(a) : "memory");
}
__device__ __forceinline__ void mma16816(float* d, const uint32_t* a, uint32_t b0, uint32_t b1) {
  asm volatile("mma.sync.aligned.m16n8k16.row.col.f32.bf16.bf16.f32 {%0,%1,%2,%3}, {%4,%5,%6,%7}, {%8,%9}, {%0,%1,%2,%3};"
    : "+f"(d[0]), "+f"(d[1]), "+f"(d[2]), "+f"(d[3]) : "r"(a[0]), "r"(a[1]), "r"(a[2]), "r"(a[3]), "r"(b0), "r"(b1));
}
__device__ __forceinline__ void mma1688(float* d, uint32_t a0, uint32_t a1, uint32_t b0) {
  asm volatile("mma.sync.aligned.m16n8k8.row.col.f32.bf16.bf16.f32 {%0,%1,%2,%3}, {%4,%5}, {%6}, {%0,%1,%2,%3};"
    : "+f"(d[0]), "+f"(d[1]), "+f"(d[2]), "+f"(d[3]) : "r"(a0), "r"(a1), "r"(b0));
}
__device__ __forceinline__ uint32_t pack2(float lo, float hi) { uint32_t r; asm("cvt.rn.bf16x2.f32 %0, %1, %2;" : "=r"(r) : "f"(hi), "f"(lo)); return r; }
__device__ __forceinline__ float lo2f(uint32_t v) { return __uint_as_float(v << 16); }
__device__ __forceinline__ float hi2f(uint32_t v) { return __uint_as_float(v & 0xffff0000u); }
__device__ __forceinline__ uint32_t hmul2(uint32_t a, uint32_t b) { uint32_t r; asm("mul.rn.bf16x2 %0, %1, %2;" : "=r"(r) : "r"(a), "r"(b)); return r; }
__device__ __forceinline__ uint32_t hadd2(uint32_t a, uint32_t b) { uint32_t r; asm("add.rn.bf16x2 %0, %1, %2;" : "=r"(r) : "r"(a), "r"(b)); return r; }
__device__ __forceinline__ uint32_t hsub2(uint32_t a, uint32_t b) { uint32_t r; asm("sub.rn.bf16x2 %0, %1, %2;" : "=r"(r) : "r"(a), "r"(b)); return r; }
__device__ __forceinline__ uint32_t hfma2(uint32_t a, uint32_t b, uint32_t c) { uint32_t r; asm("fma.rn.bf16x2 %0, %1, %2, %3;" : "=r"(r) : "r"(a), "r"(b), "r"(c)); return r; }
__device__ __forceinline__ float rbf(float v) { return lo2f(pack2(v, 0.f)); }
__device__ __forceinline__ float ex2(float v) { float r; asm("ex2.approx.ftz.f32 %0, %1;" : "=f"(r) : "f"(v)); return r; }
__device__ __forceinline__ float rcp_f(float v) { float r; asm("rcp.approx.ftz.f32 %0, %1;" : "=f"(r) : "f"(v)); return r; }
__device__ __forceinline__ float sqrt_f(float v) { float r; asm("sqrt.approx.ftz.f32 %0, %1;" : "=f"(r) : "f"(v)); return r; }
__device__ __forceinline__ float sigmoid_f(float v) { return rcp_f(1.f + ex2(-1.4426950408889634f * v)); }
__device__ __forceinline__ float silu_f(float v) { return v * sigmoid_f(v); }
constexpr uint32_t ONE2 = 0x3f803f80u;

#define R8(a,o) "+f"(a[o+0]), "+f"(a[o+1]), "+f"(a[o+2]), "+f"(a[o+3]), "+f"(a[o+4]), "+f"(a[o+5]), "+f"(a[o+6]), "+f"(a[o+7])
#define R64(a,o) R8(a,o), R8(a,o+8), R8(a,o+16), R8(a,o+24), R8(a,o+32), R8(a,o+40), R8(a,o+48), R8(a,o+56)
#define D64 "{%0,%1,%2,%3,%4,%5,%6,%7,%8,%9,%10,%11,%12,%13,%14,%15,%16,%17,%18,%19,%20,%21,%22,%23,%24,%25,%26,%27,%28,%29,%30,%31," \
            "%32,%33,%34,%35,%36,%37,%38,%39,%40,%41,%42,%43,%44,%45,%46,%47,%48,%49,%50,%51,%52,%53,%54,%55,%56,%57,%58,%59,%60,%61,%62,%63"
#define D128 D64 ",%64,%65,%66,%67,%68,%69,%70,%71,%72,%73,%74,%75,%76,%77,%78,%79,%80,%81,%82,%83,%84,%85,%86,%87,%88,%89,%90,%91,%92,%93,%94,%95," \
            "%96,%97,%98,%99,%100,%101,%102,%103,%104,%105,%106,%107,%108,%109,%110,%111,%112,%113,%114,%115,%116,%117,%118,%119,%120,%121,%122,%123,%124,%125,%126,%127"

template <int TB> __device__ __forceinline__ void wgmma_ss128(float* d, uint64_t da, uint64_t db, int acc) {
  asm volatile("{\n.reg .pred p;\nsetp.ne.b32 p, %66, 0;\nwgmma.mma_async.sync.aligned.m64n128k16.f32.bf16.bf16 " D64 "}, %64, %65, p, 1, 1, 0, %67;\n}"
    : R64(d, 0) : "l"(da), "l"(db), "r"(acc), "n"(TB));
}
template <int TB> __device__ __forceinline__ void wgmma_rs128(float* d, const uint32_t* a, uint64_t db, int acc) {
  asm volatile("{\n.reg .pred p;\nsetp.ne.b32 p, %69, 0;\nwgmma.mma_async.sync.aligned.m64n128k16.f32.bf16.bf16 " D64 "}, {%64,%65,%66,%67}, %68, p, 1, 1, %70;\n}"
    : R64(d, 0) : "r"(a[0]), "r"(a[1]), "r"(a[2]), "r"(a[3]), "l"(db), "r"(acc), "n"(TB));
}
template <int TB> __device__ __forceinline__ void wgmma_ss256(float* d, uint64_t da, uint64_t db, int acc) {
  asm volatile("{\n.reg .pred p;\nsetp.ne.b32 p, %130, 0;\nwgmma.mma_async.sync.aligned.m64n256k16.f32.bf16.bf16 " D128 "}, %128, %129, p, 1, 1, 0, %131;\n}"
    : R64(d, 0), R64(d, 64) : "l"(da), "l"(db), "r"(acc), "n"(TB));
}

#define W8(a,o) "=f"(a[o+0]), "=f"(a[o+1]), "=f"(a[o+2]), "=f"(a[o+3]), "=f"(a[o+4]), "=f"(a[o+5]), "=f"(a[o+6]), "=f"(a[o+7])
#define W64(a,o) W8(a,o), W8(a,o+8), W8(a,o+16), W8(a,o+24), W8(a,o+32), W8(a,o+40), W8(a,o+48), W8(a,o+56)
template <int TB> __device__ __forceinline__ void wgmma_ss128_z(float* d, uint64_t da, uint64_t db) {
  asm volatile("wgmma.mma_async.sync.aligned.m64n128k16.f32.bf16.bf16 " D64 "}, %64, %65, 0, 1, 1, 0, %66;"
    : W64(d, 0) : "l"(da), "l"(db), "n"(TB));
}
template <int TB> __device__ __forceinline__ void wgmma_rs128_z(float* d, const uint32_t* a, uint64_t db) {
  asm volatile("wgmma.mma_async.sync.aligned.m64n128k16.f32.bf16.bf16 " D64 "}, {%64,%65,%66,%67}, %68, 0, 1, 1, %69;"
    : W64(d, 0) : "r"(a[0]), "r"(a[1]), "r"(a[2]), "r"(a[3]), "l"(db), "n"(TB));
}
template <int TB> __device__ __forceinline__ void wgmma_ss256_z(float* d, uint64_t da, uint64_t db) {
  asm volatile("wgmma.mma_async.sync.aligned.m64n256k16.f32.bf16.bf16 " D128 "}, %128, %129, 0, 1, 1, 0, %130;"
    : W64(d, 0), W64(d, 64) : "l"(da), "l"(db), "n"(TB));
}

template <int TB> __device__ __forceinline__ void wgmma_rs256(float* d, const uint32_t* a, uint64_t db) {
  asm volatile("wgmma.mma_async.sync.aligned.m64n256k16.f32.bf16.bf16 " D128 "}, {%128,%129,%130,%131}, %132, 1, 1, 1, %133;"
    : R64(d, 0), R64(d, 64) : "r"(a[0]), "r"(a[1]), "r"(a[2]), "r"(a[3]), "l"(db), "n"(TB));
}
template <int TB> __device__ __forceinline__ void wgmma_rs256_z(float* d, const uint32_t* a, uint64_t db) {
  asm volatile("wgmma.mma_async.sync.aligned.m64n256k16.f32.bf16.bf16 " D128 "}, {%128,%129,%130,%131}, %132, 0, 1, 1, %133;"
    : W64(d, 0), W64(d, 64) : "r"(a[0]), "r"(a[1]), "r"(a[2]), "r"(a[3]), "l"(db), "n"(TB));
}
#define D32 "{%0,%1,%2,%3,%4,%5,%6,%7,%8,%9,%10,%11,%12,%13,%14,%15,%16,%17,%18,%19,%20,%21,%22,%23,%24,%25,%26,%27,%28,%29,%30,%31}"
__device__ __forceinline__ void wgmma_rs64(float* d, const uint32_t* a, uint64_t db) {
  asm volatile("wgmma.mma_async.sync.aligned.m64n64k16.f32.bf16.bf16 " D32 ", {%32,%33,%34,%35}, %36, 1, 1, 1, 0;"
    : R8(d, 0), R8(d, 8), R8(d, 16), R8(d, 24) : "r"(a[0]), "r"(a[1]), "r"(a[2]), "r"(a[3]), "l"(db));
}
__device__ __forceinline__ void wgmma_rs64_z(float* d, const uint32_t* a, uint64_t db) {
  asm volatile("wgmma.mma_async.sync.aligned.m64n64k16.f32.bf16.bf16 " D32 ", {%32,%33,%34,%35}, %36, 0, 1, 1, 0;"
    : W8(d, 0), W8(d, 8), W8(d, 16), W8(d, 24) : "r"(a[0]), "r"(a[1]), "r"(a[2]), "r"(a[3]), "l"(db));
}
__device__ __forceinline__ void issue_qk(float* S, const uint32_t* Q, uint64_t dk) {
  wgmma_rs64_z(S, Q, dk);
#pragma unroll
  for (int kk = 1; kk < 8; kk++) wgmma_rs64(S, Q + 4 * kk, dk + (kk >> 2) * 512 + (kk & 3) * 2);
}
__device__ __forceinline__ void issue_pv(float* O, const uint32_t* P, uint64_t dv, int acc) {
#pragma unroll
  for (int kk = 0; kk < 4; kk++) wgmma_rs128<1>(O, P + 4 * kk, dv + kk * 128, kk ? 1 : acc);
}

#define TS(i)
#define TSC(i)
#define TSX(i)
#define TSY(k) do { if ((tid & 127) == 0) TS((k) + 40 * wg); } while (0)
#define TT(k)
#define TV(k)
#define TR(k)
#define TQ(k)
#define TH(k)
#define TA(k)
#define TAFLUSH()

struct SoftmaxState { float c0, c1, l0, l1; bool shifted; };
constexpr float SM_SCALE = 0.08838834764831845f * 1.4426950408889634f;
__device__ __forceinline__ void softmax_start(SoftmaxState& z) { z.c0 = z.c1 = z.l0 = z.l1 = 0.f; z.shifted = false; }
__device__ __forceinline__ void softmax_half(float* S, uint32_t* P, float* O, SoftmaxState& z, bool first, uint32_t tag) {
  const float lo0 = z.l0, lo1 = z.l1;
  float lim = 1.2676506002282294e30f;
  const float low = first ? 8.673617379884035e-19f : 0.f;
  if (z.shifted) {
#pragma unroll
    for (int j = 0; j < 32; j++) S[j] += (j & 2) ? z.c1 : z.c0;
  }
#pragma unroll 1
  while (true) {
    bb_fence(tag);
#pragma unroll
    for (int j = 0; j < 8; j++) {
      const float p0 = ex2(S[4 * j]), p1 = ex2(S[4 * j + 1]), p2 = ex2(S[4 * j + 2]), p3 = ex2(S[4 * j + 3]);
      z.l0 += p0; z.l1 += p2; z.l0 += p1; z.l1 += p3;
      P[2 * j] = pack2(p0, p1); P[2 * j + 1] = pack2(p2, p3);
    }
    if (!__any_sync(0xffffffffu, !(z.l0 < lim && z.l1 < lim && fminf(z.l0, z.l1) >= low) && lim > 0.f)) break;
    float d0 = fmaxf(S[0], S[1]), d1 = fmaxf(S[2], S[3]);
#pragma unroll
    for (int j = 1; j < 8; j++) { d0 = fmaxf(d0, fmaxf(S[4 * j], S[4 * j + 1])); d1 = fmaxf(d1, fmaxf(S[4 * j + 2], S[4 * j + 3])); }
    d0 = fmaxf(d0, __shfl_xor_sync(0xffffffffu, d0, 1)); d1 = fmaxf(d1, __shfl_xor_sync(0xffffffffu, d1, 1));
    d0 = fmaxf(d0, __shfl_xor_sync(0xffffffffu, d0, 2)); d1 = fmaxf(d1, __shfl_xor_sync(0xffffffffu, d1, 2));
    if (!first) { d0 = fmaxf(d0, 0.f); d1 = fmaxf(d1, 0.f); }
    z.shifted = true;
    z.c0 -= d0; z.c1 -= d1;
#pragma unroll
    for (int j = 0; j < 32; j++) S[j] -= (j & 2) ? d1 : d0;
    const float a0 = first ? 1.f : ex2(-d0), a1 = first ? 1.f : ex2(-d1);
    z.l0 = lo0 * a0; z.l1 = lo1 * a1;
    lim = -1.f;
    wg_wait<0>();
    reg_fence<64>(O);
#pragma unroll
    for (int j = 0; j < 16; j++) { O[4 * j] *= a0; O[4 * j + 1] *= a0; O[4 * j + 2] *= a1; O[4 * j + 3] *= a1; }
  }
}

__device__ __forceinline__ void modulate_frags(uint32_t* A, const uint32_t* V, const uint4* R, const uint32_t* ln) {
#pragma unroll
  for (int kk = 0; kk < 4; kk++) {
    const uint4 sa = R[kk >> 1], c1 = R[2 + (kk >> 1)];
#pragma unroll
    for (int j = 0; j < 4; j++) {
      const uint32_t n = hfma2(V[4 * kk + j], ln[(j & 1) * 2 + 1], ln[(j & 1) * 2]);
      A[4 * kk + j] = (kk & 1) ? ((j & 2) ? hfma2(n, c1.w, sa.x) : hfma2(n, c1.z, sa.w)) : ((j & 2) ? hfma2(n, c1.y, sa.z) : hfma2(n, c1.x, sa.y));
    }
  }
}
__device__ __forceinline__ void publish_record(uint4* dst, uint32_t pk, int src, int vec, bool doit) {
  const int r = vec ? 0 : 12;
  const uint32_t x = __shfl_sync(0xffffffffu, pk, src + r), y = __shfl_sync(0xffffffffu, pk, src + ((r + 4) & 12));
  const uint32_t z = __shfl_sync(0xffffffffu, pk, src + ((r + 8) & 12)), w = __shfl_sync(0xffffffffu, pk, src + ((r + 12) & 12));
  if (doit) st_pkt16(dst, ~x, y, z, w);
}
__device__ __forceinline__ void put_record(uint32_t sb, int idx, const uint4& v) {
  sts128(sb + SM_STASH + idx * 16, ~v.x, v.y, v.z, v.w);
  sts128(sb + SM_STASH + 16384 + idx * 16, ~v.x, v.y, v.z, v.w);
}
__device__ __forceinline__ float mod_value(float v, int vec) {
  v = rbf(v);
  return (vec ? rbf(1.f + v) : v) * SM_SCALE;
}

__device__ __forceinline__ void row_rcp(float& l0, float& l1) {
  l0 += __shfl_xor_sync(0xffffffffu, l0, 1); l1 += __shfl_xor_sync(0xffffffffu, l1, 1);
  l0 += __shfl_xor_sync(0xffffffffu, l0, 2); l1 += __shfl_xor_sync(0xffffffffu, l1, 2);
  l0 = rcp_f(l0); l1 = rcp_f(l1);
}
__device__ __forceinline__ void stage_o(const float* O, float r0, float r1, uint32_t stsm_addr) {
#pragma unroll
  for (int kk = 0; kk < 8; kk++) {
    stsm4((stsm_addr + (kk >> 2) * 8192) ^ ((kk & 3) * 32),
          pack2(O[8 * kk + 0] * r0, O[8 * kk + 1] * r0), pack2(O[8 * kk + 2] * r1, O[8 * kk + 3] * r1),
          pack2(O[8 * kk + 4] * r0, O[8 * kk + 5] * r0), pack2(O[8 * kk + 6] * r1, O[8 * kk + 7] * r1));
  }
}

__global__ void __cluster_dims__(2, 1, 1) __launch_bounds__(NTHREADS, 1)
fused_kernel(const Params p, const __grid_constant__ CUtensorMap mH, const __grid_constant__ CUtensorMap mWq,
             const __grid_constant__ CUtensorMap mK, const __grid_constant__ CUtensorMap mV,
             const __grid_constant__ CUtensorMap mO, const __grid_constant__ CUtensorMap mWo,
             const __grid_constant__ CUtensorMap mX, const __grid_constant__ CUtensorMap mOut,
             const __grid_constant__ CUtensorMap mWg, const __grid_constant__ CUtensorMap mWu,
             const __grid_constant__ CUtensorMap mWd, const __grid_constant__ CUtensorMap mWm,
             const __grid_constant__ CUtensorMap mWs, const __grid_constant__ CUtensorMap mWh) {
  extern __shared__ __align__(1024) uint8_t smem_raw[];
  TH(0);
  const uint32_t sb = smem_u32(smem_raw);
  const int tid = threadIdx.x;
  const int b0 = blockIdx.x;
  const int lane = tid & 31;
  const int role = __shfl_sync(0xffffffffu, tid >> 8, 0);

  if (b0 >= NMAIN) {
    const uint32_t cs = clock();
    const uint32_t tag = ld_relaxed(&g_epoch) + 1;
    const int sp = b0 - NMAIN, vec = 2 + sp;
    const int warp = __shfl_sync(0xffffffffu, tid >> 5, 0);
    float* sc = reinterpret_cast<float*>(smem_raw + SM_STASH);
    float* red = reinterpret_cast<float*>(smem_raw + SM_STASH + 4096);
    const int ridx = (lane >> 3) * 2 * RV + (sp & 1) * RV + 16 * RS + (sp >> 1) * 16 + (warp & 1) * 8 + (lane & 7);
    if (warp < 8) st_pkt16(&g_rec[warp >> 2][0][ridx + (warp & 2) * 16], 0, 0, 0, 0);
#pragma unroll 1
    for (int i = tid; i < 1024; i += NTHREADS) sc[i] = rbf(silu_f(__bfloat162float(p.c[i])));
    if (tid == 0) {
      tma_prefetch_desc(&mWs);
      for (int s = 0; s < NST2; s++) { mbar_init(sb + BAR_FULL2 + 8 * s, 1); mbar_init(sb + BAR_EMPTY2 + 8 * s, 8); }
      fence_async_smem();
      while ((uint32_t)clock() - cs < SPT) {}
    }
    __syncthreads();
    int s = 0; uint32_t ph = 0;
    if (tid == 0) TS(0);
    if (warp == 8) {
      const uint64_t pol = policy_evict_first();
#pragma unroll 1
      for (int n = 0; n < 80; n++) {
        mbar_wait_g(sb + BAR_EMPTY2 + 8 * s, ph ^ 1);
        if (elect_one()) {
          mbar_expect_tx(sb + BAR_FULL2 + 8 * s, 32768);
          if (n < 16) {
            tma_ld_hint(sb + s * ST2, &mWs, (sp & 1) * 1024 + 512 + (n >> 3) * 256 + (sp >> 1) * 128, (n & 7) * 128, sb + BAR_FULL2 + 8 * s, pol);
          } else {
#pragma unroll
            for (int j = 0; j < 4; j++) tma_ld_hint(sb + s * ST2 + j * 8192, &mWm, vec * 1024 + j * 256, (n - 16) * 16, sb + BAR_FULL2 + 8 * s, pol);
          }
        }
        __syncwarp();
        if (++s == NST2) { s = 0; ph ^= 1; }
      }
    } else if (warp < 8) {
      float acc[8];
#pragma unroll
      for (int i = 0; i < 8; i++) acc[i] = 0.f;
      auto stage = [&](uint32_t a0, int da, const float* cp, int dc) {
        mbar_wait_g(sb + BAR_FULL2 + 8 * s, ph);
#pragma unroll
        for (int i = 0; i < 8; i++) {
          const uint4 v = lds128(a0 + s * ST2 + i * da);
          const float c = cp[i * dc];
          acc[0] = fmaf(lo2f(v.x), c, acc[0]); acc[1] = fmaf(hi2f(v.x), c, acc[1]);
          acc[2] = fmaf(lo2f(v.y), c, acc[2]); acc[3] = fmaf(hi2f(v.y), c, acc[3]);
          acc[4] = fmaf(lo2f(v.z), c, acc[4]); acc[5] = fmaf(hi2f(v.z), c, acc[5]);
          acc[6] = fmaf(lo2f(v.w), c, acc[6]); acc[7] = fmaf(hi2f(v.w), c, acc[7]);
        }
        if (__shfl_sync(0xffffffffu, lane, __float_as_uint(acc[7]) & 31) < 32 && lane == 0) mbar_arrive(sb + BAR_EMPTY2 + 8 * s);
        if (++s == NST2) { s = 0; ph ^= 1; }
      };
#pragma unroll 1
      for (int n = 0; n < 16; n++) {
        stage(sb + tid * 16, 4096, sc + (n & 7) * 128 + (tid >> 4), 16);
        if ((n & 7) == 7) {
          float* r2 = red + 2048 + (n & 8) * 256;
#pragma unroll
          for (int i = 0; i < 8; i++) { r2[tid * 8 + i] = acc[i]; acc[i] = 0.f; }
          nb_sync(NB_CONS, 256);
          if (warp < 2) {
            float v0 = 0.f, v1 = 0.f;
#pragma unroll 4
            for (int i = 0; i < 16; i++) { const float2 e = reinterpret_cast<const float2*>(r2)[i * 64 + tid]; v0 += e.x; v1 += e.y; }
            publish_record(&g_rec[tag & 1][0][ridx + (n >> 3) * 32], pack2(mod_value(v0, sp & 1), mod_value(v1, sp & 1)),
                           (lane & 4) * 4 + (lane & 3), sp & 1, true);
          }
          if (tid == 0) TS(1 + (n >> 3));
        }
      }
#pragma unroll 1
      for (int n = 0; n < 64; n++) {
        stage(sb + ((tid >> 5) & 3) * 8192 + (tid >> 7) * 4096 + (tid & 31) * 16, 512, sc + n * 16 + (tid >> 7) * 8, 1);
      }
#pragma unroll
      for (int i = 0; i < 8; i++) red[(tid >> 7) * 1024 + (tid & 127) * 8 + i] = acc[i];
    }
    __syncthreads();
    float dot = 0.f;
#pragma unroll 1
    for (int i = tid; i < 512; i += NTHREADS) {
      uint32_t v = pack2(red[2 * i] + red[1024 + 2 * i], red[2 * i + 1] + red[1024 + 2 * i + 1]);
      st_pkt8(&g_mod[vec * 512 + i], v, tag);
      if (vec == 4) v = hadd2(v, ONE2);
      const uint32_t wr = reinterpret_cast<const uint32_t*>(p.w_r)[i];
      dot = fmaf(lo2f(v), lo2f(wr), fmaf(hi2f(v), hi2f(wr), dot));
    }
#pragma unroll
    for (int o = 16; o; o >>= 1) dot += __shfl_xor_sync(0xffffffffu, dot, o);
    if (lane == 0) sc[warp] = dot;
    __syncthreads();
    if (tid == 0) {
      dot = 0.f;
      for (int w = 0; w < 12; w++) dot += sc[w];
      fence_release_gpu();
      st_pkt8(&g_vdone[(vec - 2) * 16], __float_as_uint(dot), tag);
      TS(11);
#pragma unroll 1
      for (int i = 0; i < 128; i++) {
        const int u = i * 4 + (b0 - NMAIN);
        l2_prefetch(p.wo + (size_t)((4 * ((u >> 4) & 7) + (u >> 7)) * 128 + (u & 15) * 8) * 1024, 16384);
        __nanosleep(PFW);
      }
    }
    return;
  }

  const uint32_t rank = b0 & 1;
  const bool slab = !(b0 & 32), late = b0 & 16;
  const uint32_t c0 = clock();
  if (tid == 352) TS(0);
  const uint32_t slab_addr = sb + SM_WSLAB + (tid >> 5) * 4096 + (lane & 3) * 128 + (lane & 4) * 16 + (((lane >> 3) ^ lane) & 3) * 16;
  auto load_slab = [&]() {
    const bf16* wp = p.w_mod + (size_t)(512 * rank + 2 * (tid & ~31) + 2 * (lane & 3) + ((lane >> 2) & 1)) * 6144 + 32 * (b0 >> 1) + 8 * (lane >> 3);
    const uint64_t pef = policy_evict_first();
#pragma unroll
    for (int i = 0; i < 8; i++)
      asm volatile("cp.async.cg.shared.global.L2::cache_hint [%0], [%1], 16, %2;"
        :: "r"(slab_addr + i * 512), "l"(wp + (size_t)i * 8 * 6144), "l"(pef) : "memory");
  };
  if (tid == 256) {
    mbar_init(sb + BAR_XH, 1);
    fence_async_smem();
    mbar_expect_tx(sb + BAR_XH, 32768);
#pragma unroll
    for (int i = 0; i < 2; i++)
      asm volatile("cp.async.bulk.shared::cluster.global.mbarrier::complete_tx::bytes [%0], [%1], 16384, [%2];"
        :: "r"(sb + SM_XROW + i * ST1), "l"(p.x + (size_t)b0 * 16384 + i * 8192), "r"(sb + BAR_XH) : "memory");
  }
  __syncwarp();
  uint32_t cw[8];
#pragma unroll
  for (int i = 0; i < 8; i++) cw[i] = 0;
  if (!role && slab) {
#pragma unroll
    for (int i = 0; i < 8; i++) cw[i] = ld_relaxed(reinterpret_cast<const uint32_t*>(p.c) + 256 * rank + (tid & ~28) + 4 * i);
  }
  uint32_t epoch = 0;
  if (!role) epoch = ld_relaxed(&p.sc->epoch[lane]);
  if (!role && slab && !late) load_slab();
#define TILE_ROLES() \
  mbar_wait(sb + BAR_ROLE, 0); \
  const int b = 2 * __shfl_sync(0xffffffffu, lds32(sb + SM_ROLE), 0) + rank; \
  const int rt = b >> 3;     \
  const int ct = b & 7;

  if (role) {
    asm volatile("setmaxnreg.dec.sync.aligned.u32 24;");
    const int warp = __shfl_sync(0xffffffffu, tid >> 5, 0);
    if (tid == 256) {
      mbar_init(sb + BAR_RED, 1); mbar_init(sb + BAR_WH, 1);
      for (int s = 0; s < 2; s++) mbar_init(sb + BAR_OF + 8 * s, 1);
      mbar_init(sb + BAR_ROLE, 1);
      for (int s = 0; s < 5; s++) { mbar_init(sb + BAR_FULL1 + 8 * s, 1); mbar_init(sb + BAR_EMPTY1 + 8 * s, 4); }
      for (int s = 0; s < 2; s++) { mbar_init(sb + BAR_STASH + 8 * s, 1); mbar_init(sb + BAR_X + 8 * s, 1); }
      for (int s = 0; s < 4; s++) mbar_init(sb + BAR_HS + 8 * s, 1);
      mbar_init(sb + BAR_G, 16); mbar_init(sb + BAR_T1, 1); mbar_init(sb + BAR_HF, 1);
      mbar_init(sb + BAR_SFREE, 4); mbar_init(sb + BAR_TFREE, 8);
      mbar_init(sb + BAR_FFN, 4); mbar_init(sb + BAR_FFN + 8, 2);
      mbar_init(sb + BAR_CAND, 1); mbar_init(sb + BAR_VEC, 32); for (int s = 0; s < 3; s++) mbar_init(sb + BAR_TAB + 8 * s, 32);
      mbar_expect_tx(sb + BAR_RED, 1024);
      mbar_expect_tx(sb + BAR_ROLE, 4);
      asm volatile("fence.mbarrier_init.release.cluster;" ::: "memory");
    }
    __syncwarp();
    asm volatile("barrier.cluster.arrive.relaxed.aligned;" ::: "memory");
    const int ridx = ((lane >> 1) & 3) * 2 * RV + (b0 >> 6) * RV + ((b0 >> 1) & 31) * RS + 2 * rank + (lane & 1) + (lane >> 3) * 4;
    if (warp == 11 && slab && lane < 2 * RS) { st_pkt16(&g_rec[0][0][ridx], 0, 0, 0, 0); st_pkt16(&g_rec[1][0][ridx], 0, 0, 0, 0); }
    if (tid == 256) {
      tma_prefetch_desc(&mWq); tma_prefetch_desc(&mX); tma_prefetch_desc(&mH); tma_prefetch_desc(&mK); tma_prefetch_desc(&mV); tma_prefetch_desc(&mO);
    }
    uint32_t pairid = 0;
    if (tid == 320 && rank == 0) {
      uint32_t t;
      asm("mov.u32 %0, %%smid;" : "=r"(t));
      t >>= 1;
      uint32_t grp = ((0x73216540u >> (4 * ((t < 32 ? t : t < 60 ? 1 + (t - 32) % 7 : t < 62 ? t - 54 : 0) & 7))) & 7) - 1, slot;
      int it = 0;
      do {
        grp = (grp + 1) & 7;
        asm volatile("atom.relaxed.gpu.global.add.u32 %0, [%1], 1;" : "=r"(slot) : "l"(&p.sc->ticket[grp * 32]) : "memory");
        spin_guard(it);
      } while (slot >= 8);
      pairid = slot * 8 + grp;
    }
    __syncwarp();
    asm volatile("barrier.cluster.wait.aligned;" ::: "memory");
    if (tid == 320 && rank == 0) {
#pragma unroll
      for (int r = 0; r < 2; r++)
        asm volatile("st.async.weak.shared::cluster.mbarrier::complete_tx::bytes.b32 [%0], %1, [%2];"
          :: "r"(mapa(sb + SM_ROLE, r)), "r"(pairid), "r"(mapa(sb + BAR_ROLE, r)) : "memory");
    }
    __syncwarp();
    const uint32_t tag = ld_relaxed(&g_epoch) + 1;
    if (warp == 8) {
      TILE_ROLES();
      const int kvrow = (ct >> 1) * 2048 + 1536, arow = rt * 128 + rank * 64;
      const uint64_t pef = policy_evict_first();
#pragma unroll 1
      for (int pair = 0; pair < 2; pair++) {
        const int wblk = (4 * ct + 2 * pair) * 2;
        if (pair) { mbar_wait_g(sb + BAR_HF, 0); fence_async_global(); }
#pragma unroll 1
        for (int n = 0; n < 16; n++) {
          const uint32_t s = n & 3, st = sb + SM_RING + s * ST1, fb = sb + BAR_FULL1 + 8 * s;
          if (n == 2 && pair == 0) mbar_wait_g(sb + BAR_G, 0);
          mbar_wait_g(fb + (BAR_EMPTY1 - BAR_FULL1), ((n >> 2) & 1) ^ 1);
          if (elect_one()) {
            mbar_expect_tx(fb, 49152);
            if (pair) tma_ld_mc_hint(st + rank * 8192, &mH, n * 64, arow, fb, pef); else
            tma_ld_mc(st + rank * 8192, pair ? &mH : &mX, n * 64, arow, fb);
            tma_ld3_hint(st + 16384, &mWq, n * 64, wblk, fb, pef);
          }
          __syncwarp();
        }
#pragma unroll 1
        for (int n = 0; n < 16; n++) {
          const uint32_t s = n & 3, st = sb + SM_RING + s * ST1 + rank * 8192, fb = sb + BAR_FULL1 + 8 * s;
          const int h0 = n == 0 ? 0 : n == 15 ? 14 : n + 1, h1 = n == 0 ? 1 : n == 15 ? 15 : n - 1;
          mbar_wait_g(fb + (BAR_EMPTY1 - BAR_FULL1), ((n >> 2) & 1) ^ 1);
          if (elect_one()) {
            mbar_expect_tx(fb, 32768);
            tma_ld_mc(st, n == 15 ? &mV : &mK, rank * 64, kvrow + (h0 & 7) * 64, fb);
            tma_ld_mc(st + 16384, n == 0 ? &mK : &mV, rank * 64, kvrow + (h1 & 7) * 64, fb);
            if (n == 3 && pair == 1) mbar_arrive(sb + BAR_T1);
          }
          __syncwarp();
        }
      }
      {
        uint32_t s = 0, ph = 1;
#pragma unroll 1
        for (int half = 0; half < 2; half++) {
          mbar_wait_g(sb + BAR_OF + 8 * half, 0);
          fence_async_global();
#pragma unroll 1
          for (int n = 32 * half; n < 32 * half + 32; n++) {
            const uint32_t st = sb + SM_RING + s * ST1, fb = sb + BAR_FULL1 + 8 * s;
            const int k0 = ((n & 14) * 2 + (n >> 4)) * 128 + (n & 1) * 64;
            mbar_wait_g(n == 8 ? sb + BAR_SFREE : fb + (BAR_EMPTY1 - BAR_FULL1), n == 8 ? 0 : ph ^ (s >> 2));
            if (elect_one()) {
              mbar_expect_tx(fb, 32768);
              tma_ld_mc_hint(st + rank * 8192, &mO, k0, arow, fb, pef);
              tma_ld3_hint(st + 16384, &mWo, k0, 2 * ct, fb, pef);
            }
            __syncwarp();
            if (++s == 5 || n == 3) { s = 0; ph ^= 1; }
          }
        }
        if (b < NFFN) {
#pragma unroll 1
          for (s = 0; s < 2; s++) {
            mbar_wait_g(sb + BAR_EMPTY1 + 8 * s, 0);
            if (elect_one()) {
              mbar_expect_tx(sb + BAR_FFN + 8, 32768);
              tma_ld3_hint(sb + SM_RING + s * ST1, &mWd, b * 32, s * 8, sb + BAR_FFN + 8, pef);
            }
            __syncwarp();
          }
        }
      }
    } else if (warp <= 10) {
      const int w = warp - 9;
      if (slab && late && w == 0 && lane == 0) {
        tma_prefetch_desc(&mWh);
        mbar_expect_tx(sb + BAR_WH, 32768);
        while ((uint32_t)clock() - c0 < WL) {}
        const uint64_t pef = policy_evict_first();
#pragma unroll
        for (int i = 0; i < 2; i++) tma_ld_hint(sb + SM_WSLAB + i * 16384, &mWh, 32 * (b0 >> 1), 512 * rank + 256 * i, sb + BAR_WH, pef);
      }
      __syncwarp();
      TILE_ROLES();
      const uint32_t st = sb + SM_STASH + w * 16384;
#pragma unroll 1
      for (int j = 0; j < 2; j++) {
        nb_sync(NB_OST + w, 160);
        if (elect_one()) {
          fence_async_smem();
          tma_st(&mH, (2 * ct + j) * 64, rt * 128 + w * 64, st + 4096);
          bulk_commit();
          bulk_wait_read();
          mbar_arrive(sb + BAR_HS + 16 * w + 8 * j);
          if (j) {
            bulk_wait_all();
            fence_async_global();
            fence_release_gpu();
            red_add_relaxed(&g_hflag[rt * 32], 1);
          }
        }
        __syncwarp();
      }
#pragma unroll 1
      for (int r = 0; r < 4; r++) {
        nb_sync(NB_OST + w, 160);
        if (elect_one()) {
          fence_async_smem();
          const int hcol = (4 * ct + r) * 128;
          tma_st(&mO, hcol, rt * 128 + w * 64, st);
          tma_st(&mO, hcol + 64, rt * 128 + w * 64, st + 8192);
          bulk_commit();
          bulk_wait_read();
          if (r < 2) {
            mbar_arrive(sb + BAR_STASH + 8 * w);
          } else if (r == 2) {
            mbar_expect_tx(sb + BAR_X + 8 * w, 16384);
            tma_ld_hint(st, &mX, ct * 128, rt * 128 + w * 64, sb + BAR_X + 8 * w, policy_evict_first());
            tma_ld_hint(st + 8192, &mX, ct * 128 + 64, rt * 128 + w * 64, sb + BAR_X + 8 * w, policy_evict_first());
          } else {
            mbar_arrive_cl(mapa(sb + BAR_SFREE, 0)); mbar_arrive_cl(mapa(sb + BAR_SFREE, 1));
          }
          bulk_wait_all();
          fence_async_global();
          fence_release_gpu();
          red_add_relaxed(&g_oflag[(rt * 4 + r) * 32], 1);
        }
        __syncwarp();
      }
      nb_sync(NB_OST + w, 160);
      int skip = -1;
      mbar_wait_g(sb + BAR_CAND, 0);
      const bool has_cand = (lds32(sb + SM_CAND) >> 6) == w;
      if (has_cand) {
        nb_sync(NB_WIN + w, 160);
        skip = (int)lds32(sb + SM_WROW + 4 * w) - (rt * 128 + w * 64);
      }
      if ((unsigned)skip >= 64u) {
        if (elect_one()) {
          fence_async_smem();
          tma_st(&mOut, ct * 128, rt * 128 + w * 64, sb + SM_OUT + w * 16384);
          tma_st(&mOut, ct * 128 + 64, rt * 128 + w * 64, sb + SM_OUT + w * 16384 + 8192);
          bulk_commit();
          bulk_wait_read();
        }
        __syncwarp();
      } else {
        uint4* dst = reinterpret_cast<uint4*>(p.out + (size_t)(rt * 128 + w * 64 + (lane >> 4)) * 1024 + ct * 128) + (lane & 15);
#pragma unroll 2
        for (int r = lane >> 4; r < 64; r += 2) {
          const uint4 v = lds128(sb + SM_OUT + w * 16384 + ((lane >> 3) & 1) * 8192 + r * 128 + (((lane ^ r) & 7) * 16));
          if (r != skip) *dst = v;
          dst += 256;
        }
      }
      if (!has_cand) nb_sync(NB_WIN + w, 160);
    } else {
      if (slab) {
        mbar_wait_g(sb + BAR_RED, 0);
        float v = 0.f;
#pragma unroll
        for (int w = 0; w < 8; w++) v += lds_f32(sb + SM_RED + w * 128 + lane * 4);
        v += __shfl_xor_sync(0xffffffffu, v, 16);
        v = mod_value(v, b0 >> 6);
        publish_record(&g_rec[tag & 1][0][ridx], pack2(v, __shfl_down_sync(0xffffffffu, v, 1)), 2 * (lane & 1), b0 >> 6, lane < 8);
        if (lane == 0) TS(1);
      }
      mbar_wait_g(sb + BAR_G, 0);
#pragma unroll 1
      for (int i = 1; i < 4; i++) {
        const uint4* mp = &g_rec[tag & 1][(b0 >> 1) & (NREP - 1)][i == 1 ? (8 + (lane >> 2)) * RS + (lane & 3) : 16 * RS - 64 + 32 * i + lane];
        uint4 v0, v1; int it = 0;
        while (true) {
          v0 = ld_pkt16(mp); v1 = ld_pkt16(mp + RV);
          if (v0.x != 0 && v1.x != 0) break;
          spin_guard(it); __nanosleep(PLD);
        }
        put_record(sb, 32 * i + lane, v0);
        put_record(sb, 128 + 32 * i + lane, v1);
        mbar_arrive(sb + BAR_TAB - 8 + 8 * i);
        if (lane == 0) {
          TS(3 + i + (i > 2));
          if (i == 1) l2_prefetch(((b0 & 64) ? p.vc : p.kc) + (size_t)(((b0 >> 4) & 3) * 2048 + 1536) * 128 + (b0 & 15) * 4096, 8192);
        }
        __syncwarp();
      }
      TILE_ROLES();
      if (lane == 0) {
        int it = 0;
        do { __nanosleep(500); spin_guard(it); } while (ld_relaxed(&g_hflag[rt * 32]) != tag * 16u);
        fence_acquire_gpu();
        mbar_arrive(sb + BAR_HF);
        if (b < NFFN) for (int i = 0; i < 8; i++) { __nanosleep(800); l2_prefetch(p.wd + (size_t)(b * 32 + i * 4) * 1024, 8192); }
      }
      __syncwarp();
      {
        uint2 v; int it = 0;
        do { __nanosleep(1000); v = ld_pkt8(&g_vdone[(lane & 3) * 16]); spin_guard(it); }
        while (!(v.y == tag));
        __syncwarp();
        fence_acquire_gpu();
        if (lane == 1 || lane == 2) sts32(sb + SM_SCAL + (2 - lane) * 4, v.x);
      }
#pragma unroll 1
      for (int i = 0; i < 2; i++) {
        const int q = i * 32 + lane, pi = ct * 64 + q;
        const uint32_t vga = g_mod[2 * 512 + pi].x, vsb = g_mod[3 * 512 + pi].x, vcb = g_mod[4 * 512 + pi].x, vgb = g_mod[5 * 512 + pi].x;
        const uint32_t wr = reinterpret_cast<const uint32_t*>(p.w_r)[pi];
        const uint32_t c1 = hadd2(vcb, ONE2);
        const float al = lo2f(c1) * lo2f(wr), ah = hi2f(c1) * hi2f(wr);
        const uint32_t o8 = (q & 3) * 8 + ((q >> 2) & 1) * 4;
        sts32(sb + SM_GA + (q >> 3) * 32 + o8, vga);
        sts128(sb + SM_REC + q * 16, c1, vsb, vgb, 0);
        const uint32_t ahi = pack2(al, ah), alo = pack2(al - lo2f(ahi), ah - hi2f(ahi));
        const uint32_t ba = sb + SM_B1 + (q >> 3) * 128 + o8;
        sts32(ba, ONE2); sts32(ba + 32, ahi); sts32(ba + 64, alo); sts32(ba + 96, 0);
      }
      if (lane == 0) TS(28);
      if (lane == 0) {
        tma_prefetch_desc(&mWo); tma_prefetch_desc(&mOut); tma_prefetch_desc(&mWd); tma_prefetch_desc(&mWg); tma_prefetch_desc(&mWu);
#pragma unroll 1
        for (int r = 0; r < 4; r++) {
          int it = 0;
          do { __nanosleep(200); spin_guard(it); } while (ld_relaxed(&g_oflag[(rt * 4 + r) * 32]) != tag * 16u);
          if (r & 1) { fence_acquire_gpu(); mbar_arrive(sb + BAR_OF + 8 * (r >> 1)); }
          if (r == 1 && b < NFFN) {
            const uint64_t pef = policy_evict_first();
            mbar_wait_g(sb + BAR_T1, 0);
#pragma unroll 1
            for (int i = 0; i < 4; i++) {
              mbar_expect_tx(sb + BAR_FFN, 16384);
              tma_ld_hint(sb + SM_RING + i * ST1 + 32768, &mWg, b * 32, i * 256, sb + BAR_FFN, pef);
              __nanosleep(GATED);
            }
          }
        }
      }
      __syncwarp();
      if (b < NFFN) {
        mbar_wait_g(sb + BAR_TFREE, 0);
        const uint64_t pef = policy_evict_first();
#pragma unroll 1
        for (int i = 0; i < 5; i++) {
          if (i > 0 && lane == 0) {
            mbar_expect_tx(sb + BAR_FFN, 16384);
            tma_ld_hint(sb + SM_RING + (i - 1) * ST1 + 32768, &mWu, b * 32, (i - 1) * 256, sb + BAR_FFN, pef);
          }
          if (i < 4) {
#pragma unroll 1
            for (int j = 0; j < 8; j++) {
              asm volatile("prefetch.global.L2 [%0];" :: "l"(p.wu + (size_t)(i * 256 + j * 32 + lane) * 3584 + b * 32) : "memory");
              __nanosleep(UPD);
            }
            __nanosleep(500);
          }
        }
      }
      if (lane == 0) TS(29);
#pragma unroll 1
      for (int i = lane; i < 128; i += 32) st_pkt16(&g_stats[b * 128 + i], 0, 0, 0, 0);
      st_pkt16(&g_cand[b * 32 + lane], 0, 0, 0, 0);
      if (lane < 8) st_pkt16(&g_entry[(ct * 16 + rt) * 8 + lane], 0, 0, 0, 0);
#pragma unroll 1
      for (int i = lane; i < (b < NFFN ? 512 : 0); i += 32) st_pkt16(&g_ypart[((i >> 2) * NFFN + b) * 4 + (i & 3)], 0, 0, 0, 0);
      mbar_arrive(sb + BAR_VEC);
      uint4* const cp = &g_cand[b * 32 + lane];
      uint4* const ep = &g_entry[(ct * 16 + rt) * 8];
      nb_sync(NB_AMAX, 288);
      TV(0);
      const uint2 e = lds64(sb + SM_AMAX + (lane & 7) * 8);
      const int tmax = __reduce_max_sync(0xffffffffu, (int)e.x);
      const uint32_t row = ~tmax & 127;
      const int wl = row >> 4;
      const uint32_t xa = sb + SM_X2 + (row >> 6) * 16384 + (lane >> 4) * 8192 + (row & 63) * 128 + (lane & 3) * 4
                        + ((((lane >> 1) & 6) ^ (row & 7)) * 16);
      const uint32_t v0 = lds32(xa), v1 = lds32(xa ^ 16);
      if (lane == wl) st_pkt16(ep, (tmax | 127) - rt, rt * 128 + row, e.y, tag);
      st_pkt16(cp, v0, v1, tag, 0);
      if (lane == 0) { sts32(sb + SM_CAND, row); mbar_arrive(sb + BAR_CAND); }
      TV(1);
      if (lane == 0) TS(15);
    }
  } else {
    const int warp = tid >> 5;
    const int wg = warp >> 2, wq = warp & 3;
    const int g = lane >> 2, t = lane & 3;
    uint32_t tag;
    uint32_t ln[4];
    float acc[128];
    uint32_t bf[16];
    auto gemv = [&]() {
          if (late) mbar_wait(sb + BAR_WH, 0); else
          asm volatile("cp.async.wait_all;" ::: "memory");
          float d0[4] = {0.f, 0.f, 0.f, 0.f}, d1[4] = {0.f, 0.f, 0.f, 0.f};
#pragma unroll
          for (int i = 0; i < 8; i++) {
            const uint4 wv = lds128(slab_addr + i * 512);
            const uint32_t a[4] = {wv.x, wv.y, wv.z, wv.w};
            mma16816((i & 1) ? d1 : d0, a, bf[2 * i], bf[2 * i + 1]);
          }
#pragma unroll
          for (int i = 0; i < 4; i++) { d0[i] += d1[i]; d0[i] += __shfl_xor_sync(0xffffffffu, d0[i], 6); }
          const uint32_t dst = mapa(sb + SM_MISC, t & 1) - SM_MISC;
          if (!(lane & 6)) st_async_f32x4(dst + SM_RED + warp * 128 + rank * 64 + g * 8, d0, dst + BAR_RED);
          TH(4);
    };
    {
      asm volatile("barrier.cluster.arrive.relaxed.aligned;" ::: "memory");
      if (lane == 0) st_pkt16(&g_lnst[8 * b0 + warp], 0, 0, 0, 0);
      TH(1);
      asm volatile("setmaxnreg.inc.sync.aligned.u32 240;");
      TH(2);
#pragma unroll
      for (int i = 0; i < 8; i++) {
        const float sv = silu_f((g & 4) ? hi2f(cw[i]) : lo2f(cw[i]));
        const uint32_t sp = (g & 1) ? pack2(0.f, sv) : pack2(sv, 0.f);
        bf[2 * i] = (g & 2) ? 0 : sp; bf[2 * i + 1] = (g & 2) ? sp : 0;
      }
      asm volatile("barrier.cluster.wait.aligned;" ::: "memory");
#pragma unroll
      for (int i = 0; i < 128; i++) acc[i] = 0.f;
      reg_fence<128>(acc);
      tag = __shfl_sync(0xffffffffu, epoch, 0) + 1;
      TH(3);
      if (slab && !late) gemv();
      {
        {
          mbar_wait(sb + BAR_XH, 0);
          TH(5);
          float ds[4] = {0.f, 0.f, 0.f, 0.f}, dq[4][4];
#pragma unroll
          for (int i = 0; i < 4; i++) { dq[i][0] = dq[i][1] = dq[i][2] = dq[i][3] = 0.f; }
#pragma unroll
          for (int i = 0; i < 8; i++) {
            uint32_t a[4];
            ldsm4(sb + SM_XROW + wg * ST1 + wq * 4096 + ((lane >> 3) & 1) * 2048 + i * 256 + (lane >> 4) * 128 + (lane & 7) * 16, a);
            mma16816(ds, a, ONE2, ONE2);
            mma1688(dq[0], a[0], a[1], a[0]); mma1688(dq[1], a[0], a[1], a[1]);
            mma1688(dq[2], a[2], a[3], a[2]); mma1688(dq[3], a[2], a[3], a[3]);
          }
          const bool dg = t == (g >> 1);
          const float q0 = dg ? ((g & 1) ? dq[0][1] + dq[2][1] : dq[0][0] + dq[2][0]) : 0.f;
          const float q1 = dg ? ((g & 1) ? dq[1][3] + dq[3][3] : dq[1][2] + dq[3][2]) : 0.f;
          float q = ((lane & 1) ? q1 : q0) + __shfl_xor_sync(0xffffffffu, (lane & 1) ? q0 : q1, 1);
          float sm = (lane & 1) ? ds[2] : ds[0];
          q += __shfl_xor_sync(0xffffffffu, q, 2);
#pragma unroll
          for (int o = 4; o <= 16; o <<= 1) { q += __shfl_xor_sync(0xffffffffu, q, o); sm += __shfl_xor_sync(0xffffffffu, sm, o); }
          const float mean = sm * (1.f / 1024.f);
          const float rd = rcp_f(rbf(sqrt_f(rbf(rbf(fmaxf(fmaf(-mean, mean, q * (1.f / 1024.f)), 0.f)) + 1e-5f))));
          const float mean1 = __shfl_sync(0xffffffffu, mean, 1), rd1 = __shfl_sync(0xffffffffu, rd, 1);
          const uint32_t rh = pack2(rd, rd1);
          if (lane == 0) st_pkt16(&g_lnst[8 * b0 + warp], pack2(-rbf(mean) * lo2f(rh), -rbf(mean1) * hi2f(rh)), rh, 0, tag);
          TH(6);
          if (tid == 0) TS(2);
        }
      }
    }
    if (slab && late) gemv();
    TILE_ROLES();
    const uint32_t xa0 = sb + SM_RING + (warp * 16 + (lane & 15)) * 128 + (((lane >> 4) ^ (lane & 7)) * 16);
    uint32_t V[16];
    {
      const uint4* mp = &g_rec[tag & 1][(b0 >> 1) & (NREP - 1)][RV * wg + (lane >> 2) * RS + (lane & 3)];
      const uint4* lp = &g_lnst[(8 * rt + warp) * 8 + (g >> 1)];
      mbar_wait(sb + BAR_FULL1, 0);
#pragma unroll
      for (int kk = 0; kk < 4; kk++) ldsm4(xa0 ^ (kk * 32), V + 4 * kk);
      uint4 v0 = make_uint4(1, 0, 0, 0), l0, l1;
      int it = 0;
      while ((uint32_t)clock() - c0 < HD) {}
      do { if (wq == 0) v0 = ld_pkt16(mp);
           l0 = ld_pkt16(lp); l1 = ld_pkt16(lp + 4); spin_guard(it); }
        while (!(__all_sync(0xffffffffu, v0.x != 0 && l0.w == tag && l1.w == tag)));
      TH(7);
      if (wq == 0) put_record(sb, 128 * wg + lane, v0);
      const uint32_t sel = (g & 1) ? 0x3232 : 0x1010;
      ln[0] = __byte_perm(l0.x, 0, sel); ln[1] = __byte_perm(l0.y, 0, sel);
      ln[2] = __byte_perm(l1.x, 0, sel); ln[3] = __byte_perm(l1.y, 0, sel);
      __syncwarp();
      if (lane < 2) mbar_arrive_cl(mapa(sb + BAR_G, lane));
      nb_sync(NB_CONS, 256);
      if (tid == 0) TS(3);
      TH(13);
    }

    const uint32_t rel = mapa(sb + SM_MISC, lane & 1) - SM_MISC;
    const uint32_t stsm_addr = sb + SM_STASH + wg * 16384 + (wq * 16 + (lane & 15)) * 128 + (((lane >> 4) ^ (lane & 7)) * 16);

    uint32_t ph = 0;
    uint32_t X[32];
    {
      const uint32_t tab0 = sb + SM_STASH + wg * 16384 + t * 16;
      const uint64_t db0 = mk_desc(sb + SM_RING + 16384, 8192);
      uint32_t A[2][16];
      uint32_t xa[4];
#pragma unroll
      for (int kk = 0; kk < 4; kk++) xa[kk] = xa0 ^ (kk * 32);
      uint32_t tab = tab0;
      reg_fence<4>(xa);
      asm volatile("{\n.reg .pred p;\nsetp.eq.u32 p, %4, 0;\n@p ld.shared.v4.u32 {%0,%1,%2,%3}, [%5];\n}"
        : "+r"(ln[2]), "+r"(ln[0]), "+r"(ln[3]), "+r"(ln[1]) : "r"(tag), "r"(sb));
      int hs = 2 * ct;
      uint4 R[4];
#pragma unroll
      for (int kk = 0; kk < 4; kk++) R[kk] = lds128(tab + (kk >> 1) * 2048 + (kk & 1) * 64);
#pragma unroll 1
      for (int k4 = 0; k4 < 4; k4++) {
#pragma unroll
        for (int s = 0; s < 4; s++) {
          uint32_t* a = A[s & 1];
          const int sn = (s + 1) & 3;
          const uint32_t pn = (k4 + (s == 3)) & 1;
          modulate_frags(a, V, R, ln);
          if (hs == (s & 2)) {
            if (s & 1) mbar_wait(sb + BAR_HS + 16 * wg, 0);
#pragma unroll
            for (int kk = 0; kk < 4; kk++) stsm4((stsm_addr + 4096) ^ (kk * 32), a[4 * kk], a[4 * kk + 1], a[4 * kk + 2], a[4 * kk + 3]);
            nb_arrive(NB_OST + wg, 160);
          }
          if (s == 0 && k4 == 0) TH(8);
          TQ(3 * s);
          if (s == 0 && k4 == 0 && tid == 0) { TS(6); TSC(61); }
          wg_fence();
#pragma unroll
          for (int kk = 0; kk < 4; kk++) wgmma_rs256<1>(acc, a + 4 * kk, db0 + s * (ST1 >> 4) + kk * 128);
          wg_commit();
          if (s == 3) TQ(12);
          if (s == 3 && k4 < 3) mbar_wait(sb + BAR_TAB + 8 * k4, 0);
          if (s == 3) TQ(13);
#pragma unroll
          for (int kk = 0; kk < 4; kk++) R[kk] = lds128(tab + (s + 1) * 128 + (kk >> 1) * 2048 + (kk & 1) * 64);
          wg_wait<1>();
          if (k4 == 0) TH(9 + s);
          TQ(3 * s + 1);
          reg_fence<16>(A[(s & 1) ^ 1]);
          if ((tid & 127) < 2 && (s | k4)) mbar_arrive_cl(rel + BAR_EMPTY1 + 8 * ((s + 3) & 3));
          if (s < 3 || k4 < 3) {
            mbar_wait(sb + BAR_FULL1 + 8 * sn, pn);
            TQ(3 * s + 2);
#pragma unroll
            for (int kk = 0; kk < 4; kk++) ldsm4(xa[kk] + sn * ST1, V + 4 * kk);
          }
        }
        tab += 512; hs -= 4;
      }
      mbar_wait(sb + BAR_HS + 16 * wg + 8, 0);
      wg_wait<0>();
      reg_fence<128>(acc);
    }
#pragma unroll 1
    for (int pair = 0; pair < 2; pair++) {
      uint32_t Q[32];
      TR(0);
      {
        if ((tid & 127) < 2) mbar_arrive_cl(rel + BAR_EMPTY1 + 8 * 3);
        if (pair == 1) mbar_wait(sb + BAR_STASH + 8 * wg, 1);
#pragma unroll
        for (int i = 0; i < 32; i++) Q[i] = pack2(acc[2 * i], acc[2 * i + 1]);
        const uint32_t qs = sb + SM_STASH + wg * 16384 + wq * 2048 + lane * 16;
#pragma unroll
        for (int i = 0; i < 8; i++)
          sts128(qs + (i & 3) * 512 + (i >> 2) * 8192, pack2(acc[64 + 8 * i], acc[65 + 8 * i]), pack2(acc[66 + 8 * i], acc[67 + 8 * i]),
                 pack2(acc[68 + 8 * i], acc[69 + 8 * i]), pack2(acc[70 + 8 * i], acc[71 + 8 * i]));
      }
      if (tid == 0) TS(8 + pair * 2);
      TR(1);
      float O[64], SL[32], SH[32];
      uint32_t PL[16], PH[16];
      SoftmaxState z;
      const uint64_t d0 = mk_desc(sb + SM_RING, 8192);
      {
        mbar_wait(sb + BAR_FULL1, ph);
        wg_fence();
        issue_qk(SL, Q, d0);
        wg_commit();
        issue_qk(SH, Q, d0 + 1024);
        wg_commit();
#pragma unroll
        for (int i = 0; i < 64; i++) O[i] = 0.f;
        reg_fence<64>(O);
        wg_wait<1>();
        reg_fence<32>(SL);
        softmax_start(z);
        softmax_half(SL, PL, O, z, true, tag);
        wg_wait<0>();
        reg_fence<32>(SH);
        if ((tid & 127) < 2) mbar_arrive_cl(rel + BAR_EMPTY1);
      }
      float lp0 = 0.f, lp1 = 0.f;
      uint32_t dB = (uint32_t)d0 + 1 * (ST1 >> 4), dA = (uint32_t)d0 + 2 * (ST1 >> 4);
      const uint32_t dBx = dB ^ ((uint32_t)d0 + 3 * (ST1 >> 4)), dAx = dA ^ (uint32_t)d0;
      uint32_t so = 0;
      bool ready = false;
#pragma unroll 1
      for (int i = 0; i < 7; i++) {
        TA(0);
        TR(2 + i);
        if (!ready) mbar_wait(sb + BAR_FULL1 + 8 + so, ph);
        TA(1);
        TA(2);
        wg_fence();
        issue_qk(SL, Q, (d0 & 0xffffffff00000000ull) | dB);
        if (i == 4) {
          __syncwarp();
          stage_o(O, lp0, lp1, stsm_addr);
        }
        wg_fence();
        issue_pv(O, PL, ((d0 & 0xffffffff00000000ull) | dB) + 1024, i != 4);
        wg_commit();
        if (i == 4) {
          nb_arrive(NB_OST + wg, 160);
        }
        TA(3);
        ph ^= i & 1;
        ready = mbar_test(sb + BAR_FULL1 + 16 - so, ph);
        softmax_half(SH, PH, O, z, false, tag);
        TA(4);
        wg_wait<0>();
        TA(5);
        reg_fence<32>(SL); reg_fence<16>(PL);
        if ((tid & 127) < 2) mbar_arrive_cl(rel + BAR_EMPTY1 + 8 + so);
        if (!ready) mbar_wait(sb + BAR_FULL1 + 16 - so, ph);
        TA(6);
        wg_fence();
        issue_qk(SH, Q, (d0 & 0xffffffff00000000ull) | dA);
        wg_commit();
        issue_pv(O, PH, ((d0 & 0xffffffff00000000ull) | dA) + 1024, 1);
        wg_commit();
        if (i == 2) {
          wg_wait<1>();
          reg_fence<32>(Q);
          const uint32_t qs = sb + SM_STASH + wg * 16384 + wq * 2048 + lane * 16;
#pragma unroll
          for (int j = 0; j < 8; j++) { const uint4 v = lds128(qs + (j & 3) * 512 + (j >> 2) * 8192); Q[4 * j] = v.x; Q[4 * j + 1] = v.y; Q[4 * j + 2] = v.z; Q[4 * j + 3] = v.w; }
        }
        TA(10);
        if (i == 3) { lp0 = z.l0; lp1 = z.l1; row_rcp(lp0, lp1); softmax_start(z); }
        TA(7);
        so ^= 16; dB ^= dBx; dA ^= dAx;
        ready = mbar_test(sb + BAR_FULL1 + 8 + so, ph);
        softmax_half(SL, PL, O, z, i == 3, tag);
        TA(8);
        wg_wait<0>();
        TA(9);
        reg_fence<32>(SH); reg_fence<16>(PH); reg_fence<64>(O); reg_fence<32>(Q);
        if ((tid & 127) < 2) mbar_arrive_cl(rel + BAR_EMPTY1 + so);
      }
      TAFLUSH();
      TR(9);
      {
        if (!ready) mbar_wait(sb + BAR_FULL1 + 8 * 3, ph);
        ph ^= 1;
        const uint64_t dv = d0 + 3 * (ST1 >> 4);
        wg_fence();
        issue_pv(O, PL, dv, 1);
        wg_commit();
        bb_fence(tag);
        softmax_half(SH, PH, O, z, false, tag);
        wg_fence();
        issue_pv(O, PH, dv + 1024, 1);
        wg_commit();
        TR(10);
        row_rcp(z.l0, z.l1);
        mbar_wait(sb + (pair ? BAR_X : BAR_STASH) + 8 * wg, 0);
#pragma unroll
        for (int kk = 0; kk < 8; kk++) ldsm4((stsm_addr + (kk >> 2) * 8192) ^ ((kk & 3) * 32), X + 4 * kk);
        reg_fence<32>(X);
        __syncwarp();
        wg_wait<0>();
        reg_fence<64>(O);
        TR(11);
        if ((tid & 127) < 2) mbar_arrive_cl(rel + BAR_EMPTY1 + 8 * 3);
        stage_o(O, z.l0, z.l1, stsm_addr);
        nb_arrive(NB_OST + wg, 160);
      }
      TR(12);
      if (tid == 0) { TS(9 + pair * 2); TSC(62); }
      if (pair == 1) break;
      {
        mbar_wait(sb + BAR_FULL1, ph);
        const uint64_t da = mk_desc(sb + SM_RING + wg * 8192, 16), db = mk_desc(sb + SM_RING + 16384, 8192);
        wg_fence();
        wgmma_ss256_z<1>(acc, da, db);
#pragma unroll
        for (int kk = 1; kk < 4; kk++) wgmma_ss256<1>(acc, da + kk * 2, db + kk * 128, 1);
        wg_commit();
      }
#pragma unroll 1
      for (int kt = 1; kt < 16; kt++) {
        const uint32_t s = kt & 3;
        if (s == 0) ph ^= 1;
        mbar_wait(sb + BAR_FULL1 + 8 * s, ph);
        const uint32_t st = sb + SM_RING + s * ST1;
        const uint64_t da = mk_desc(st + wg * 8192, 16), db = mk_desc(st + 16384, 8192);
        wg_fence();
#pragma unroll
        for (int kk = 0; kk < 4; kk++) wgmma_ss256<1>(acc, da + kk * 2, db + kk * 128, 1);
        wg_commit();
        wg_wait<1>();
        if ((tid & 127) < 2) mbar_arrive_cl(rel + BAR_EMPTY1 + 8 * ((s + 3) & 3));
      }
      ph ^= 1;
      wg_wait<0>();
      reg_fence<128>(acc);
      TR(13);
    }

    uint4 WG[16], WU[16];
    const int fp = 64 * warp + 8 * g + t;
    uint32_t fsb0, fsb1, fcb0, fcb1, fgb0, fgb1;
    const uint32_t gu_base = sb + SM_RING + (warp >> 1) * ST1 + 32768 + (warp & 1) * 8192;
    const uint32_t gu_addr = gu_base + t * 128 + (g & 1) * 64 + ((g >> 1) ^ t) * 16;
    {
      const uint64_t da0 = mk_desc(sb + SM_RING + __shfl_sync(0xffffffffu, wg, 0) * 8192, 16), db0 = mk_desc(sb + SM_RING + 16384, 8192);
#pragma unroll
      for (int n = 0; n < 4 + 5 * PEEL; n++) {
        const int s = n < 4 ? n : (n - 4) % 5;
        mbar_wait(sb + BAR_FULL1 + 8 * s, n < 4 ? 0 : ((n - 4) / 5 + (s < 4)) & 1);
        if (n < 4) TSX(40 + wg * 6 + n);
        const uint64_t da = da0 + s * (ST1 >> 4), db = db0 + s * (ST1 >> 4);
        wg_fence();
        if (n == 0) wgmma_ss128_z<1>(acc, da, db); else wgmma_ss128<1>(acc, da, db, 1);
#pragma unroll
        for (int kk = 1; kk < 4; kk++) wgmma_ss128<1>(acc, da + kk * 2, db + kk * 128, 1);
        wg_commit();
        if (n == 1) {
          mbar_wait(sb + BAR_OF, 0);
          const uint2* mp = &g_mod[3 * 512 + fp];
          fsb0 = ld_pkt8(mp).x; fsb1 = ld_pkt8(mp + 4).x; fcb0 = ld_pkt8(mp + 512).x; fcb1 = ld_pkt8(mp + 516).x;
          fgb0 = ld_pkt8(mp + 1024).x; fgb1 = ld_pkt8(mp + 1028).x;
        }
        if (n == 0 && b < NFFN) mbar_wait(sb + BAR_FFN, 0);
        {
          constexpr int NT = 4 + 5 * PEEL, F0 = NT > 16 ? NT - 16 : 0;
#pragma unroll
          for (int i = 0; i < 16; i++) if (F0 + i * (NT - F0) / 16 == n) WG[i] = lds128(gu_addr + i * 512);
        }
        if (n > 0) {
          wg_wait<1>();
          if ((tid & 127) < 2) mbar_arrive_cl(rel + BAR_EMPTY1 + 8 * (n == 4 ? 3 : s ? s - 1 : 4));
        }
      }
      TSX(44 + wg * 6);
      {
        uint32_t dep = 0;
#pragma unroll
        for (int i = 0; i < 16; i++) dep ^= WG[i].x;
        if (__shfl_sync(0xffffffffu, tag, dep & 31) == tag && lane == 2) mbar_arrive(sb + BAR_TFREE);
      }
      {
        uint32_t so = 0, sp = 4 * 8, par = PEEL + 1;
#pragma unroll 1
        for (int n = 4 + 5 * PEEL; n < 64; n++) {
          mbar_wait(sb + BAR_FULL1 + so, (par + (so >> 5)) & 1);
          const uint64_t da = da0 + so * (ST1 >> 7), db = db0 + so * (ST1 >> 7);
          wg_fence();
#pragma unroll
          for (int kk = 0; kk < 4; kk++) wgmma_ss128<1>(acc, da + kk * 2, db + kk * 128, 1);
          wg_commit();
          wg_wait<1>();
          if ((tid & 127) < 2) mbar_arrive_cl(rel + BAR_EMPTY1 + sp);
          sp = so; so += 8;
          if (so == 40) { so = 0; par++; }
        }
      }
    }
    mbar_wait(sb + BAR_VEC, 0);
    const int lrow = warp * 16 + g;
    uint2 ga[8], b1[8];
#pragma unroll
    for (int kk = 0; kk < 8; kk++) { ga[kk] = lds64(sb + SM_GA + kk * 32 + t * 8); b1[kk] = lds64(sb + SM_B1 + min(g, 3) * 32 + t * 8 + kk * 128); }
    uint4* const stp = &g_stats[b * 128 + lrow + 8 * t];
    bb_fence(tag);
    wg_wait<0>();
    reg_fence<64>(acc);
    if (tid == 0) { TS(12); TSC(63); }

    TT(0);
    {
      float d1[4] = {0.f, 0.f, 0.f, 0.f}, d2[4] = {0.f, 0.f, 0.f, 0.f}, d3[4] = {0.f, 0.f, 0.f, 0.f};
      float d4[4] = {0.f, 0.f, 0.f, 0.f}, d5[4] = {0.f, 0.f, 0.f, 0.f};
#pragma unroll
      for (int kk = 0; kk < 8; kk++) {
        uint32_t* x = X + 4 * kk;
        x[0] = hfma2(ga[kk].x, pack2(acc[8 * kk + 0], acc[8 * kk + 1]), x[0]);
        x[1] = hfma2(ga[kk].x, pack2(acc[8 * kk + 2], acc[8 * kk + 3]), x[1]);
        x[2] = hfma2(ga[kk].y, pack2(acc[8 * kk + 4], acc[8 * kk + 5]), x[2]);
        x[3] = hfma2(ga[kk].y, pack2(acc[8 * kk + 6], acc[8 * kk + 7]), x[3]);
        mma16816(d1, x, b1[kk].x, b1[kk].y);
        mma1688(d2, x[0], x[1], x[0]); mma1688(d3, x[0], x[1], x[1]);
        mma1688(d4, x[2], x[3], x[2]); mma1688(d5, x[2], x[3], x[3]);
      }
      const int qb = lane & 28;
      const float q0 = __shfl_sync(0xffffffffu, (g & 1) ? d2[1] + d4[1] : d2[0] + d4[0], qb | (g >> 1));
      const float q1 = __shfl_sync(0xffffffffu, (g & 1) ? d3[3] + d5[3] : d3[2] + d5[2], qb | (g >> 1));
      const float e0 = __shfl_xor_sync(0xffffffffu, t ? d1[0] : d1[3], 1);
      const float e1 = __shfl_sync(0xffffffffu, d1[2], qb);
      if (t < 2) st_pkt16(stp, __float_as_uint(t ? e1 : d1[0]), __float_as_uint(t ? q1 : q0),
                          __float_as_uint((t ? d1[2] : d1[1]) + e0), tag);
    }
    TSY(13);
    TT(1);
    float mb, rd, den, br;
    {
      const uint4* sp = &g_stats[(rt * 8 + 4 * (t & 1)) * 128 + lrow + 4 * (t & 2)];
      mbar_wait(sb + BAR_EMPTY1 + 8 * 3, 0);
#pragma unroll
      for (int kk = 0; kk < 8; kk++) stsm4((stsm_addr - SM_STASH + SM_X2 + (kk >> 2) * 8192) ^ ((kk & 3) * 32), X[4 * kk], X[4 * kk + 1], X[4 * kk + 2], X[4 * kk + 3]);
      if (b < NFFN) mbar_wait(sb + BAR_FFN, 1);
#pragma unroll
      for (int i = 0; i < WU1; i++) WU[i] = lds128(gu_addr + i * 512);
      bb_fence(tag);
      TT(2);
      uint4 v0, v1, v2, v3;
      int it = 0;
      do { v0 = ld_pkt16(sp); v1 = ld_pkt16(sp + 128); v2 = ld_pkt16(sp + 256); v3 = ld_pkt16(sp + 384); spin_guard(it); }
        while (!(__all_sync(0xffffffffu, v0.w == tag && v1.w == tag && v2.w == tag && v3.w == tag)));
      TT(3);
      float sm = (__uint_as_float(v0.x) + __uint_as_float(v1.x)) + (__uint_as_float(v2.x) + __uint_as_float(v3.x));
      float sq = (__uint_as_float(v0.y) + __uint_as_float(v1.y)) + (__uint_as_float(v2.y) + __uint_as_float(v3.y));
      float dt = (__uint_as_float(v0.z) + __uint_as_float(v1.z)) + (__uint_as_float(v2.z) + __uint_as_float(v3.z));
      sm += __shfl_xor_sync(0xffffffffu, sm, 1); sq += __shfl_xor_sync(0xffffffffu, sq, 1); dt += __shfl_xor_sync(0xffffffffu, dt, 1);
      const uint2 scal = lds64(sb + SM_SCAL);
      const float mu = sm * (1.f / 1024.f);
      mb = rbf(mu);
      den = rbf(sqrt_f(rbf(rbf(fmaxf(fmaf(-mu, mu, sq * (1.f / 1024.f)), 0.f)) + 1e-5f)));
      rd = rcp_f(den);
      br = fmaf(fmaf(-mb, __uint_as_float(scal.x), dt), rd, __uint_as_float(scal.y));
    }
    TSY(14);
    TT(4);
    {
      const int rb = __float_as_int(br);
      const int key = ((rb ^ ((rb >> 31) & 0x7fffffff)) | 127) - (lrow + 4 * (t & 2));
      if (key == __reduce_max_sync(0xffffffffu, key)) sts64(sb + SM_AMAX + warp * 8, (uint32_t)key, pack2(mb, den));
      __syncwarp();
      nb_arrive(NB_AMAX, 288);
    }
    TT(5);
    const uint4* ep = &g_entry[(warp * 16 + (lane & 15)) * 8];
    const uint32_t slot = sb + SM_STASH + wg * 8192 + (tid & 127) * 16;
    cp_async16(slot, ep);
    {
      const float rh = rbf(rd);
      const uint32_t u = pack2(-mb * rh, rh);
      const int qb = lane & 28;
      const uint32_t u0 = __shfl_sync(0xffffffffu, u, qb), u1 = __shfl_sync(0xffffffffu, u, qb | 2);
      const uint32_t m0 = __byte_perm(u0, 0, 0x1010), h0 = __byte_perm(u0, 0, 0x3232);
      const uint32_t m1 = __byte_perm(u1, 0, 0x1010), h1 = __byte_perm(u1, 0, 0x3232);
#pragma unroll
      for (int j = 0; j < 16; j++) {
        const uint4 rec = lds128(sb + SM_REC + (4 * j + t) * 16);
        X[2 * j] = hfma2(rec.z, hfma2(hfma2(X[2 * j], h0, m0), rec.x, rec.y), X[2 * j]);
        X[2 * j + 1] = hfma2(rec.z, hfma2(hfma2(X[2 * j + 1], h1, m1), rec.x, rec.y), X[2 * j + 1]);
      }
#pragma unroll
      for (int kk = 0; kk < 8; kk++) stsm4((stsm_addr - SM_STASH + SM_OUT + (kk >> 2) * 8192) ^ ((kk & 3) * 32), X[4 * kk], X[4 * kk + 1], X[4 * kk + 2], X[4 * kk + 3]);
    }
    cp_async_wait();
    uint4 ent = lds128(slot);
    TSY(16);
    TT(6);
    int wrow;
    uint32_t xs0, xs1, hs0, hs1;
    uint32_t WD[64];
    const uint32_t wd_addr = sb + SM_RING + wg * ST1 + wq * 8192 + ((lane & 7) + ((lane >> 4) << 3)) * 128 + ((((lane >> 3) & 1) ^ (lane & 7)) * 16);
    {
      int gmax;
      auto leader = [&]() {
        gmax = __reduce_max_sync(0xffffffffu, ent.w == tag ? (int)ent.x : (int)0x8000000f);
        return ~gmax & 15;
      };
      int wt = leader(), it = 0;
      TT(7);
      nb_arrive(NB_OST + wg, 160);
      TT(8);
      cp_async16(slot + 2048, &g_cand[(wt * 8 + warp) * 32 + lane]);
      if (ent.w != tag) cp_async16(slot, ep);
#pragma unroll
      for (int i = WU1; i < 16; i++) WU[i] = lds128(gu_addr + i * 512);
      if (b < NFFN) mbar_wait(sb + BAR_FFN + 8, 0);
#pragma unroll
      for (int mt = 0; mt < 8; mt++)
#pragma unroll
        for (int s = 0; s < 2; s++) ldsm4t((wd_addr + (mt >> 2) * 4096 + s * 2048) ^ ((mt & 3) * 32), WD + (mt * 2 + s) * 4);
      cp_async_wait();
      uint4 v = lds128(slot + 2048);
      ent = lds128(slot);
      TT(9);
      while (true) {
        const int have = wt;
        wt = leader();
        if (__all_sync(0xffffffffu, ent.w == tag && have == wt && v.z == tag)) break;
        v = ld_pkt16(&g_cand[(wt * 8 + warp) * 32 + lane]);
        if (ent.w != tag) ent = ld_pkt16(ep);
        spin_guard(it);
      }
      TT(10);
      ent.x = gmax ^ ((gmax >> 31) & 0x7fffffff);
      wrow = __shfl_sync(0xffffffffu, ent.y, wt); ent.z = __shfl_sync(0xffffffffu, ent.z, wt);
      xs0 = v.x; xs1 = v.y;
      const uint32_t mm = __byte_perm(ent.z, 0, 0x1010);
      const float rs = rcp_f(hi2f(ent.z));
      const uint32_t e0 = hsub2(xs0, mm), e1 = hsub2(xs1, mm);
      hs0 = hfma2(pack2(lo2f(e0) * rs, hi2f(e0) * rs), hadd2(fcb0, ONE2), fsb0);
      hs1 = hfma2(pack2(lo2f(e1) * rs, hi2f(e1) * rs), hadd2(fcb1, ONE2), fsb1);
    }
    if ((tid & 127) == 0) sts32(sb + SM_WROW + 4 * wg, wrow);
    nb_arrive(NB_WIN + wg, 160);
    TSY(17);
    TT(11);
    if (b < NFFN) {
      float da[4][4];
#pragma unroll
      for (int i = 0; i < 4; i++) { da[i][0] = da[i][1] = da[i][2] = da[i][3] = 0.f; }
      const uint32_t selv = ((g & 1) ? 0x1044 : 0x4410) + ((g & 4) ? ((g & 1) ? 0x2200 : 0x0022) : 0);
      const uint32_t sel0 = (g & 2) ? 0x4444 : selv, sel1 = (g & 2) ? selv : 0x4444;
#pragma unroll
      for (int s = 0; s < 16; s++) {
        const uint32_t v = __shfl_sync(0xffffffffu, (s & 1) ? hs1 : hs0, 4 * (s >> 1) + t);
        const uint32_t b0 = __byte_perm(v, 0, sel0), b1 = __byte_perm(v, 0, sel1);
        const uint32_t a0[4] = {WG[s].x, WG[s].y, WG[s].z, WG[s].w};
        const uint32_t a1[4] = {WU[s].x, WU[s].y, WU[s].z, WU[s].w};
        mma16816(da[(s & 1) * 2], a0, b0, b1);
        mma16816(da[(s & 1) * 2 + 1], a1, b0, b1);
      }
      {
        float v[4];
#pragma unroll
        for (int i = 0; i < 4; i++) {
          const float vg = da[0][i] + da[2][i], vu = da[1][i] + da[3][i];
          v[i] = ((g & 1) ? vu : vg) + __shfl_xor_sync(0xffffffffu, (g & 1) ? vg : vu, 6);
        }
        if ((t >> 1) == (g & 1))
          sts128(gu_base + (g & 1) * 128 + (g >> 1) * 32 + (t & 1) * 16, __float_as_uint(v[0]), __float_as_uint(v[1]), __float_as_uint(v[2]), __float_as_uint(v[3]));
      }
      TT(12);
      nb_sync(NB_CONS, 256);
      float gp[8], up[8];
#pragma unroll
      for (int w = 0; w < 8; w++) {
        const uint32_t a = sb + SM_RING + (w >> 1) * ST1 + 32768 + (w & 1) * 8192 + lane * 4;
        gp[w] = lds_f32(a); up[w] = lds_f32(a + 128);
      }
      const float gsum = ((gp[0] + gp[1]) + (gp[2] + gp[3])) + ((gp[4] + gp[5]) + (gp[6] + gp[7]));
      const float usum = ((up[0] + up[1]) + (up[2] + up[3])) + ((up[4] + up[5]) + (up[6] + up[7]));
      const float act = rbf(silu_f(rbf(gsum))) * rbf(usum);
      TT(13);
      const uint32_t ap = pack2(act, __shfl_down_sync(0xffffffffu, act, 1));
      const uint32_t b00 = __shfl_sync(0xffffffffu, ap, 2 * t), b01 = __shfl_sync(0xffffffffu, ap, 2 * t + 8);
      const uint32_t b10 = __shfl_sync(0xffffffffu, ap, 2 * t + 16), b11 = __shfl_sync(0xffffffffu, ap, 2 * t + 24);
      float y[8][4];
#pragma unroll
      for (int mt = 0; mt < 8; mt++) {
        y[mt][0] = y[mt][1] = y[mt][2] = y[mt][3] = 0.f;
        mma16816(y[mt], WD + (mt * 2) * 4, b00, b01);
        mma16816(y[mt], WD + (mt * 2 + 1) * 4, b10, b11);
      }
#pragma unroll
      for (int e = 0; e < 2; e++) {
        const float v0 = t == 0 ? y[e][0] : t == 1 ? y[2 + e][0] : t == 2 ? y[4 + e][0] : y[6 + e][0];
        const float v1 = t == 0 ? y[e][2] : t == 1 ? y[2 + e][2] : t == 2 ? y[4 + e][2] : y[6 + e][2];
        const int f = 16 * warp + 2 * (2 * t + e) + (g >> 2);
        st_pkt16(&g_ypart[(f * NFFN + b) * 4 + (g & 3)], __float_as_uint(v0), __float_as_uint(v1), tag, 0);
      }
    }
    TSY(18);
    TT(14);
    {
      const int pw = warp - (warp > (b >> 4));
      if (warp != (b >> 4)) {
        const uint4* yp = &g_ypart[b * NFFN * 4 + pw * 64 + lane];
        uint4 v0, v1;
        int it = 0;
        { const uint32_t c1 = clock(); while ((uint32_t)clock() - c1 < (b < NFFN ? YD : YD + 1500)) {} }
        do { v0 = ld_pkt16(yp); v1 = ld_pkt16(yp + 32); spin_guard(it); }
        while (!(__all_sync(0xffffffffu, v0.z == tag && v1.z == tag)));
        float y0 = __uint_as_float(v0.x) + __uint_as_float(v1.x), y1 = __uint_as_float(v0.y) + __uint_as_float(v1.y);
#pragma unroll
        for (int o = 4; o <= 16; o <<= 1) { y0 += __shfl_xor_sync(0xffffffffu, y0, o); y1 += __shfl_xor_sync(0xffffffffu, y1, o); }
        if (lane < 4) sts64(sb + SM_YRED + pw * 32 + lane * 8, __float_as_uint(y0), __float_as_uint(y1));
      }
    }
    TT(15);
    if (warp != (b >> 4)) {
      nb_arrive(NB_CONS, 256);
    } else {
      nb_sync(NB_CONS, 256);
      float y0 = 0.f, y1 = 0.f;
      if (lane < 28) { const uint2 e = lds64(sb + SM_YRED + lane * 8); y0 = __uint_as_float(e.x); y1 = __uint_as_float(e.y); }
#pragma unroll
      for (int o = 4; o <= 16; o <<= 1) { y0 += __shfl_xor_sync(0xffffffffu, y0, o); y1 += __shfl_xor_sync(0xffffffffu, y1, o); }
      const int src = 2 * (t & 1);
      const float ya = __shfl_sync(0xffffffffu, y0, src), yb = __shfl_sync(0xffffffffu, y0, src + 1);
      const float yc = __shfl_sync(0xffffffffu, y1, src), yd = __shfl_sync(0xffffffffu, y1, src + 1);
      if (g == ((b >> 1) & 7) && (t >> 1) == (b & 1)) {
        const float rs = rbf(__uint_as_float(ent.x));
        const float sg = sigmoid_f(rs);
        const uint32_t sg2 = pack2(sg, sg);
        const uint32_t o0 = hadd2(xs0, hmul2(fgb0, hadd2(hs0, hmul2(pack2(ya, yb), sg2))));
        const uint32_t o1 = hadd2(xs1, hmul2(fgb1, hadd2(hs1, hmul2(pack2(yc, yd), sg2))));
        uint32_t* op = reinterpret_cast<uint32_t*>(p.out + (size_t)wrow * 1024) + fp;
        op[0] = o0; op[4] = o1;
      }
      if (b == 0) {
        if (lane < 8) st_relaxed(&p.sc->ticket[lane * 32], 0);
        st_relaxed(&p.sc->epoch[lane], tag);
      }
      if (lane == 0) TS(19);
    }
  }
}

typedef CUresult (*EncodeFn)(CUtensorMap*, CUtensorMapDataType, cuuint32_t, void*, const cuuint64_t*, const cuuint64_t*,
                             const cuuint32_t*, const cuuint32_t*, CUtensorMapInterleave, CUtensorMapSwizzle,
                             CUtensorMapL2promotion, CUtensorMapFloatOOBfill);

CUtensorMap make_map(EncodeFn enc, const void* ptr, uint64_t rows, uint64_t cols, uint32_t box_rows, uint32_t box_cols, CUtensorMapSwizzle sw) {
  CUtensorMap m;
  cuuint64_t dims[2] = {cols, rows};
  cuuint64_t strides[1] = {cols * 2};
  cuuint32_t box[2] = {box_cols, box_rows};
  cuuint32_t es[2] = {1, 1};
  enc(&m, CU_TENSOR_MAP_DATA_TYPE_BFLOAT16, 2, const_cast<void*>(ptr), dims, strides, box, es, CU_TENSOR_MAP_INTERLEAVE_NONE, sw,
      CU_TENSOR_MAP_L2_PROMOTION_L2_128B, CU_TENSOR_MAP_FLOAT_OOB_FILL_NONE);
  return m;
}

CUtensorMap make_map3(EncodeFn enc, const void* ptr, uint64_t rows, uint64_t cols, uint32_t box_rows, uint32_t box_blks) {
  CUtensorMap m;
  cuuint64_t dims[3] = {64, rows, cols / 64};
  cuuint64_t strides[2] = {cols * 2, 128};
  cuuint32_t box[3] = {64, box_rows, box_blks};
  cuuint32_t es[3] = {1, 1, 1};
  enc(&m, CU_TENSOR_MAP_DATA_TYPE_BFLOAT16, 3, const_cast<void*>(ptr), dims, strides, box, es, CU_TENSOR_MAP_INTERLEAVE_NONE,
      CU_TENSOR_MAP_SWIZZLE_128B, CU_TENSOR_MAP_L2_PROMOTION_L2_128B, CU_TENSOR_MAP_FLOAT_OOB_FILL_NONE);
  return m;
}

}

extern "C" void kernel_launch(void* const* d_in, const int* in_sizes, int n_in, void* d_out, int out_size) {
  (void)in_sizes; (void)n_in; (void)out_size;
  Params p;
  p.x = (const bf16*)d_in[0]; p.kc = (const bf16*)d_in[1]; p.vc = (const bf16*)d_in[2];
  p.wq = (const bf16*)d_in[3]; p.wo = (const bf16*)d_in[4]; p.w_r = (const bf16*)d_in[6];
  p.wg = (const bf16*)d_in[7]; p.wu = (const bf16*)d_in[8]; p.wd = (const bf16*)d_in[9];
  p.c = (const bf16*)d_in[10]; p.w_mod = (const bf16*)d_in[11]; p.out = (bf16*)d_out;

  void* fn = nullptr;
  cudaDriverEntryPointQueryResult st;
  cudaGetDriverEntryPoint("cuTensorMapEncodeTiled", &fn, cudaEnableDefault, &st);
  EncodeFn enc = (EncodeFn)fn;
  void* scp = nullptr;
  cudaGetSymbolAddress(&scp, g_scratch);
  p.sc = (Scratch*)scp;
  void *hp = p.sc->h, *op = p.sc->o;
  const CUtensorMapSwizzle S128 = CU_TENSOR_MAP_SWIZZLE_128B;
  CUtensorMap mH = make_map(enc, hp, 2048, 1024, 64, 64, S128);
  CUtensorMap mWq = make_map3(enc, p.wq, 1024, 4096, 64, 4);
  CUtensorMap mK = make_map(enc, p.kc, 8192, 128, 64, 64, S128);
  CUtensorMap mV = make_map(enc, p.vc, 8192, 128, 64, 64, S128);
  CUtensorMap mO = make_map(enc, op, 2048, 4096, 64, 64, S128);
  CUtensorMap mWo = make_map3(enc, p.wo, 4096, 1024, 64, 2);
  CUtensorMap mX = make_map(enc, p.x, 2048, 1024, 64, 64, S128);
  CUtensorMap mOut = make_map(enc, p.out, 2048, 1024, 64, 64, S128);
  CUtensorMap mWg = make_map(enc, p.wg, 1024, 3584, 256, 32, CU_TENSOR_MAP_SWIZZLE_64B);
  CUtensorMap mWu = make_map(enc, p.wu, 1024, 3584, 256, 32, CU_TENSOR_MAP_SWIZZLE_64B);
  CUtensorMap mWd = make_map3(enc, p.wd, 3584, 1024, 32, 8);
  CUtensorMap mWm = make_map(enc, p.w_mod, 1024, 6144, 16, 256, CU_TENSOR_MAP_SWIZZLE_NONE);
  CUtensorMap mWh = make_map(enc, p.w_mod, 1024, 6144, 256, 32, CU_TENSOR_MAP_SWIZZLE_64B);
  CUtensorMap mWs = make_map(enc, p.w_mod, 1024, 6144, 128, 128, CU_TENSOR_MAP_SWIZZLE_NONE);
  cudaFuncSetAttribute(fused_kernel, cudaFuncAttributeMaxDynamicSharedMemorySize, SMEM_BYTES);
  fused_kernel<<<NCTA, NTHREADS, SMEM_BYTES>>>(p, mH, mWq, mK, mV, mO, mWo, mX, mOut, mWg, mWu, mWd, mWm, mWs, mWh);
}
```

```cpp
#include <cuda_runtime.h>
#include <cuda_bf16.h>
#include <cuda.h>
#include <stdint.h>
#include <stddef.h>

#define UPD 200
#define GATED 700
#define PFW 100
#define OP0 200
#define OP3 90
#define PLD 200
#define WL 3500
#define SPT 5000
#define HD 6000
#define YD 500
#define PEEL 1
#define WU1 12

namespace {

typedef __nv_bfloat16 bf16;

constexpr int NTHREADS = 384;
constexpr int NMAIN = 128;
constexpr int NCTA = 132;
constexpr int RS = 8, RV = 16 * RS + 64;
constexpr int NREP = 4;
constexpr int NFFN = 112;

constexpr uint32_t SM_RING = 0;
constexpr uint32_t ST1 = 49152;
constexpr uint32_t ST2 = 32768;
constexpr int NST2 = 6;
constexpr uint32_t SM_STASH = 196608;
constexpr uint32_t SM_MISC = 229376;
constexpr uint32_t BAR_FULL1 = SM_MISC + 0;
constexpr uint32_t BAR_EMPTY1 = SM_MISC + 40;
constexpr uint32_t BAR_FULL2 = SM_MISC + 0;
constexpr uint32_t BAR_EMPTY2 = SM_MISC + 48;
constexpr uint32_t BAR_STASH = SM_MISC + 160;
constexpr uint32_t BAR_SFREE = SM_MISC + 176;
constexpr uint32_t BAR_TFREE = SM_MISC + 184;
constexpr uint32_t BAR_FFN = SM_MISC + 192;
constexpr uint32_t BAR_VEC = SM_MISC + 208;
constexpr uint32_t BAR_RED = SM_MISC + 216;
constexpr uint32_t BAR_XH = SM_MISC + 152;
constexpr uint32_t BAR_HS = SM_MISC + 80;
constexpr uint32_t BAR_G = SM_MISC + 112;
constexpr uint32_t BAR_T1 = SM_MISC + 120;
constexpr uint32_t BAR_HF = SM_MISC + 128;
constexpr uint32_t BAR_X = SM_MISC + 136;
constexpr uint32_t BAR_OF = SM_MISC + 224;
constexpr uint32_t BAR_ROLE = SM_MISC + 240;
constexpr uint32_t SM_ROLE = SM_MISC + 248;
constexpr uint32_t SM_GA = SM_MISC + 256;
constexpr uint32_t SM_SCAL = SM_MISC + 512;
constexpr uint32_t SM_WROW = SM_MISC + 520;
constexpr uint32_t SM_AMAX = SM_MISC + 528;
constexpr uint32_t SM_YRED = SM_MISC + 656;
constexpr uint32_t SM_X2 = 2 * ST1, SM_OUT = 3 * ST1;
constexpr uint32_t SM_REC = SM_MISC + 1024;
constexpr uint32_t BAR_TAB = SM_MISC + 1000;
constexpr uint32_t BAR_CAND = SM_MISC + 880;
constexpr uint32_t SM_CAND = SM_MISC + 888;
constexpr uint32_t BAR_WH = SM_MISC + 960;
constexpr uint32_t SM_WSLAB = 2 * 49152 + 16384;
constexpr uint32_t SM_XROW = 2 * 49152;
constexpr uint32_t SM_RED = SM_MISC + 2048;
constexpr uint32_t SM_B1 = SM_MISC + 2048;
constexpr uint32_t SMEM_BYTES = 232448;

constexpr int NB_CONS = 1, NB_WIN = 2  , NB_OST = 4  , NB_AMAX = 6;

struct __align__(1024) Scratch {
  uint32_t epoch[32];
  uint32_t hflag[16 * 32];
  uint32_t oflag[64 * 32];
  uint2 vdone[4 * 16];
  uint32_t pad[96 + 512];
  uint32_t ticket[8 * 32];
  uint2 mod[3072];
  uint4 rec[2][NREP][2 * RV];
  uint4 lnst[1024];
  uint4 entry[8 * 16 * 8];
  uint4 cand[16 * 8 * 32];
  uint4 stats[16 * 8 * 128];
  uint4 ypart[128 * NFFN * 4];
  unsigned long long ts[NCTA * 64];
  uint16_t h[2048 * 1024];
  uint16_t o[2048 * 4096];
};
__device__ Scratch g_scratch;
#define g_epoch (p.sc->epoch[0])
#define g_hflag (p.sc->hflag)
#define g_oflag (p.sc->oflag)
#define g_mod (p.sc->mod)
#define g_entry (p.sc->entry)
#define g_cand (p.sc->cand)
#define g_stats (p.sc->stats)
#define g_ypart (p.sc->ypart)
#define g_vdone (p.sc->vdone)
#define g_lnst (p.sc->lnst)
#define g_rec (p.sc->rec)
#define g_ts (p.sc->ts)
#define g_h (p.sc->h)

struct Params {
  const bf16* w_mod; const bf16* c; Scratch* sc; const bf16* x; const bf16* w_r; bf16* out;
  const bf16* wq; const bf16* wo; const bf16* wg; const bf16* wu; const bf16* wd; const bf16* kc; const bf16* vc;
};

__device__ __forceinline__ uint32_t smem_u32(const void* p) { return (uint32_t)__cvta_generic_to_shared(p); }
__device__ __forceinline__ void mbar_init(uint32_t bar, uint32_t cnt) { asm volatile("mbarrier.init.shared::cta.b64 [%0], %1;" :: "r"(bar), "r"(cnt) : "memory"); }
__device__ __forceinline__ void mbar_expect_tx(uint32_t bar, uint32_t bytes) { asm volatile("mbarrier.arrive.expect_tx.shared::cta.b64 _, [%0], %1;" :: "r"(bar), "r"(bytes) : "memory"); }
__device__ __forceinline__ void mbar_arrive(uint32_t bar) { asm volatile("mbarrier.arrive.shared::cta.b64 _, [%0];" :: "r"(bar) : "memory"); }
__device__ __forceinline__ void mbar_arrive_cl(uint32_t cluster_addr) { asm volatile("mbarrier.arrive.shared::cluster.b64 _, [%0];" :: "r"(cluster_addr) : "memory"); }
__device__ __forceinline__ uint32_t mapa(uint32_t addr, uint32_t cta) { uint32_t r; asm("mapa.shared::cluster.u32 %0, %1, %2;" : "=r"(r) : "r"(addr), "r"(cta)); return r; }
__device__ __forceinline__ bool mbar_test(uint32_t bar, uint32_t parity) {
  uint32_t ok;
  asm volatile("{\n.reg .pred p;\nmbarrier.test_wait.parity.shared::cta.b64 p, [%1], %2;\nselp.u32 %0, 1, 0, p;\n}" : "=r"(ok) : "r"(bar), "r"(parity) : "memory");
  return ok;
}
constexpr int SPIN_LIMIT = 300000;
__device__ __forceinline__ void spin_guard(int& it) {
  asm volatile("{\n.reg .pred p;\n.reg .b64 z;\nadd.s32 %0, %0, 1;\nsetp.gt.s32 p, %0, %1;\nmov.b64 z, 0;\n@p st.volatile.global.u32 [z], %0;\n}" : "+r"(it) : "n"(SPIN_LIMIT));
}
__device__ __forceinline__ void mbar_wait_g(uint32_t bar, uint32_t parity) {
  asm volatile("{\n.reg .pred p, q;\n.reg .b32 c;\n.reg .b64 z;\nmov.b32 c, 0;\nmov.b64 z, 0;\nMW_LOOP:\n"
               "mbarrier.try_wait.parity.shared::cta.b64 p, [%0], %1;\nadd.s32 c, c, 1;\nsetp.gt.s32 q, c, %2;\n"
               "@q st.volatile.global.u32 [z], c;\n@!p bra MW_LOOP;\n}" :: "r"(bar), "r"(parity), "n"(SPIN_LIMIT) : "memory");
}
__device__ __forceinline__ void mbar_wait(uint32_t bar, uint32_t parity) {
  asm volatile("{\n.reg .pred p;\nMW_LOOP:\nmbarrier.try_wait.parity.shared::cta.b64 p, [%0], %1;\n@!p bra MW_LOOP;\n}" :: "r"(bar), "r"(parity) : "memory");
}
__device__ __forceinline__ void bb_fence(uint32_t v) {
  asm volatile("{\n.reg .pred p;\n.reg .u32 c;\nsetp.ne.u32 p, %0, 0;\n@p bra.uni BF_DONE;\nBF_LOOP:\nnanosleep.u32 1;\nmov.u32 c, %%clock;\nsetp.eq.u32 p, c, 0;\n@p bra.uni BF_LOOP;\nBF_DONE:\n}" :: "r"(v) : "memory");
}
__device__ __forceinline__ bool elect_one() {
  uint32_t pred;
  asm volatile("{\n.reg .pred P;\nelect.sync _|P, 0xffffffff;\nselp.u32 %0, 1, 0, P;\n}" : "=r"(pred));
  return pred;
}
__device__ __forceinline__ void tma_ld_hint(uint32_t dst, const CUtensorMap* m, int c0, int c1, uint32_t bar, uint64_t pol) {
  asm volatile("cp.async.bulk.tensor.2d.shared::cluster.global.mbarrier::complete_tx::bytes.L2::cache_hint [%0], [%1, {%3, %4}], [%2], %5;"
    :: "r"(dst), "l"(m), "r"(bar), "r"(c0), "r"(c1), "l"(pol) : "memory");
}
__device__ __forceinline__ void tma_ld_mc(uint32_t dst, const CUtensorMap* m, int c0, int c1, uint32_t bar) {
  asm volatile("cp.async.bulk.tensor.2d.shared::cluster.global.mbarrier::complete_tx::bytes.multicast::cluster [%0], [%1, {%3, %4}], [%2], %5;"
    :: "r"(dst), "l"(m), "r"(bar), "r"(c0), "r"(c1), "h"((uint16_t)3) : "memory");
}
__device__ __forceinline__ void tma_ld_mc_hint(uint32_t dst, const CUtensorMap* m, int c0, int c1, uint32_t bar, uint64_t pol) {
  asm volatile("cp.async.bulk.tensor.2d.shared::cluster.global.mbarrier::complete_tx::bytes.multicast::cluster.L2::cache_hint [%0], [%1, {%3, %4}], [%2], %5, %6;"
    :: "r"(dst), "l"(m), "r"(bar), "r"(c0), "r"(c1), "h"((uint16_t)3), "l"(pol) : "memory");
}
__device__ __forceinline__ void tma_ld3_hint(uint32_t dst, const CUtensorMap* m, int row, int blk, uint32_t bar, uint64_t pol) {
  asm volatile("cp.async.bulk.tensor.3d.shared::cluster.global.mbarrier::complete_tx::bytes.L2::cache_hint [%0], [%1, {0, %3, %4}], [%2], %5;"
    :: "r"(dst), "l"(m), "r"(bar), "r"(row), "r"(blk), "l"(pol) : "memory");
}
__device__ __forceinline__ void tma_st(const CUtensorMap* m, int c0, int c1, uint32_t src) {
  asm volatile("cp.async.bulk.tensor.2d.global.shared::cta.bulk_group [%0, {%2, %3}], [%1];" :: "l"(m), "r"(src), "r"(c0), "r"(c1) : "memory");
}
__device__ __forceinline__ void tma_prefetch_desc(const CUtensorMap* m) { asm volatile("prefetch.tensormap [%0];" :: "l"(m) : "memory"); }
__device__ __forceinline__ void l2_prefetch(const void* p, uint32_t bytes) { asm volatile("cp.async.bulk.prefetch.L2.global [%0], %1;" :: "l"(p), "r"(bytes) : "memory"); }
__device__ __forceinline__ void bulk_commit() { asm volatile("cp.async.bulk.commit_group;" ::: "memory"); }
__device__ __forceinline__ void bulk_wait_read() { asm volatile("cp.async.bulk.wait_group.read 0;" ::: "memory"); }
__device__ __forceinline__ void bulk_wait_all() { asm volatile("cp.async.bulk.wait_group 0;" ::: "memory"); }
__device__ __forceinline__ void fence_async_smem() { asm volatile("fence.proxy.async.shared::cta;" ::: "memory"); }
__device__ __forceinline__ void fence_async_global() { asm volatile("fence.proxy.async.global;" ::: "memory"); }
__device__ __forceinline__ void fence_acquire_gpu() { asm volatile("fence.acquire.gpu;" ::: "memory"); }
__device__ __forceinline__ void fence_release_gpu() { asm volatile("fence.release.gpu;" ::: "memory"); }
__device__ __forceinline__ void st_async_f32x4(uint32_t cluster_addr, const float* v, uint32_t cluster_bar) {
  asm volatile("st.async.weak.shared::cluster.mbarrier::complete_tx::bytes.v4.f32 [%0], {%1,%2,%3,%4}, [%5];"
    :: "r"(cluster_addr), "f"(v[0]), "f"(v[1]), "f"(v[2]), "f"(v[3]), "r"(cluster_bar) : "memory");
}
__device__ __forceinline__ void nb_sync(int id, int n) { asm volatile("bar.sync %0, %1;" :: "r"(id), "r"(n) : "memory"); }
__device__ __forceinline__ void nb_arrive(int id, int n) { asm volatile("bar.arrive %0, %1;" :: "r"(id), "r"(n) : "memory"); }
__device__ __forceinline__ void wg_fence() { asm volatile("wgmma.fence.sync.aligned;" ::: "memory"); }
__device__ __forceinline__ void wg_commit() { asm volatile("wgmma.commit_group.sync.aligned;" ::: "memory"); }
template <int N> __device__ __forceinline__ void wg_wait() { asm volatile("wgmma.wait_group.sync.aligned %0;" :: "n"(N) : "memory"); }
template <int N> __device__ __forceinline__ void reg_fence(float* a) {
#pragma unroll
  for (int i = 0; i < N; i++) asm volatile("" : "+f"(a[i]) :: "memory");
}
template <int N> __device__ __forceinline__ void reg_fence(uint32_t* a) {
#pragma unroll
  for (int i = 0; i < N; i++) asm volatile("" : "+r"(a[i]) :: "memory");
}
__device__ __forceinline__ uint64_t mk_desc(uint32_t addr, uint32_t lbo) {
  return (uint64_t)((addr & 0x3FFFF) >> 4) | ((uint64_t)(lbo >> 4) << 16) | ((uint64_t)(1024 >> 4) << 32) | (1ull << 62);
}

__device__ __forceinline__ uint64_t policy_evict_first() { uint64_t pol; asm("createpolicy.fractional.L2::evict_first.b64 %0, 1.0;" : "=l"(pol)); return pol; }
__device__ __forceinline__ uint32_t ld_relaxed(const uint32_t* p) { uint32_t v; asm volatile("ld.relaxed.gpu.global.u32 %0, [%1];" : "=r"(v) : "l"(p) : "memory"); return v; }
__device__ __forceinline__ void st_relaxed(uint32_t* p, uint32_t v) { asm volatile("st.relaxed.gpu.global.u32 [%0], %1;" :: "l"(p), "r"(v) : "memory"); }
__device__ __forceinline__ void red_add_relaxed(uint32_t* p, uint32_t v) { asm volatile("red.relaxed.gpu.global.add.u32 [%0], %1;" :: "l"(p), "r"(v) : "memory"); }
__device__ __forceinline__ uint2 ld_pkt8(const uint2* p) {
  uint2 v; asm volatile("{\n.reg .b64 t;\nld.relaxed.gpu.global.b64 t, [%2];\nmov.b64 {%0,%1}, t;\n}" : "=r"(v.x), "=r"(v.y) : "l"(p) : "memory"); return v;
}
__device__ __forceinline__ void st_pkt8(uint2* p, uint32_t a, uint32_t b) {
  asm volatile("{\n.reg .b64 t;\nmov.b64 t, {%1,%2};\nst.relaxed.gpu.global.b64 [%0], t;\n}" :: "l"(p), "r"(a), "r"(b) : "memory");
}
__device__ __forceinline__ uint4 ld_pkt16(const uint4* p) {
  uint4 v; asm volatile("{\n.reg .b128 t;\n.reg .b64 a, b;\nld.relaxed.gpu.global.b128 t, [%4];\nmov.b128 {a, b}, t;\nmov.b64 {%0,%1}, a;\nmov.b64 {%2,%3}, b;\n}"
    : "=r"(v.x), "=r"(v.y), "=r"(v.z), "=r"(v.w) : "l"(p) : "memory"); return v;
}
__device__ __forceinline__ void st_pkt16(uint4* p, uint32_t x, uint32_t y, uint32_t z, uint32_t w) {
  asm volatile("{\n.reg .b128 t;\n.reg .b64 a, b;\nmov.b64 a, {%1,%2};\nmov.b64 b, {%3,%4};\nmov.b128 t, {a, b};\nst.relaxed.gpu.global.b128 [%0], t;\n}"
    :: "l"(p), "r"(x), "r"(y), "r"(z), "r"(w) : "memory");
}
__device__ __forceinline__ void cp_async16(uint32_t dst, const void* src) { asm volatile("cp.async.cg.shared.global [%0], [%1], 16;" :: "r"(dst), "l"(src) : "memory"); }
__device__ __forceinline__ void cp_async_wait() { asm volatile("cp.async.wait_all;" ::: "memory"); }
__device__ __forceinline__ uint32_t lds32(uint32_t a) { uint32_t v; asm volatile("ld.shared.u32 %0, [%1];" : "=r"(v) : "r"(a) : "memory"); return v; }
__device__ __forceinline__ float lds_f32(uint32_t a) { float v; asm volatile("ld.shared.f32 %0, [%1];" : "=f"(v) : "r"(a) : "memory"); return v; }
__device__ __forceinline__ uint2 lds64(uint32_t a) { uint2 v; asm volatile("ld.shared.v2.u32 {%0,%1}, [%2];" : "=r"(v.x), "=r"(v.y) : "r"(a) : "memory"); return v; }
__device__ __forceinline__ uint4 lds128(uint32_t a) { uint4 v; asm volatile("ld.shared.v4.u32 {%0,%1,%2,%3}, [%4];" : "=r"(v.x), "=r"(v.y), "=r"(v.z), "=r"(v.w) : "r"(a) : "memory"); return v; }
__device__ __forceinline__ void sts32(uint32_t a, uint32_t v) { asm volatile("st.shared.u32 [%0], %1;" :: "r"(a), "r"(v) : "memory"); }
__device__ __forceinline__ void sts64(uint32_t a, uint32_t x, uint32_t y) { asm volatile("st.shared.v2.u32 [%0], {%1,%2};" :: "r"(a), "r"(x), "r"(y) : "memory"); }
__device__ __forceinline__ void sts128(uint32_t a, uint32_t x, uint32_t y, uint32_t z, uint32_t w) { asm volatile("st.shared.v4.u32 [%0], {%1,%2,%3,%4};" :: "r"(a), "r"(x), "r"(y), "r"(z), "r"(w) : "memory"); }
__device__ __forceinline__ void stsm4(uint32_t a, uint32_t x, uint32_t y, uint32_t z, uint32_t w) {
  asm volatile("stmatrix.sync.aligned.m8n8.x4.shared.b16 [%0], {%1,%2,%3,%4};" :: "r"(a), "r"(x), "r"(y), "r"(z), "r"(w) : "memory");
}
__device__ __forceinline__ void ldsm4(uint32_t a, uint32_t* r) {
  asm volatile("ldmatrix.sync.aligned.m8n8.x4.shared.b16 {%0,%1,%2,%3}, [%4];" : "=r"(r[0]), "=r"(r[1]), "=r"(r[2]), "=r"(r[3]) : "r"(a) : "memory");
}
__device__ __forceinline__ void ldsm4t(uint32_t a, uint32_t* r) {
  asm volatile("ldmatrix.sync.aligned.m8n8.x4.trans.shared.b16 {%0,%1,%2,%3}, [%4];" : "=r"(r[0]), "=r"(r[1]), "=r"(r[2]), "=r"(r[3]) : "r"(a) : "memory");
}
__device__ __forceinline__ void mma16816(float* d, const uint32_t* a, uint32_t b0, uint32_t b1) {
  asm volatile("mma.sync.aligned.m16n8k16.row.col.f32.bf16.bf16.f32 {%0,%1,%2,%3}, {%4,%5,%6,%7}, {%8,%9}, {%0,%1,%2,%3};"
    : "+f"(d[0]), "+f"(d[1]), "+f"(d[2]), "+f"(d[3]) : "r"(a[0]), "r"(a[1]), "r"(a[2]), "r"(a[3]), "r"(b0), "r"(b1));
}
__device__ __forceinline__ void mma1688(float* d, uint32_t a0, uint32_t a1, uint32_t b0) {
  asm volatile("mma.sync.aligned.m16n8k8.row.col.f32.bf16.bf16.f32 {%0,%1,%2,%3}, {%4,%5}, {%6}, {%0,%1,%2,%3};"
    : "+f"(d[0]), "+f"(d[1]), "+f"(d[2]), "+f"(d[3]) : "r"(a0), "r"(a1), "r"(b0));
}
__device__ __forceinline__ uint32_t pack2(float lo, float hi) { uint32_t r; asm("cvt.rn.bf16x2.f32 %0, %1, %2;" : "=r"(r) : "f"(hi), "f"(lo)); return r; }
__device__ __forceinline__ float lo2f(uint32_t v) { return __uint_as_float(v << 16); }
__device__ __forceinline__ float hi2f(uint32_t v) { return __uint_as_float(v & 0xffff0000u); }
__device__ __forceinline__ uint32_t hmul2(uint32_t a, uint32_t b) { uint32_t r; asm("mul.rn.bf16x2 %0, %1, %2;" : "=r"(r) : "r"(a), "r"(b)); return r; }
__device__ __forceinline__ uint32_t hadd2(uint32_t a, uint32_t b) { uint32_t r; asm("add.rn.bf16x2 %0, %1, %2;" : "=r"(r) : "r"(a), "r"(b)); return r; }
__device__ __forceinline__ uint32_t hsub2(uint32_t a, uint32_t b) { uint32_t r; asm("sub.rn.bf16x2 %0, %1, %2;" : "=r"(r) : "r"(a), "r"(b)); return r; }
__device__ __forceinline__ uint32_t hfma2(uint32_t a, uint32_t b, uint32_t c) { uint32_t r; asm("fma.rn.bf16x2 %0, %1, %2, %3;" : "=r"(r) : "r"(a), "r"(b), "r"(c)); return r; }
__device__ __forceinline__ float rbf(float v) { return lo2f(pack2(v, 0.f)); }
__device__ __forceinline__ float ex2(float v) { float r; asm("ex2.approx.ftz.f32 %0, %1;" : "=f"(r) : "f"(v)); return r; }
__device__ __forceinline__ float rcp_f(float v) { float r; asm("rcp.approx.ftz.f32 %0, %1;" : "=f"(r) : "f"(v)); return r; }
__device__ __forceinline__ float sqrt_f(float v) { float r; asm("sqrt.approx.ftz.f32 %0, %1;" : "=f"(r) : "f"(v)); return r; }
__device__ __forceinline__ float sigmoid_f(float v) { return rcp_f(1.f + ex2(-1.4426950408889634f * v)); }
__device__ __forceinline__ float silu_f(float v) { return v * sigmoid_f(v); }
constexpr uint32_t ONE2 = 0x3f803f80u;

#define R8(a,o) "+f"(a[o+0]), "+f"(a[o+1]), "+f"(a[o+2]), "+f"(a[o+3]), "+f"(a[o+4]), "+f"(a[o+5]), "+f"(a[o+6]), "+f"(a[o+7])
#define R64(a,o) R8(a,o), R8(a,o+8), R8(a,o+16), R8(a,o+24), R8(a,o+32), R8(a,o+40), R8(a,o+48), R8(a,o+56)
#define D64 "{%0,%1,%2,%3,%4,%5,%6,%7,%8,%9,%10,%11,%12,%13,%14,%15,%16,%17,%18,%19,%20,%21,%22,%23,%24,%25,%26,%27,%28,%29,%30,%31," \
            "%32,%33,%34,%35,%36,%37,%38,%39,%40,%41,%42,%43,%44,%45,%46,%47,%48,%49,%50,%51,%52,%53,%54,%55,%56,%57,%58,%59,%60,%61,%62,%63"
#define D128 D64 ",%64,%65,%66,%67,%68,%69,%70,%71,%72,%73,%74,%75,%76,%77,%78,%79,%80,%81,%82,%83,%84,%85,%86,%87,%88,%89,%90,%91,%92,%93,%94,%95," \
            "%96,%97,%98,%99,%100,%101,%102,%103,%104,%105,%106,%107,%108,%109,%110,%111,%112,%113,%114,%115,%116,%117,%118,%119,%120,%121,%122,%123,%124,%125,%126,%127"

template <int TB> __device__ __forceinline__ void wgmma_ss128(float* d, uint64_t da, uint64_t db, int acc) {
  asm volatile("{\n.reg .pred p;\nsetp.ne.b32 p, %66, 0;\nwgmma.mma_async.sync.aligned.m64n128k16.f32.bf16.bf16 " D64 "}, %64, %65, p, 1, 1, 0, %67;\n}"
    : R64(d, 0) : "l"(da), "l"(db), "r"(acc), "n"(TB));
}
template <int TB> __device__ __forceinline__ void wgmma_rs128(float* d, const uint32_t* a, uint64_t db, int acc) {
  asm volatile("{\n.reg .pred p;\nsetp.ne.b32 p, %69, 0;\nwgmma.mma_async.sync.aligned.m64n128k16.f32.bf16.bf16 " D64 "}, {%64,%65,%66,%67}, %68, p, 1, 1, %70;\n}"
    : R64(d, 0) : "r"(a[0]), "r"(a[1]), "r"(a[2]), "r"(a[3]), "l"(db), "r"(acc), "n"(TB));
}
template <int TB> __device__ __forceinline__ void wgmma_ss256(float* d, uint64_t da, uint64_t db, int acc) {
  asm volatile("{\n.reg .pred p;\nsetp.ne.b32 p, %130, 0;\nwgmma.mma_async.sync.aligned.m64n256k16.f32.bf16.bf16 " D128 "}, %128, %129, p, 1, 1, 0, %131;\n}"
    : R64(d, 0), R64(d, 64) : "l"(da), "l"(db), "r"(acc), "n"(TB));
}

#define W8(a,o) "=f"(a[o+0]), "=f"(a[o+1]), "=f"(a[o+2]), "=f"(a[o+3]), "=f"(a[o+4]), "=f"(a[o+5]), "=f"(a[o+6]), "=f"(a[o+7])
#define W64(a,o) W8(a,o), W8(a,o+8), W8(a,o+16), W8(a,o+24), W8(a,o+32), W8(a,o+40), W8(a,o+48), W8(a,o+56)
template <int TB> __device__ __forceinline__ void wgmma_ss128_z(float* d, uint64_t da, uint64_t db) {
  asm volatile("wgmma.mma_async.sync.aligned.m64n128k16.f32.bf16.bf16 " D64 "}, %64, %65, 0, 1, 1, 0, %66;"
    : W64(d, 0) : "l"(da), "l"(db), "n"(TB));
}
template <int TB> __device__ __forceinline__ void wgmma_rs128_z(float* d, const uint32_t* a, uint64_t db) {
  asm volatile("wgmma.mma_async.sync.aligned.m64n128k16.f32.bf16.bf16 " D64 "}, {%64,%65,%66,%67}, %68, 0, 1, 1, %69;"
    : W64(d, 0) : "r"(a[0]), "r"(a[1]), "r"(a[2]), "r"(a[3]), "l"(db), "n"(TB));
}
template <int TB> __device__ __forceinline__ void wgmma_ss256_z(float* d, uint64_t da, uint64_t db) {
  asm volatile("wgmma.mma_async.sync.aligned.m64n256k16.f32.bf16.bf16 " D128 "}, %128, %129, 0, 1, 1, 0, %130;"
    : W64(d, 0), W64(d, 64) : "l"(da), "l"(db), "n"(TB));
}

template <int TB> __device__ __forceinline__ void wgmma_rs256(float* d, const uint32_t* a, uint64_t db) {
  asm volatile("wgmma.mma_async.sync.aligned.m64n256k16.f32.bf16.bf16 " D128 "}, {%128,%129,%130,%131}, %132, 1, 1, 1, %133;"
    : R64(d, 0), R64(d, 64) : "r"(a[0]), "r"(a[1]), "r"(a[2]), "r"(a[3]), "l"(db), "n"(TB));
}
template <int TB> __device__ __forceinline__ void wgmma_rs256_z(float* d, const uint32_t* a, uint64_t db) {
  asm volatile("wgmma.mma_async.sync.aligned.m64n256k16.f32.bf16.bf16 " D128 "}, {%128,%129,%130,%131}, %132, 0, 1, 1, %133;"
    : W64(d, 0), W64(d, 64) : "r"(a[0]), "r"(a[1]), "r"(a[2]), "r"(a[3]), "l"(db), "n"(TB));
}
#define D32 "{%0,%1,%2,%3,%4,%5,%6,%7,%8,%9,%10,%11,%12,%13,%14,%15,%16,%17,%18,%19,%20,%21,%22,%23,%24,%25,%26,%27,%28,%29,%30,%31}"
__device__ __forceinline__ void wgmma_rs64(float* d, const uint32_t* a, uint64_t db) {
  asm volatile("wgmma.mma_async.sync.aligned.m64n64k16.f32.bf16.bf16 " D32 ", {%32,%33,%34,%35}, %36, 1, 1, 1, 0;"
    : R8(d, 0), R8(d, 8), R8(d, 16), R8(d, 24) : "r"(a[0]), "r"(a[1]), "r"(a[2]), "r"(a[3]), "l"(db));
}
__device__ __forceinline__ void wgmma_rs64_z(float* d, const uint32_t* a, uint64_t db) {
  asm volatile("wgmma.mma_async.sync.aligned.m64n64k16.f32.bf16.bf16 " D32 ", {%32,%33,%34,%35}, %36, 0, 1, 1, 0;"
    : W8(d, 0), W8(d, 8), W8(d, 16), W8(d, 24) : "r"(a[0]), "r"(a[1]), "r"(a[2]), "r"(a[3]), "l"(db));
}
__device__ __forceinline__ void issue_qk(float* S, const uint32_t* Q, uint64_t dk) {
  wgmma_rs64_z(S, Q, dk);
#pragma unroll
  for (int kk = 1; kk < 8; kk++) wgmma_rs64(S, Q + 4 * kk, dk + (kk >> 2) * 512 + (kk & 3) * 2);
}
__device__ __forceinline__ void issue_pv(float* O, const uint32_t* P, uint64_t dv, int acc) {
#pragma unroll
  for (int kk = 0; kk < 4; kk++) wgmma_rs128<1>(O, P + 4 * kk, dv + kk * 128, kk ? 1 : acc);
}

#define TS(i)
#define TSC(i)
#define TSX(i)
#define TSY(k) do { if ((tid & 127) == 0) TS((k) + 40 * wg); } while (0)
#define TT(k)
#define TV(k)
#define TR(k)
#define TQ(k)
#define TH(k)
#define TA(k)
#define TAFLUSH()

struct SoftmaxState { float c0, c1, l0, l1; bool shifted; };
constexpr float SM_SCALE = 0.08838834764831845f * 1.4426950408889634f;
__device__ __forceinline__ void softmax_start(SoftmaxState& z) { z.c0 = z.c1 = z.l0 = z.l1 = 0.f; z.shifted = false; }
__device__ __forceinline__ void softmax_half(float* S, uint32_t* P, float* O, SoftmaxState& z, bool first, uint32_t tag) {
  const float lo0 = z.l0, lo1 = z.l1;
  float lim = 1.2676506002282294e30f;
  const float low = first ? 8.673617379884035e-19f : 0.f;
  if (z.shifted) {
#pragma unroll
    for (int j = 0; j < 32; j++) S[j] += (j & 2) ? z.c1 : z.c0;
  }
#pragma unroll 1
  while (true) {
    bb_fence(tag);
#pragma unroll
    for (int j = 0; j < 8; j++) {
      const float p0 = ex2(S[4 * j]), p1 = ex2(S[4 * j + 1]), p2 = ex2(S[4 * j + 2]), p3 = ex2(S[4 * j + 3]);
      z.l0 += p0; z.l1 += p2; z.l0 += p1; z.l1 += p3;
      P[2 * j] = pack2(p0, p1); P[2 * j + 1] = pack2(p2, p3);
    }
    if (!__any_sync(0xffffffffu, !(z.l0 < lim && z.l1 < lim && fminf(z.l0, z.l1) >= low) && lim > 0.f)) break;
    float d0 = fmaxf(S[0], S[1]), d1 = fmaxf(S[2], S[3]);
#pragma unroll
    for (int j = 1; j < 8; j++) { d0 = fmaxf(d0, fmaxf(S[4 * j], S[4 * j + 1])); d1 = fmaxf(d1, fmaxf(S[4 * j + 2], S[4 * j + 3])); }
    d0 = fmaxf(d0, __shfl_xor_sync(0xffffffffu, d0, 1)); d1 = fmaxf(d1, __shfl_xor_sync(0xffffffffu, d1, 1));
    d0 = fmaxf(d0, __shfl_xor_sync(0xffffffffu, d0, 2)); d1 = fmaxf(d1, __shfl_xor_sync(0xffffffffu, d1, 2));
    if (!first) { d0 = fmaxf(d0, 0.f); d1 = fmaxf(d1, 0.f); }
    z.shifted = true;
    z.c0 -= d0; z.c1 -= d1;
#pragma unroll
    for (int j = 0; j < 32; j++) S[j] -= (j & 2) ? d1 : d0;
    const float a0 = first ? 1.f : ex2(-d0), a1 = first ? 1.f : ex2(-d1);
    z.l0 = lo0 * a0; z.l1 = lo1 * a1;
    lim = -1.f;
    wg_wait<0>();
    reg_fence<64>(O);
#pragma unroll
    for (int j = 0; j < 16; j++) { O[4 * j] *= a0; O[4 * j + 1] *= a0; O[4 * j + 2] *= a1; O[4 * j + 3] *= a1; }
  }
}

__device__ __forceinline__ void modulate_frags(uint32_t* A, const uint32_t* V, const uint4* R, const uint32_t* ln) {
#pragma unroll
  for (int kk = 0; kk < 4; kk++) {
    const uint4 sa = R[kk >> 1], c1 = R[2 + (kk >> 1)];
#pragma unroll
    for (int j = 0; j < 4; j++) {
      const uint32_t n = hfma2(V[4 * kk + j], ln[(j & 1) * 2 + 1], ln[(j & 1) * 2]);
      A[4 * kk + j] = (kk & 1) ? ((j & 2) ? hfma2(n, c1.w, sa.x) : hfma2(n, c1.z, sa.w)) : ((j & 2) ? hfma2(n, c1.y, sa.z) : hfma2(n, c1.x, sa.y));
    }
  }
}
__device__ __forceinline__ void publish_record(uint4* dst, uint32_t pk, int src, int vec, bool doit) {
  const int r = vec ? 0 : 12;
  const uint32_t x = __shfl_sync(0xffffffffu, pk, src + r), y = __shfl_sync(0xffffffffu, pk, src + ((r + 4) & 12));
  const uint32_t z = __shfl_sync(0xffffffffu, pk, src + ((r + 8) & 12)), w = __shfl_sync(0xffffffffu, pk, src + ((r + 12) & 12));
  if (doit) st_pkt16(dst, ~x, y, z, w);
}
__device__ __forceinline__ void put_record(uint32_t sb, int idx, const uint4& v) {
  sts128(sb + SM_STASH + idx * 16, ~v.x, v.y, v.z, v.w);
  sts128(sb + SM_STASH + 16384 + idx * 16, ~v.x, v.y, v.z, v.w);
}
__device__ __forceinline__ float mod_value(float v, int vec) {
  v = rbf(v);
  return (vec ? rbf(1.f + v) : v) * SM_SCALE;
}

__device__ __forceinline__ void row_rcp(float& l0, float& l1) {
  l0 += __shfl_xor_sync(0xffffffffu, l0, 1); l1 += __shfl_xor_sync(0xffffffffu, l1, 1);
  l0 += __shfl_xor_sync(0xffffffffu, l0, 2); l1 += __shfl_xor_sync(0xffffffffu, l1, 2);
  l0 = rcp_f(l0); l1 = rcp_f(l1);
}
__device__ __forceinline__ void stage_o(const float* O, float r0, float r1, uint32_t stsm_addr) {
#pragma unroll
  for (int kk = 0; kk < 8; kk++) {
    stsm4((stsm_addr + (kk >> 2) * 8192) ^ ((kk & 3) * 32),
          pack2(O[8 * kk + 0] * r0, O[8 * kk + 1] * r0), pack2(O[8 * kk + 2] * r1, O[8 * kk + 3] * r1),
          pack2(O[8 * kk + 4] * r0, O[8 * kk + 5] * r0), pack2(O[8 * kk + 6] * r1, O[8 * kk + 7] * r1));
  }
}

__global__ void __cluster_dims__(2, 1, 1) __launch_bounds__(NTHREADS, 1)
fused_kernel(const Params p, const __grid_constant__ CUtensorMap mH, const __grid_constant__ CUtensorMap mWq,
             const __grid_constant__ CUtensorMap mK, const __grid_constant__ CUtensorMap mV,
             const __grid_constant__ CUtensorMap mO, const __grid_constant__ CUtensorMap mWo,
             const __grid_constant__ CUtensorMap mX, const __grid_constant__ CUtensorMap mOut,
             const __grid_constant__ CUtensorMap mWg, const __grid_constant__ CUtensorMap mWu,
             const __grid_constant__ CUtensorMap mWd, const __grid_constant__ CUtensorMap mWm,
             const __grid_constant__ CUtensorMap mWs, const __grid_constant__ CUtensorMap mWh,
             const __grid_constant__ CUtensorMap mOs) {
  extern __shared__ __align__(1024) uint8_t smem_raw[];
  TH(0);
  const uint32_t sb = smem_u32(smem_raw);
  const int tid = threadIdx.x;
  const int b0 = blockIdx.x;
  const int lane = tid & 31;
  const int role = __shfl_sync(0xffffffffu, tid >> 8, 0);

  if (b0 >= NMAIN) {
    const uint32_t cs = clock();
    const uint32_t tag = ld_relaxed(&g_epoch) + 1;
    const int sp = b0 - NMAIN, vec = 2 + sp;
    const int warp = __shfl_sync(0xffffffffu, tid >> 5, 0);
    float* sc = reinterpret_cast<float*>(smem_raw + SM_STASH);
    float* red = reinterpret_cast<float*>(smem_raw + SM_STASH + 4096);
    const int ridx = (lane >> 3) * 2 * RV + (sp & 1) * RV + 16 * RS + (sp >> 1) * 16 + (warp & 1) * 8 + (lane & 7);
    if (warp < 8) st_pkt16(&g_rec[warp >> 2][0][ridx + (warp & 2) * 16], 0, 0, 0, 0);
#pragma unroll 1
    for (int i = tid; i < 1024; i += NTHREADS) sc[i] = rbf(silu_f(__bfloat162float(p.c[i])));
    if (tid == 0) {
      tma_prefetch_desc(&mWs);
      for (int s = 0; s < NST2; s++) { mbar_init(sb + BAR_FULL2 + 8 * s, 1); mbar_init(sb + BAR_EMPTY2 + 8 * s, 8); }
      fence_async_smem();
      while ((uint32_t)clock() - cs < SPT) {}
    }
    __syncthreads();
    int s = 0; uint32_t ph = 0;
    if (tid == 0) TS(0);
    if (warp == 8) {
      const uint64_t pol = policy_evict_first();
#pragma unroll 1
      for (int n = 0; n < 80; n++) {
        mbar_wait_g(sb + BAR_EMPTY2 + 8 * s, ph ^ 1);
        if (elect_one()) {
          mbar_expect_tx(sb + BAR_FULL2 + 8 * s, 32768);
          if (n < 16) {
            tma_ld_hint(sb + s * ST2, &mWs, (sp & 1) * 1024 + 512 + (n >> 3) * 256 + (sp >> 1) * 128, (n & 7) * 128, sb + BAR_FULL2 + 8 * s, pol);
          } else {
#pragma unroll
            for (int j = 0; j < 4; j++) tma_ld_hint(sb + s * ST2 + j * 8192, &mWm, vec * 1024 + j * 256, (n - 16) * 16, sb + BAR_FULL2 + 8 * s, pol);
          }
        }
        __syncwarp();
        if (++s == NST2) { s = 0; ph ^= 1; }
      }
    } else if (warp < 8) {
      float acc[8];
#pragma unroll
      for (int i = 0; i < 8; i++) acc[i] = 0.f;
      auto stage = [&](uint32_t a0, int da, const float* cp, int dc) {
        mbar_wait_g(sb + BAR_FULL2 + 8 * s, ph);
#pragma unroll
        for (int i = 0; i < 8; i++) {
          const uint4 v = lds128(a0 + s * ST2 + i * da);
          const float c = cp[i * dc];
          acc[0] = fmaf(lo2f(v.x), c, acc[0]); acc[1] = fmaf(hi2f(v.x), c, acc[1]);
          acc[2] = fmaf(lo2f(v.y), c, acc[2]); acc[3] = fmaf(hi2f(v.y), c, acc[3]);
          acc[4] = fmaf(lo2f(v.z), c, acc[4]); acc[5] = fmaf(hi2f(v.z), c, acc[5]);
          acc[6] = fmaf(lo2f(v.w), c, acc[6]); acc[7] = fmaf(hi2f(v.w), c, acc[7]);
        }
        if (__shfl_sync(0xffffffffu, lane, __float_as_uint(acc[7]) & 31) < 32 && lane == 0) mbar_arrive(sb + BAR_EMPTY2 + 8 * s);
        if (++s == NST2) { s = 0; ph ^= 1; }
      };
#pragma unroll 1
      for (int n = 0; n < 16; n++) {
        stage(sb + tid * 16, 4096, sc + (n & 7) * 128 + (tid >> 4), 16);
        if ((n & 7) == 7) {
          float* r2 = red + 2048 + (n & 8) * 256;
#pragma unroll
          for (int i = 0; i < 8; i++) { r2[tid * 8 + i] = acc[i]; acc[i] = 0.f; }
          nb_sync(NB_CONS, 256);
          if (warp < 2) {
            float v0 = 0.f, v1 = 0.f;
#pragma unroll 4
            for (int i = 0; i < 16; i++) { const float2 e = reinterpret_cast<const float2*>(r2)[i * 64 + tid]; v0 += e.x; v1 += e.y; }
            publish_record(&g_rec[tag & 1][0][ridx + (n >> 3) * 32], pack2(mod_value(v0, sp & 1), mod_value(v1, sp & 1)),
                           (lane & 4) * 4 + (lane & 3), sp & 1, true);
          }
          if (tid == 0) TS(1 + (n >> 3));
        }
      }
#pragma unroll 1
      for (int n = 0; n < 64; n++) {
        stage(sb + ((tid >> 5) & 3) * 8192 + (tid >> 7) * 4096 + (tid & 31) * 16, 512, sc + n * 16 + (tid >> 7) * 8, 1);
      }
#pragma unroll
      for (int i = 0; i < 8; i++) red[(tid >> 7) * 1024 + (tid & 127) * 8 + i] = acc[i];
    }
    __syncthreads();
    float dot = 0.f;
#pragma unroll 1
    for (int i = tid; i < 512; i += NTHREADS) {
      uint32_t v = pack2(red[2 * i] + red[1024 + 2 * i], red[2 * i + 1] + red[1024 + 2 * i + 1]);
      st_pkt8(&g_mod[vec * 512 + i], v, tag);
      if (vec == 4) v = hadd2(v, ONE2);
      const uint32_t wr = reinterpret_cast<const uint32_t*>(p.w_r)[i];
      dot = fmaf(lo2f(v), lo2f(wr), fmaf(hi2f(v), hi2f(wr), dot));
    }
#pragma unroll
    for (int o = 16; o; o >>= 1) dot += __shfl_xor_sync(0xffffffffu, dot, o);
    if (lane == 0) sc[warp] = dot;
    __syncthreads();
    if (tid == 0) {
      dot = 0.f;
      for (int w = 0; w < 12; w++) dot += sc[w];
      fence_release_gpu();
      st_pkt8(&g_vdone[(vec - 2) * 16], __float_as_uint(dot), tag);
      TS(11);
#pragma unroll 1
      for (int i = 0; i < 128; i++) {
        const int u = i * 4 + (b0 - NMAIN);
        l2_prefetch(p.wo + (size_t)((4 * ((u >> 4) & 7) + (u >> 7)) * 128 + (u & 15) * 8) * 1024, 16384);
        __nanosleep(PFW);
      }
    }
    return;
  }

  const uint32_t rank = b0 & 1;
  const bool slab = !(b0 & 32), late = b0 & 16;
  const uint32_t c0 = clock();
  if (tid == 352) TS(0);
  const uint32_t slab_addr = sb + SM_WSLAB + (tid >> 5) * 4096 + (lane & 3) * 128 + (lane & 4) * 16 + (((lane >> 3) ^ lane) & 3) * 16;
  auto load_slab = [&]() {
    const bf16* wp = p.w_mod + (size_t)(512 * rank + 2 * (tid & ~31) + 2 * (lane & 3) + ((lane >> 2) & 1)) * 6144 + 32 * (b0 >> 1) + 8 * (lane >> 3);
    const uint64_t pef = policy_evict_first();
#pragma unroll
    for (int i = 0; i < 8; i++)
      asm volatile("cp.async.cg.shared.global.L2::cache_hint [%0], [%1], 16, %2;"
        :: "r"(slab_addr + i * 512), "l"(wp + (size_t)i * 8 * 6144), "l"(pef) : "memory");
  };
  if (tid == 256) {
    mbar_init(sb + BAR_XH, 1);
    fence_async_smem();
    mbar_expect_tx(sb + BAR_XH, 32768);
#pragma unroll
    for (int i = 0; i < 2; i++)
      asm volatile("cp.async.bulk.shared::cluster.global.mbarrier::complete_tx::bytes [%0], [%1], 16384, [%2];"
        :: "r"(sb + SM_XROW + i * ST1), "l"(p.x + (size_t)b0 * 16384 + i * 8192), "r"(sb + BAR_XH) : "memory");
  }
  __syncwarp();
  uint32_t cw[8];
#pragma unroll
  for (int i = 0; i < 8; i++) cw[i] = 0;
  if (!role && slab) {
#pragma unroll
    for (int i = 0; i < 8; i++) cw[i] = ld_relaxed(reinterpret_cast<const uint32_t*>(p.c) + 256 * rank + (tid & ~28) + 4 * i);
  }
  uint32_t epoch = 0;
  if (!role) epoch = ld_relaxed(&p.sc->epoch[lane]);
  if (!role && slab && !late) load_slab();
#define TILE_ROLES() \
  mbar_wait(sb + BAR_ROLE, 0); \
  const int b = 2 * __shfl_sync(0xffffffffu, lds32(sb + SM_ROLE), 0) + rank; \
  const int rt = b >> 3;     \
  const int ct = b & 7;

  if (role) {
    asm volatile("setmaxnreg.dec.sync.aligned.u32 24;");
    const int warp = __shfl_sync(0xffffffffu, tid >> 5, 0);
    if (tid == 256) {
      mbar_init(sb + BAR_RED, 1); mbar_init(sb + BAR_WH, 1);
      for (int s = 0; s < 2; s++) mbar_init(sb + BAR_OF + 8 * s, 1);
      mbar_init(sb + BAR_ROLE, 1);
      for (int s = 0; s < 5; s++) { mbar_init(sb + BAR_FULL1 + 8 * s, 1); mbar_init(sb + BAR_EMPTY1 + 8 * s, 4); }
      for (int s = 0; s < 2; s++) { mbar_init(sb + BAR_STASH + 8 * s, 1); mbar_init(sb + BAR_X + 8 * s, 1); }
      for (int s = 0; s < 4; s++) mbar_init(sb + BAR_HS + 8 * s, 1);
      mbar_init(sb + BAR_G, 16); mbar_init(sb + BAR_T1, 1); mbar_init(sb + BAR_HF, 1);
      mbar_init(sb + BAR_SFREE, 4); mbar_init(sb + BAR_TFREE, 8);
      mbar_init(sb + BAR_FFN, 4); mbar_init(sb + BAR_FFN + 8, 2);
      mbar_init(sb + BAR_CAND, 1); mbar_init(sb + BAR_VEC, 32); for (int s = 0; s < 3; s++) mbar_init(sb + BAR_TAB + 8 * s, 32);
      mbar_expect_tx(sb + BAR_RED, 1024);
      mbar_expect_tx(sb + BAR_ROLE, 4);
      asm volatile("fence.mbarrier_init.release.cluster;" ::: "memory");
    }
    __syncwarp();
    asm volatile("barrier.cluster.arrive.relaxed.aligned;" ::: "memory");
    const int ridx = ((lane >> 1) & 3) * 2 * RV + (b0 >> 6) * RV + ((b0 >> 1) & 31) * RS + 2 * rank + (lane & 1) + (lane >> 3) * 4;
    if (warp == 11 && slab && lane < 2 * RS) { st_pkt16(&g_rec[0][0][ridx], 0, 0, 0, 0); st_pkt16(&g_rec[1][0][ridx], 0, 0, 0, 0); }
    if (tid == 256) {
      tma_prefetch_desc(&mWq); tma_prefetch_desc(&mX); tma_prefetch_desc(&mH); tma_prefetch_desc(&mK); tma_prefetch_desc(&mV); tma_prefetch_desc(&mOs);
    }
    uint32_t pairid = 0;
    if (tid == 320 && rank == 0) {
      uint32_t t;
      asm("mov.u32 %0, %%smid;" : "=r"(t));
      t >>= 1;
      uint32_t grp = ((0x73216540u >> (4 * ((t < 32 ? t : t < 60 ? 1 + (t - 32) % 7 : t < 62 ? t - 54 : 0) & 7))) & 7) - 1, slot;
      int it = 0;
      do {
        grp = (grp + 1) & 7;
        asm volatile("atom.relaxed.gpu.global.add.u32 %0, [%1], 1;" : "=r"(slot) : "l"(&p.sc->ticket[grp * 32]) : "memory");
        spin_guard(it);
      } while (slot >= 8);
      pairid = slot * 8 + grp;
    }
    __syncwarp();
    asm volatile("barrier.cluster.wait.aligned;" ::: "memory");
    if (tid == 320 && rank == 0) {
#pragma unroll
      for (int r = 0; r < 2; r++)
        asm volatile("st.async.weak.shared::cluster.mbarrier::complete_tx::bytes.b32 [%0], %1, [%2];"
          :: "r"(mapa(sb + SM_ROLE, r)), "r"(pairid), "r"(mapa(sb + BAR_ROLE, r)) : "memory");
    }
    __syncwarp();
    const uint32_t tag = ld_relaxed(&g_epoch) + 1;
    if (warp == 8) {
      TILE_ROLES();
      const int kvrow = (ct >> 1) * 2048 + 1536, arow = rt * 128 + rank * 64;
      const uint64_t pef = policy_evict_first();
#pragma unroll 1
      for (int pair = 0; pair < 2; pair++) {
        const int wblk = (4 * ct + 2 * pair) * 2;
        if (pair) { mbar_wait_g(sb + BAR_HF, 0); fence_async_global(); }
#pragma unroll 1
        for (int n = 0; n < 16; n++) {
          const uint32_t s = n & 3, st = sb + SM_RING + s * ST1, fb = sb + BAR_FULL1 + 8 * s;
          if (n == 2 && pair == 0) mbar_wait_g(sb + BAR_G, 0);
          mbar_wait_g(fb + (BAR_EMPTY1 - BAR_FULL1), ((n >> 2) & 1) ^ 1);
          if (elect_one()) {
            mbar_expect_tx(fb, 49152);
            if (pair) tma_ld_mc_hint(st + rank * 8192, &mH, n * 64, arow, fb, pef); else
            tma_ld_mc(st + rank * 8192, pair ? &mH : &mX, n * 64, arow, fb);
            tma_ld3_hint(st + 16384, &mWq, n * 64, wblk, fb, pef);
          }
          __syncwarp();
        }
#pragma unroll 1
        for (int n = 0; n < 16; n++) {
          const uint32_t s = n & 3, st = sb + SM_RING + s * ST1 + rank * 8192, fb = sb + BAR_FULL1 + 8 * s;
          const int h0 = n == 0 ? 0 : n == 15 ? 14 : n + 1, h1 = n == 0 ? 1 : n == 15 ? 15 : n - 1;
          mbar_wait_g(fb + (BAR_EMPTY1 - BAR_FULL1), ((n >> 2) & 1) ^ 1);
          if (elect_one()) {
            mbar_expect_tx(fb, 32768);
            tma_ld_mc(st, n == 15 ? &mV : &mK, rank * 64, kvrow + (h0 & 7) * 64, fb);
            tma_ld_mc(st + 16384, n == 0 ? &mK : &mV, rank * 64, kvrow + (h1 & 7) * 64, fb);
            if (n == 3 && pair == 1) mbar_arrive(sb + BAR_T1);
          }
          __syncwarp();
        }
      }
      {
        uint32_t s = 0, ph = 1;
#pragma unroll 1
        for (int half = 0; half < 2; half++) {
          mbar_wait_g(sb + BAR_OF + 8 * half, 0);
          fence_async_global();
#pragma unroll 1
          for (int n = 32 * half; n < 32 * half + 32; n++) {
            const uint32_t st = sb + SM_RING + s * ST1, fb = sb + BAR_FULL1 + 8 * s;
            const int k0 = ((n & 14) * 2 + (n >> 4)) * 128 + (n & 1) * 64;
            mbar_wait_g(n == 8 ? sb + BAR_SFREE : fb + (BAR_EMPTY1 - BAR_FULL1), n == 8 ? 0 : ph ^ (s >> 2));
            if (elect_one()) {
              mbar_expect_tx(fb, 32768);
              tma_ld_mc_hint(st + rank * 8192, &mO, k0, arow, fb, pef);
              tma_ld3_hint(st + 16384, &mWo, k0, 2 * ct, fb, pef);
            }
            __syncwarp();
            if (++s == 5 || n == 3) { s = 0; ph ^= 1; }
          }
        }
        if (b < NFFN) {
#pragma unroll 1
          for (s = 0; s < 2; s++) {
            mbar_wait_g(sb + BAR_EMPTY1 + 8 * s, 0);
            if (elect_one()) {
              mbar_expect_tx(sb + BAR_FFN + 8, 32768);
              tma_ld3_hint(sb + SM_RING + s * ST1, &mWd, b * 32, s * 8, sb + BAR_FFN + 8, pef);
            }
            __syncwarp();
          }
        }
      }
    } else if (warp <= 10) {
      const int w = warp - 9;
      if (slab && late && w == 0 && lane == 0) {
        tma_prefetch_desc(&mWh);
        mbar_expect_tx(sb + BAR_WH, 32768);
        while ((uint32_t)clock() - c0 < WL) {}
        const uint64_t pef = policy_evict_first();
#pragma unroll
        for (int i = 0; i < 2; i++) tma_ld_hint(sb + SM_WSLAB + i * 16384, &mWh, 32 * (b0 >> 1), 512 * rank + 256 * i, sb + BAR_WH, pef);
      }
      __syncwarp();
      TILE_ROLES();
      const uint32_t st = sb + SM_STASH + w * 16384;
#pragma unroll 1
      for (int j = 0; j < 2; j++) {
        nb_sync(NB_OST + w, 160);
        if (elect_one()) {
          fence_async_smem();
          tma_st(&mH, (2 * ct + j) * 64, rt * 128 + w * 64, st + 4096);
          bulk_commit();
          bulk_wait_read();
          mbar_arrive(sb + BAR_HS + 16 * w + 8 * j);
          if (j) {
            bulk_wait_all();
            fence_async_global();
            fence_release_gpu();
            red_add_relaxed(&g_hflag[rt * 32], 1);
          }
        }
        __syncwarp();
      }
#pragma unroll 1
      for (int r = 0; r < 4; r++) {
        nb_sync(NB_OST + w, 160);
        if (elect_one()) {
          fence_async_smem();
          const int hcol = (4 * ct + r) * 128;
#pragma unroll 1
          for (int i = 0; i < 8; i++) {
            tma_st(&mOs, hcol + (i & 4) * 16, rt * 128 + w * 64 + (i & 3) * 16, st + i * 2048);
            __nanosleep(r == 3 ? OP3 : OP0);
          }
          bulk_commit();
          bulk_wait_read();
          if (r < 2) {
            mbar_arrive(sb + BAR_STASH + 8 * w);
          } else if (r == 2) {
            mbar_expect_tx(sb + BAR_X + 8 * w, 16384);
            tma_ld_hint(st, &mX, ct * 128, rt * 128 + w * 64, sb + BAR_X + 8 * w, policy_evict_first());
            tma_ld_hint(st + 8192, &mX, ct * 128 + 64, rt * 128 + w * 64, sb + BAR_X + 8 * w, policy_evict_first());
          } else {
            mbar_arrive_cl(mapa(sb + BAR_SFREE, 0)); mbar_arrive_cl(mapa(sb + BAR_SFREE, 1));
          }
          bulk_wait_all();
          fence_async_global();
          fence_release_gpu();
          red_add_relaxed(&g_oflag[(rt * 4 + r) * 32], 1);
        }
        __syncwarp();
      }
      nb_sync(NB_OST + w, 160);
      int skip = -1;
      mbar_wait_g(sb + BAR_CAND, 0);
      const bool has_cand = (lds32(sb + SM_CAND) >> 6) == w;
      if (has_cand) {
        nb_sync(NB_WIN + w, 160);
        skip = (int)lds32(sb + SM_WROW + 4 * w) - (rt * 128 + w * 64);
      }
      if ((unsigned)skip >= 64u) {
        if (elect_one()) {
          fence_async_smem();
          tma_st(&mOut, ct * 128, rt * 128 + w * 64, sb + SM_OUT + w * 16384);
          tma_st(&mOut, ct * 128 + 64, rt * 128 + w * 64, sb + SM_OUT + w * 16384 + 8192);
          bulk_commit();
          bulk_wait_read();
        }
        __syncwarp();
      } else {
        uint4* dst = reinterpret_cast<uint4*>(p.out + (size_t)(rt * 128 + w * 64 + (lane >> 4)) * 1024 + ct * 128) + (lane & 15);
#pragma unroll 2
        for (int r = lane >> 4; r < 64; r += 2) {
          const uint4 v = lds128(sb + SM_OUT + w * 16384 + ((lane >> 3) & 1) * 8192 + r * 128 + (((lane ^ r) & 7) * 16));
          if (r != skip) *dst = v;
          dst += 256;
        }
      }
      if (!has_cand) nb_sync(NB_WIN + w, 160);
    } else {
      if (slab) {
        mbar_wait_g(sb + BAR_RED, 0);
        float v = 0.f;
#pragma unroll
        for (int w = 0; w < 8; w++) v += lds_f32(sb + SM_RED + w * 128 + lane * 4);
        v += __shfl_xor_sync(0xffffffffu, v, 16);
        v = mod_value(v, b0 >> 6);
        publish_record(&g_rec[tag & 1][0][ridx], pack2(v, __shfl_down_sync(0xffffffffu, v, 1)), 2 * (lane & 1), b0 >> 6, lane < 8);
        if (lane == 0) TS(1);
      }
      mbar_wait_g(sb + BAR_G, 0);
#pragma unroll 1
      for (int i = 1; i < 4; i++) {
        const uint4* mp = &g_rec[tag & 1][(b0 >> 1) & (NREP - 1)][i == 1 ? (8 + (lane >> 2)) * RS + (lane & 3) : 16 * RS - 64 + 32 * i + lane];
        uint4 v0, v1; int it = 0;
        while (true) {
          v0 = ld_pkt16(mp); v1 = ld_pkt16(mp + RV);
          if (v0.x != 0 && v1.x != 0) break;
          spin_guard(it); __nanosleep(PLD);
        }
        put_record(sb, 32 * i + lane, v0);
        put_record(sb, 128 + 32 * i + lane, v1);
        mbar_arrive(sb + BAR_TAB - 8 + 8 * i);
        if (lane == 0) {
          TS(3 + i + (i > 2));
          if (i == 1) l2_prefetch(((b0 & 64) ? p.vc : p.kc) + (size_t)(((b0 >> 4) & 3) * 2048 + 1536) * 128 + (b0 & 15) * 4096, 8192);
        }
        __syncwarp();
      }
      TILE_ROLES();
      if (lane == 0) {
        int it = 0;
        do { __nanosleep(500); spin_guard(it); } while (ld_relaxed(&g_hflag[rt * 32]) != tag * 16u);
        fence_acquire_gpu();
        mbar_arrive(sb + BAR_HF);
        if (b < NFFN) for (int i = 0; i < 8; i++) { __nanosleep(800); l2_prefetch(p.wd + (size_t)(b * 32 + i * 4) * 1024, 8192); }
      }
      __syncwarp();
      {
        uint2 v; int it = 0;
        do { __nanosleep(1000); v = ld_pkt8(&g_vdone[(lane & 3) * 16]); spin_guard(it); }
        while (!(v.y == tag));
        __syncwarp();
        fence_acquire_gpu();
        if (lane == 1 || lane == 2) sts32(sb + SM_SCAL + (2 - lane) * 4, v.x);
      }
#pragma unroll 1
      for (int i = 0; i < 2; i++) {
        const int q = i * 32 + lane, pi = ct * 64 + q;
        const uint32_t vga = g_mod[2 * 512 + pi].x, vsb = g_mod[3 * 512 + pi].x, vcb = g_mod[4 * 512 + pi].x, vgb = g_mod[5 * 512 + pi].x;
        const uint32_t wr = reinterpret_cast<const uint32_t*>(p.w_r)[pi];
        const uint32_t c1 = hadd2(vcb, ONE2);
        const float al = lo2f(c1) * lo2f(wr), ah = hi2f(c1) * hi2f(wr);
        const uint32_t o8 = (q & 3) * 8 + ((q >> 2) & 1) * 4;
        sts32(sb + SM_GA + (q >> 3) * 32 + o8, vga);
        sts128(sb + SM_REC + q * 16, c1, vsb, vgb, 0);
        const uint32_t ahi = pack2(al, ah), alo = pack2(al - lo2f(ahi), ah - hi2f(ahi));
        const uint32_t ba = sb + SM_B1 + (q >> 3) * 128 + o8;
        sts32(ba, ONE2); sts32(ba + 32, ahi); sts32(ba + 64, alo); sts32(ba + 96, 0);
      }
      if (lane == 0) TS(28);
      if (lane == 0) {
        tma_prefetch_desc(&mWo); tma_prefetch_desc(&mO); tma_prefetch_desc(&mOut); tma_prefetch_desc(&mWd); tma_prefetch_desc(&mWg); tma_prefetch_desc(&mWu);
#pragma unroll 1
        for (int r = 0; r < 4; r++) {
          int it = 0;
          do { __nanosleep(200); spin_guard(it); } while (ld_relaxed(&g_oflag[(rt * 4 + r) * 32]) != tag * 16u);
          if (r & 1) { fence_acquire_gpu(); mbar_arrive(sb + BAR_OF + 8 * (r >> 1)); }
          if (r == 1 && b < NFFN) {
            const uint64_t pef = policy_evict_first();
            mbar_wait_g(sb + BAR_T1, 0);
#pragma unroll 1
            for (int i = 0; i < 4; i++) {
              mbar_expect_tx(sb + BAR_FFN, 16384);
              tma_ld_hint(sb + SM_RING + i * ST1 + 32768, &mWg, b * 32, i * 256, sb + BAR_FFN, pef);
              __nanosleep(GATED);
            }
          }
        }
      }
      __syncwarp();
      if (b < NFFN) {
        mbar_wait_g(sb + BAR_TFREE, 0);
        const uint64_t pef = policy_evict_first();
#pragma unroll 1
        for (int i = 0; i < 5; i++) {
          if (i > 0 && lane == 0) {
            mbar_expect_tx(sb + BAR_FFN, 16384);
            tma_ld_hint(sb + SM_RING + (i - 1) * ST1 + 32768, &mWu, b * 32, (i - 1) * 256, sb + BAR_FFN, pef);
          }
          if (i < 4) {
#pragma unroll 1
            for (int j = 0; j < 8; j++) {
              asm volatile("prefetch.global.L2 [%0];" :: "l"(p.wu + (size_t)(i * 256 + j * 32 + lane) * 3584 + b * 32) : "memory");
              __nanosleep(UPD);
            }
            __nanosleep(500);
          }
        }
      }
      if (lane == 0) TS(29);
#pragma unroll 1
      for (int i = lane; i < 128; i += 32) st_pkt16(&g_stats[b * 128 + i], 0, 0, 0, 0);
      st_pkt16(&g_cand[b * 32 + lane], 0, 0, 0, 0);
      if (lane < 8) st_pkt16(&g_entry[(ct * 16 + rt) * 8 + lane], 0, 0, 0, 0);
#pragma unroll 1
      for (int i = lane; i < (b < NFFN ? 512 : 0); i += 32) st_pkt16(&g_ypart[((i >> 2) * NFFN + b) * 4 + (i & 3)], 0, 0, 0, 0);
      mbar_arrive(sb + BAR_VEC);
      uint4* const cp = &g_cand[b * 32 + lane];
      uint4* const ep = &g_entry[(ct * 16 + rt) * 8];
      nb_sync(NB_AMAX, 288);
      TV(0);
      const uint2 e = lds64(sb + SM_AMAX + (lane & 7) * 8);
      const int tmax = __reduce_max_sync(0xffffffffu, (int)e.x);
      const uint32_t row = ~tmax & 127;
      const int wl = row >> 4;
      const uint32_t xa = sb + SM_X2 + (row >> 6) * 16384 + (lane >> 4) * 8192 + (row & 63) * 128 + (lane & 3) * 4
                        + ((((lane >> 1) & 6) ^ (row & 7)) * 16);
      const uint32_t v0 = lds32(xa), v1 = lds32(xa ^ 16);
      if (lane == wl) st_pkt16(ep, (tmax | 127) - rt, rt * 128 + row, e.y, tag);
      st_pkt16(cp, v0, v1, tag, 0);
      if (lane == 0) { sts32(sb + SM_CAND, row); mbar_arrive(sb + BAR_CAND); }
      TV(1);
      if (lane == 0) TS(15);
    }
  } else {
    const int warp = tid >> 5;
    const int wg = warp >> 2, wq = warp & 3;
    const int g = lane >> 2, t = lane & 3;
    uint32_t tag;
    uint32_t ln[4];
    float acc[128];
    uint32_t bf[16];
    auto gemv = [&]() {
          if (late) mbar_wait(sb + BAR_WH, 0); else
          asm volatile("cp.async.wait_all;" ::: "memory");
          float d0[4] = {0.f, 0.f, 0.f, 0.f}, d1[4] = {0.f, 0.f, 0.f, 0.f};
#pragma unroll
          for (int i = 0; i < 8; i++) {
            const uint4 wv = lds128(slab_addr + i * 512);
            const uint32_t a[4] = {wv.x, wv.y, wv.z, wv.w};
            mma16816((i & 1) ? d1 : d0, a, bf[2 * i], bf[2 * i + 1]);
          }
#pragma unroll
          for (int i = 0; i < 4; i++) { d0[i] += d1[i]; d0[i] += __shfl_xor_sync(0xffffffffu, d0[i], 6); }
          const uint32_t dst = mapa(sb + SM_MISC, t & 1) - SM_MISC;
          if (!(lane & 6)) st_async_f32x4(dst + SM_RED + warp * 128 + rank * 64 + g * 8, d0, dst + BAR_RED);
          TH(4);
    };
    {
      asm volatile("barrier.cluster.arrive.relaxed.aligned;" ::: "memory");
      if (lane == 0) st_pkt16(&g_lnst[8 * b0 + warp], 0, 0, 0, 0);
      TH(1);
      asm volatile("setmaxnreg.inc.sync.aligned.u32 240;");
      TH(2);
#pragma unroll
      for (int i = 0; i < 8; i++) {
        const float sv = silu_f((g & 4) ? hi2f(cw[i]) : lo2f(cw[i]));
        const uint32_t sp = (g & 1) ? pack2(0.f, sv) : pack2(sv, 0.f);
        bf[2 * i] = (g & 2) ? 0 : sp; bf[2 * i + 1] = (g & 2) ? sp : 0;
      }
      asm volatile("barrier.cluster.wait.aligned;" ::: "memory");
#pragma unroll
      for (int i = 0; i < 128; i++) acc[i] = 0.f;
      reg_fence<128>(acc);
      tag = __shfl_sync(0xffffffffu, epoch, 0) + 1;
      TH(3);
      if (slab && !late) gemv();
      {
        {
          mbar_wait(sb + BAR_XH, 0);
          TH(5);
          float ds[4] = {0.f, 0.f, 0.f, 0.f}, dq[4][4];
#pragma unroll
          for (int i = 0; i < 4; i++) { dq[i][0] = dq[i][1] = dq[i][2] = dq[i][3] = 0.f; }
#pragma unroll
          for (int i = 0; i < 8; i++) {
            uint32_t a[4];
            ldsm4(sb + SM_XROW + wg * ST1 + wq * 4096 + ((lane >> 3) & 1) * 2048 + i * 256 + (lane >> 4) * 128 + (lane & 7) * 16, a);
            mma16816(ds, a, ONE2, ONE2);
            mma1688(dq[0], a[0], a[1], a[0]); mma1688(dq[1], a[0], a[1], a[1]);
            mma1688(dq[2], a[2], a[3], a[2]); mma1688(dq[3], a[2], a[3], a[3]);
          }
          const bool dg = t == (g >> 1);
          const float q0 = dg ? ((g & 1) ? dq[0][1] + dq[2][1] : dq[0][0] + dq[2][0]) : 0.f;
          const float q1 = dg ? ((g & 1) ? dq[1][3] + dq[3][3] : dq[1][2] + dq[3][2]) : 0.f;
          float q = ((lane & 1) ? q1 : q0) + __shfl_xor_sync(0xffffffffu, (lane & 1) ? q0 : q1, 1);
          float sm = (lane & 1) ? ds[2] : ds[0];
          q += __shfl_xor_sync(0xffffffffu, q, 2);
#pragma unroll
          for (int o = 4; o <= 16; o <<= 1) { q += __shfl_xor_sync(0xffffffffu, q, o); sm += __shfl_xor_sync(0xffffffffu, sm, o); }
          const float mean = sm * (1.f / 1024.f);
          const float rd = rcp_f(rbf(sqrt_f(rbf(rbf(fmaxf(fmaf(-mean, mean, q * (1.f / 1024.f)), 0.f)) + 1e-5f))));
          const float mean1 = __shfl_sync(0xffffffffu, mean, 1), rd1 = __shfl_sync(0xffffffffu, rd, 1);
          const uint32_t rh = pack2(rd, rd1);
          if (lane == 0) st_pkt16(&g_lnst[8 * b0 + warp], pack2(-rbf(mean) * lo2f(rh), -rbf(mean1) * hi2f(rh)), rh, 0, tag);
          TH(6);
          if (tid == 0) TS(2);
        }
      }
    }
    if (slab && late) gemv();
    TILE_ROLES();
    const uint32_t xa0 = sb + SM_RING + (warp * 16 + (lane & 15)) * 128 + (((lane >> 4) ^ (lane & 7)) * 16);
    uint32_t V[16];
    {
      const uint4* mp = &g_rec[tag & 1][(b0 >> 1) & (NREP - 1)][RV * wg + (lane >> 2) * RS + (lane & 3)];
      const uint4* lp = &g_lnst[(8 * rt + warp) * 8 + (g >> 1)];
      mbar_wait(sb + BAR_FULL1, 0);
#pragma unroll
      for (int kk = 0; kk < 4; kk++) ldsm4(xa0 ^ (kk * 32), V + 4 * kk);
      uint4 v0 = make_uint4(1, 0, 0, 0), l0, l1;
      int it = 0;
      while ((uint32_t)clock() - c0 < HD) {}
      do { if (wq == 0) v0 = ld_pkt16(mp);
           l0 = ld_pkt16(lp); l1 = ld_pkt16(lp + 4); spin_guard(it); }
        while (!(__all_sync(0xffffffffu, v0.x != 0 && l0.w == tag && l1.w == tag)));
      TH(7);
      if (wq == 0) put_record(sb, 128 * wg + lane, v0);
      const uint32_t sel = (g & 1) ? 0x3232 : 0x1010;
      ln[0] = __byte_perm(l0.x, 0, sel); ln[1] = __byte_perm(l0.y, 0, sel);
      ln[2] = __byte_perm(l1.x, 0, sel); ln[3] = __byte_perm(l1.y, 0, sel);
      __syncwarp();
      if (lane < 2) mbar_arrive_cl(mapa(sb + BAR_G, lane));
      nb_sync(NB_CONS, 256);
      if (tid == 0) TS(3);
      TH(13);
    }

    const uint32_t rel = mapa(sb + SM_MISC, lane & 1) - SM_MISC;
    const uint32_t stsm_addr = sb + SM_STASH + wg * 16384 + (wq * 16 + (lane & 15)) * 128 + (((lane >> 4) ^ (lane & 7)) * 16);

    uint32_t ph = 0;
    uint32_t X[32];
    {
      const uint32_t tab0 = sb + SM_STASH + wg * 16384 + t * 16;
      const uint64_t db0 = mk_desc(sb + SM_RING + 16384, 8192);
      uint32_t A[2][16];
      uint32_t xa[4];
#pragma unroll
      for (int kk = 0; kk < 4; kk++) xa[kk] = xa0 ^ (kk * 32);
      uint32_t tab = tab0;
      reg_fence<4>(xa);
      asm volatile("{\n.reg .pred p;\nsetp.eq.u32 p, %4, 0;\n@p ld.shared.v4.u32 {%0,%1,%2,%3}, [%5];\n}"
        : "+r"(ln[2]), "+r"(ln[0]), "+r"(ln[3]), "+r"(ln[1]) : "r"(tag), "r"(sb));
      int hs = 2 * ct;
      uint4 R[4];
#pragma unroll
      for (int kk = 0; kk < 4; kk++) R[kk] = lds128(tab + (kk >> 1) * 2048 + (kk & 1) * 64);
#pragma unroll 1
      for (int k4 = 0; k4 < 4; k4++) {
#pragma unroll
        for (int s = 0; s < 4; s++) {
          uint32_t* a = A[s & 1];
          const int sn = (s + 1) & 3;
          const uint32_t pn = (k4 + (s == 3)) & 1;
          modulate_frags(a, V, R, ln);
          if (hs == (s & 2)) {
            if (s & 1) mbar_wait(sb + BAR_HS + 16 * wg, 0);
#pragma unroll
            for (int kk = 0; kk < 4; kk++) stsm4((stsm_addr + 4096) ^ (kk * 32), a[4 * kk], a[4 * kk + 1], a[4 * kk + 2], a[4 * kk + 3]);
            nb_arrive(NB_OST + wg, 160);
          }
          if (s == 0 && k4 == 0) TH(8);
          TQ(3 * s);
          if (s == 0 && k4 == 0 && tid == 0) { TS(6); TSC(61); }
          wg_fence();
#pragma unroll
          for (int kk = 0; kk < 4; kk++) wgmma_rs256<1>(acc, a + 4 * kk, db0 + s * (ST1 >> 4) + kk * 128);
          wg_commit();
          if (s == 3) TQ(12);
          if (s == 3 && k4 < 3) mbar_wait(sb + BAR_TAB + 8 * k4, 0);
          if (s == 3) TQ(13);
#pragma unroll
          for (int kk = 0; kk < 4; kk++) R[kk] = lds128(tab + (s + 1) * 128 + (kk >> 1) * 2048 + (kk & 1) * 64);
          wg_wait<1>();
          if (k4 == 0) TH(9 + s);
          TQ(3 * s + 1);
          reg_fence<16>(A[(s & 1) ^ 1]);
          if ((tid & 127) < 2 && (s | k4)) mbar_arrive_cl(rel + BAR_EMPTY1 + 8 * ((s + 3) & 3));
          if (s < 3 || k4 < 3) {
            mbar_wait(sb + BAR_FULL1 + 8 * sn, pn);
            TQ(3 * s + 2);
#pragma unroll
            for (int kk = 0; kk < 4; kk++) ldsm4(xa[kk] + sn * ST1, V + 4 * kk);
          }
        }
        tab += 512; hs -= 4;
      }
      mbar_wait(sb + BAR_HS + 16 * wg + 8, 0);
      wg_wait<0>();
      reg_fence<128>(acc);
    }
#pragma unroll 1
    for (int pair = 0; pair < 2; pair++) {
      uint32_t Q[32];
      TR(0);
      {
        if ((tid & 127) < 2) mbar_arrive_cl(rel + BAR_EMPTY1 + 8 * 3);
        if (pair == 1) mbar_wait(sb + BAR_STASH + 8 * wg, 1);
#pragma unroll
        for (int i = 0; i < 32; i++) Q[i] = pack2(acc[2 * i], acc[2 * i + 1]);
        const uint32_t qs = sb + SM_STASH + wg * 16384 + wq * 2048 + lane * 16;
#pragma unroll
        for (int i = 0; i < 8; i++)
          sts128(qs + (i & 3) * 512 + (i >> 2) * 8192, pack2(acc[64 + 8 * i], acc[65 + 8 * i]), pack2(acc[66 + 8 * i], acc[67 + 8 * i]),
                 pack2(acc[68 + 8 * i], acc[69 + 8 * i]), pack2(acc[70 + 8 * i], acc[71 + 8 * i]));
      }
      if (tid == 0) TS(8 + pair * 2);
      TR(1);
      float O[64], SL[32], SH[32];
      uint32_t PL[16], PH[16];
      SoftmaxState z;
      const uint64_t d0 = mk_desc(sb + SM_RING, 8192);
      {
        mbar_wait(sb + BAR_FULL1, ph);
        wg_fence();
        issue_qk(SL, Q, d0);
        wg_commit();
        issue_qk(SH, Q, d0 + 1024);
        wg_commit();
#pragma unroll
        for (int i = 0; i < 64; i++) O[i] = 0.f;
        reg_fence<64>(O);
        wg_wait<1>();
        reg_fence<32>(SL);
        softmax_start(z);
        softmax_half(SL, PL, O, z, true, tag);
        wg_wait<0>();
        reg_fence<32>(SH);
        if ((tid & 127) < 2) mbar_arrive_cl(rel + BAR_EMPTY1);
      }
      float lp0 = 0.f, lp1 = 0.f;
      uint32_t dB = (uint32_t)d0 + 1 * (ST1 >> 4), dA = (uint32_t)d0 + 2 * (ST1 >> 4);
      const uint32_t dBx = dB ^ ((uint32_t)d0 + 3 * (ST1 >> 4)), dAx = dA ^ (uint32_t)d0;
      uint32_t so = 0;
      bool ready = false;
#pragma unroll 1
      for (int i = 0; i < 7; i++) {
        TA(0);
        TR(2 + i);
        if (!ready) mbar_wait(sb + BAR_FULL1 + 8 + so, ph);
        TA(1);
        TA(2);
        wg_fence();
        issue_qk(SL, Q, (d0 & 0xffffffff00000000ull) | dB);
        if (i == 4) {
          __syncwarp();
          stage_o(O, lp0, lp1, stsm_addr);
        }
        wg_fence();
        issue_pv(O, PL, ((d0 & 0xffffffff00000000ull) | dB) + 1024, i != 4);
        wg_commit();
        if (i == 4) {
          nb_arrive(NB_OST + wg, 160);
        }
        TA(3);
        ph ^= i & 1;
        ready = mbar_test(sb + BAR_FULL1 + 16 - so, ph);
        softmax_half(SH, PH, O, z, false, tag);
        TA(4);
        wg_wait<0>();
        TA(5);
        reg_fence<32>(SL); reg_fence<16>(PL);
        if ((tid & 127) < 2) mbar_arrive_cl(rel + BAR_EMPTY1 + 8 + so);
        if (!ready) mbar_wait(sb + BAR_FULL1 + 16 - so, ph);
        TA(6);
        wg_fence();
        issue_qk(SH, Q, (d0 & 0xffffffff00000000ull) | dA);
        wg_commit();
        issue_pv(O, PH, ((d0 & 0xffffffff00000000ull) | dA) + 1024, 1);
        wg_commit();
        if (i == 2) {
          wg_wait<1>();
          reg_fence<32>(Q);
          const uint32_t qs = sb + SM_STASH + wg * 16384 + wq * 2048 + lane * 16;
#pragma unroll
          for (int j = 0; j < 8; j++) { const uint4 v = lds128(qs + (j & 3) * 512 + (j >> 2) * 8192); Q[4 * j] = v.x; Q[4 * j + 1] = v.y; Q[4 * j + 2] = v.z; Q[4 * j + 3] = v.w; }
        }
        TA(10);
        if (i == 3) { lp0 = z.l0; lp1 = z.l1; row_rcp(lp0, lp1); softmax_start(z); }
        TA(7);
        so ^= 16; dB ^= dBx; dA ^= dAx;
        ready = mbar_test(sb + BAR_FULL1 + 8 + so, ph);
        softmax_half(SL, PL, O, z, i == 3, tag);
        TA(8);
        wg_wait<0>();
        TA(9);
        reg_fence<32>(SH); reg_fence<16>(PH); reg_fence<64>(O); reg_fence<32>(Q);
        if ((tid & 127) < 2) mbar_arrive_cl(rel + BAR_EMPTY1 + so);
      }
      TAFLUSH();
      TR(9);
      {
        if (!ready) mbar_wait(sb + BAR_FULL1 + 8 * 3, ph);
        ph ^= 1;
        const uint64_t dv = d0 + 3 * (ST1 >> 4);
        wg_fence();
        issue_pv(O, PL, dv, 1);
        wg_commit();
        bb_fence(tag);
        softmax_half(SH, PH, O, z, false, tag);
        wg_fence();
        issue_pv(O, PH, dv + 1024, 1);
        wg_commit();
        TR(10);
        row_rcp(z.l0, z.l1);
        mbar_wait(sb + (pair ? BAR_X : BAR_STASH) + 8 * wg, 0);
#pragma unroll
        for (int kk = 0; kk < 8; kk++) ldsm4((stsm_addr + (kk >> 2) * 8192) ^ ((kk & 3) * 32), X + 4 * kk);
        reg_fence<32>(X);
        __syncwarp();
        wg_wait<0>();
        reg_fence<64>(O);
        TR(11);
        if ((tid & 127) < 2) mbar_arrive_cl(rel + BAR_EMPTY1 + 8 * 3);
        stage_o(O, z.l0, z.l1, stsm_addr);
        nb_arrive(NB_OST + wg, 160);
      }
      TR(12);
      if (tid == 0) { TS(9 + pair * 2); TSC(62); }
      if (pair == 1) break;
      {
        mbar_wait(sb + BAR_FULL1, ph);
        const uint64_t da = mk_desc(sb + SM_RING + wg * 8192, 16), db = mk_desc(sb + SM_RING + 16384, 8192);
        wg_fence();
        wgmma_ss256_z<1>(acc, da, db);
#pragma unroll
        for (int kk = 1; kk < 4; kk++) wgmma_ss256<1>(acc, da + kk * 2, db + kk * 128, 1);
        wg_commit();
      }
#pragma unroll 1
      for (int kt = 1; kt < 16; kt++) {
        const uint32_t s = kt & 3;
        if (s == 0) ph ^= 1;
        mbar_wait(sb + BAR_FULL1 + 8 * s, ph);
        const uint32_t st = sb + SM_RING + s * ST1;
        const uint64_t da = mk_desc(st + wg * 8192, 16), db = mk_desc(st + 16384, 8192);
        wg_fence();
#pragma unroll
        for (int kk = 0; kk < 4; kk++) wgmma_ss256<1>(acc, da + kk * 2, db + kk * 128, 1);
        wg_commit();
        wg_wait<1>();
        if ((tid & 127) < 2) mbar_arrive_cl(rel + BAR_EMPTY1 + 8 * ((s + 3) & 3));
      }
      ph ^= 1;
      wg_wait<0>();
      reg_fence<128>(acc);
      TR(13);
    }

    uint4 WG[16], WU[16];
    const int fp = 64 * warp + 8 * g + t;
    uint32_t fsb0, fsb1, fcb0, fcb1, fgb0, fgb1;
    const uint32_t gu_base = sb + SM_RING + (warp >> 1) * ST1 + 32768 + (warp & 1) * 8192;
    const uint32_t gu_addr = gu_base + t * 128 + (g & 1) * 64 + ((g >> 1) ^ t) * 16;
    {
      const uint64_t da0 = mk_desc(sb + SM_RING + __shfl_sync(0xffffffffu, wg, 0) * 8192, 16), db0 = mk_desc(sb + SM_RING + 16384, 8192);
#pragma unroll
      for (int n = 0; n < 4 + 5 * PEEL; n++) {
        const int s = n < 4 ? n : (n - 4) % 5;
        mbar_wait(sb + BAR_FULL1 + 8 * s, n < 4 ? 0 : ((n - 4) / 5 + (s < 4)) & 1);
        if (n < 4) TSX(40 + wg * 6 + n);
        const uint64_t da = da0 + s * (ST1 >> 4), db = db0 + s * (ST1 >> 4);
        wg_fence();
        if (n == 0) wgmma_ss128_z<1>(acc, da, db); else wgmma_ss128<1>(acc, da, db, 1);
#pragma unroll
        for (int kk = 1; kk < 4; kk++) wgmma_ss128<1>(acc, da + kk * 2, db + kk * 128, 1);
        wg_commit();
        if (n == 1) {
          mbar_wait(sb + BAR_OF, 0);
          const uint2* mp = &g_mod[3 * 512 + fp];
          fsb0 = ld_pkt8(mp).x; fsb1 = ld_pkt8(mp + 4).x; fcb0 = ld_pkt8(mp + 512).x; fcb1 = ld_pkt8(mp + 516).x;
          fgb0 = ld_pkt8(mp + 1024).x; fgb1 = ld_pkt8(mp + 1028).x;
        }
        if (n == 0 && b < NFFN) mbar_wait(sb + BAR_FFN, 0);
        {
          constexpr int NT = 4 + 5 * PEEL, F0 = NT > 16 ? NT - 16 : 0;
#pragma unroll
          for (int i = 0; i < 16; i++) if (F0 + i * (NT - F0) / 16 == n) WG[i] = lds128(gu_addr + i * 512);
        }
        if (n > 0) {
          wg_wait<1>();
          if ((tid & 127) < 2) mbar_arrive_cl(rel + BAR_EMPTY1 + 8 * (n == 4 ? 3 : s ? s - 1 : 4));
        }
      }
      TSX(44 + wg * 6);
      {
        uint32_t dep = 0;
#pragma unroll
        for (int i = 0; i < 16; i++) dep ^= WG[i].x;
        if (__shfl_sync(0xffffffffu, tag, dep & 31) == tag && lane == 2) mbar_arrive(sb + BAR_TFREE);
      }
      {
        uint32_t so = 0, sp = 4 * 8, par = PEEL + 1;
#pragma unroll 1
        for (int n = 4 + 5 * PEEL; n < 64; n++) {
          mbar_wait(sb + BAR_FULL1 + so, (par + (so >> 5)) & 1);
          const uint64_t da = da0 + so * (ST1 >> 7), db = db0 + so * (ST1 >> 7);
          wg_fence();
#pragma unroll
          for (int kk = 0; kk < 4; kk++) wgmma_ss128<1>(acc, da + kk * 2, db + kk * 128, 1);
          wg_commit();
          wg_wait<1>();
          if ((tid & 127) < 2) mbar_arrive_cl(rel + BAR_EMPTY1 + sp);
          sp = so; so += 8;
          if (so == 40) { so = 0; par++; }
        }
      }
    }
    mbar_wait(sb + BAR_VEC, 0);
    const int lrow = warp * 16 + g;
    uint2 ga[8], b1[8];
#pragma unroll
    for (int kk = 0; kk < 8; kk++) { ga[kk] = lds64(sb + SM_GA + kk * 32 + t * 8); b1[kk] = lds64(sb + SM_B1 + min(g, 3) * 32 + t * 8 + kk * 128); }
    uint4* const stp = &g_stats[b * 128 + lrow + 8 * t];
    bb_fence(tag);
    wg_wait<0>();
    reg_fence<64>(acc);
    if (tid == 0) { TS(12); TSC(63); }

    TT(0);
    {
      float d1[4] = {0.f, 0.f, 0.f, 0.f}, d2[4] = {0.f, 0.f, 0.f, 0.f}, d3[4] = {0.f, 0.f, 0.f, 0.f};
      float d4[4] = {0.f, 0.f, 0.f, 0.f}, d5[4] = {0.f, 0.f, 0.f, 0.f};
#pragma unroll
      for (int kk = 0; kk < 8; kk++) {
        uint32_t* x = X + 4 * kk;
        x[0] = hfma2(ga[kk].x, pack2(acc[8 * kk + 0], acc[8 * kk + 1]), x[0]);
        x[1] = hfma2(ga[kk].x, pack2(acc[8 * kk + 2], acc[8 * kk + 3]), x[1]);
        x[2] = hfma2(ga[kk].y, pack2(acc[8 * kk + 4], acc[8 * kk + 5]), x[2]);
        x[3] = hfma2(ga[kk].y, pack2(acc[8 * kk + 6], acc[8 * kk + 7]), x[3]);
        mma16816(d1, x, b1[kk].x, b1[kk].y);
        mma1688(d2, x[0], x[1], x[0]); mma1688(d3, x[0], x[1], x[1]);
        mma1688(d4, x[2], x[3], x[2]); mma1688(d5, x[2], x[3], x[3]);
      }
      const int qb = lane & 28;
      const float q0 = __shfl_sync(0xffffffffu, (g & 1) ? d2[1] + d4[1] : d2[0] + d4[0], qb | (g >> 1));
      const float q1 = __shfl_sync(0xffffffffu, (g & 1) ? d3[3] + d5[3] : d3[2] + d5[2], qb | (g >> 1));
      const float e0 = __shfl_xor_sync(0xffffffffu, t ? d1[0] : d1[3], 1);
      const float e1 = __shfl_sync(0xffffffffu, d1[2], qb);
      if (t < 2) st_pkt16(stp, __float_as_uint(t ? e1 : d1[0]), __float_as_uint(t ? q1 : q0),
                          __float_as_uint((t ? d1[2] : d1[1]) + e0), tag);
    }
    TSY(13);
    TT(1);
    float mb, rd, den, br;
    {
      const uint4* sp = &g_stats[(rt * 8 + 4 * (t & 1)) * 128 + lrow + 4 * (t & 2)];
      mbar_wait(sb + BAR_EMPTY1 + 8 * 3, 0);
#pragma unroll
      for (int kk = 0; kk < 8; kk++) stsm4((stsm_addr - SM_STASH + SM_X2 + (kk >> 2) * 8192) ^ ((kk & 3) * 32), X[4 * kk], X[4 * kk + 1], X[4 * kk + 2], X[4 * kk + 3]);
      if (b < NFFN) mbar_wait(sb + BAR_FFN, 1);
#pragma unroll
      for (int i = 0; i < WU1; i++) WU[i] = lds128(gu_addr + i * 512);
      bb_fence(tag);
      TT(2);
      uint4 v0, v1, v2, v3;
      int it = 0;
      do { v0 = ld_pkt16(sp); v1 = ld_pkt16(sp + 128); v2 = ld_pkt16(sp + 256); v3 = ld_pkt16(sp + 384); spin_guard(it); }
        while (!(__all_sync(0xffffffffu, v0.w == tag && v1.w == tag && v2.w == tag && v3.w == tag)));
      TT(3);
      float sm = (__uint_as_float(v0.x) + __uint_as_float(v1.x)) + (__uint_as_float(v2.x) + __uint_as_float(v3.x));
      float sq = (__uint_as_float(v0.y) + __uint_as_float(v1.y)) + (__uint_as_float(v2.y) + __uint_as_float(v3.y));
      float dt = (__uint_as_float(v0.z) + __uint_as_float(v1.z)) + (__uint_as_float(v2.z) + __uint_as_float(v3.z));
      sm += __shfl_xor_sync(0xffffffffu, sm, 1); sq += __shfl_xor_sync(0xffffffffu, sq, 1); dt += __shfl_xor_sync(0xffffffffu, dt, 1);
      const uint2 scal = lds64(sb + SM_SCAL);
      const float mu = sm * (1.f / 1024.f);
      mb = rbf(mu);
      den = rbf(sqrt_f(rbf(rbf(fmaxf(fmaf(-mu, mu, sq * (1.f / 1024.f)), 0.f)) + 1e-5f)));
      rd = rcp_f(den);
      br = fmaf(fmaf(-mb, __uint_as_float(scal.x), dt), rd, __uint_as_float(scal.y));
    }
    TSY(14);
    TT(4);
    {
      const int rb = __float_as_int(br);
      const int key = ((rb ^ ((rb >> 31) & 0x7fffffff)) | 127) - (lrow + 4 * (t & 2));
      if (key == __reduce_max_sync(0xffffffffu, key)) sts64(sb + SM_AMAX + warp * 8, (uint32_t)key, pack2(mb, den));
      __syncwarp();
      nb_arrive(NB_AMAX, 288);
    }
    TT(5);
    const uint4* ep = &g_entry[(warp * 16 + (lane & 15)) * 8];
    const uint32_t slot = sb + SM_STASH + wg * 8192 + (tid & 127) * 16;
    cp_async16(slot, ep);
    {
      const float rh = rbf(rd);
      const uint32_t u = pack2(-mb * rh, rh);
      const int qb = lane & 28;
      const uint32_t u0 = __shfl_sync(0xffffffffu, u, qb), u1 = __shfl_sync(0xffffffffu, u, qb | 2);
      const uint32_t m0 = __byte_perm(u0, 0, 0x1010), h0 = __byte_perm(u0, 0, 0x3232);
      const uint32_t m1 = __byte_perm(u1, 0, 0x1010), h1 = __byte_perm(u1, 0, 0x3232);
#pragma unroll
      for (int j = 0; j < 16; j++) {
        const uint4 rec = lds128(sb + SM_REC + (4 * j + t) * 16);
        X[2 * j] = hfma2(rec.z, hfma2(hfma2(X[2 * j], h0, m0), rec.x, rec.y), X[2 * j]);
        X[2 * j + 1] = hfma2(rec.z, hfma2(hfma2(X[2 * j + 1], h1, m1), rec.x, rec.y), X[2 * j + 1]);
      }
#pragma unroll
      for (int kk = 0; kk < 8; kk++) stsm4((stsm_addr - SM_STASH + SM_OUT + (kk >> 2) * 8192) ^ ((kk & 3) * 32), X[4 * kk], X[4 * kk + 1], X[4 * kk + 2], X[4 * kk + 3]);
    }
    cp_async_wait();
    uint4 ent = lds128(slot);
    TSY(16);
    TT(6);
    int wrow;
    uint32_t xs0, xs1, hs0, hs1;
    uint32_t WD[64];
    const uint32_t wd_addr = sb + SM_RING + wg * ST1 + wq * 8192 + ((lane & 7) + ((lane >> 4) << 3)) * 128 + ((((lane >> 3) & 1) ^ (lane & 7)) * 16);
    {
      int gmax;
      auto leader = [&]() {
        gmax = __reduce_max_sync(0xffffffffu, ent.w == tag ? (int)ent.x : (int)0x8000000f);
        return ~gmax & 15;
      };
      int wt = leader(), it = 0;
      TT(7);
      nb_arrive(NB_OST + wg, 160);
      TT(8);
      cp_async16(slot + 2048, &g_cand[(wt * 8 + warp) * 32 + lane]);
      if (ent.w != tag) cp_async16(slot, ep);
#pragma unroll
      for (int i = WU1; i < 16; i++) WU[i] = lds128(gu_addr + i * 512);
      if (b < NFFN) mbar_wait(sb + BAR_FFN + 8, 0);
#pragma unroll
      for (int mt = 0; mt < 8; mt++)
#pragma unroll
        for (int s = 0; s < 2; s++) ldsm4t((wd_addr + (mt >> 2) * 4096 + s * 2048) ^ ((mt & 3) * 32), WD + (mt * 2 + s) * 4);
      cp_async_wait();
      uint4 v = lds128(slot + 2048);
      ent = lds128(slot);
      TT(9);
      while (true) {
        const int have = wt;
        wt = leader();
        if (__all_sync(0xffffffffu, ent.w == tag && have == wt && v.z == tag)) break;
        v = ld_pkt16(&g_cand[(wt * 8 + warp) * 32 + lane]);
        if (ent.w != tag) ent = ld_pkt16(ep);
        spin_guard(it);
      }
      TT(10);
      ent.x = gmax ^ ((gmax >> 31) & 0x7fffffff);
      wrow = __shfl_sync(0xffffffffu, ent.y, wt); ent.z = __shfl_sync(0xffffffffu, ent.z, wt);
      xs0 = v.x; xs1 = v.y;
      const uint32_t mm = __byte_perm(ent.z, 0, 0x1010);
      const float rs = rcp_f(hi2f(ent.z));
      const uint32_t e0 = hsub2(xs0, mm), e1 = hsub2(xs1, mm);
      hs0 = hfma2(pack2(lo2f(e0) * rs, hi2f(e0) * rs), hadd2(fcb0, ONE2), fsb0);
      hs1 = hfma2(pack2(lo2f(e1) * rs, hi2f(e1) * rs), hadd2(fcb1, ONE2), fsb1);
    }
    if ((tid & 127) == 0) sts32(sb + SM_WROW + 4 * wg, wrow);
    nb_arrive(NB_WIN + wg, 160);
    TSY(17);
    TT(11);
    if (b < NFFN) {
      float da[4][4];
#pragma unroll
      for (int i = 0; i < 4; i++) { da[i][0] = da[i][1] = da[i][2] = da[i][3] = 0.f; }
      const uint32_t selv = ((g & 1) ? 0x1044 : 0x4410) + ((g & 4) ? ((g & 1) ? 0x2200 : 0x0022) : 0);
      const uint32_t sel0 = (g & 2) ? 0x4444 : selv, sel1 = (g & 2) ? selv : 0x4444;
#pragma unroll
      for (int s = 0; s < 16; s++) {
        const uint32_t v = __shfl_sync(0xffffffffu, (s & 1) ? hs1 : hs0, 4 * (s >> 1) + t);
        const uint32_t b0 = __byte_perm(v, 0, sel0), b1 = __byte_perm(v, 0, sel1);
        const uint32_t a0[4] = {WG[s].x, WG[s].y, WG[s].z, WG[s].w};
        const uint32_t a1[4] = {WU[s].x, WU[s].y, WU[s].z, WU[s].w};
        mma16816(da[(s & 1) * 2], a0, b0, b1);
        mma16816(da[(s & 1) * 2 + 1], a1, b0, b1);
      }
      {
        float v[4];
#pragma unroll
        for (int i = 0; i < 4; i++) {
          const float vg = da[0][i] + da[2][i], vu = da[1][i] + da[3][i];
          v[i] = ((g & 1) ? vu : vg) + __shfl_xor_sync(0xffffffffu, (g & 1) ? vg : vu, 6);
        }
        if ((t >> 1) == (g & 1))
          sts128(gu_base + (g & 1) * 128 + (g >> 1) * 32 + (t & 1) * 16, __float_as_uint(v[0]), __float_as_uint(v[1]), __float_as_uint(v[2]), __float_as_uint(v[3]));
      }
      TT(12);
      nb_sync(NB_CONS, 256);
      float gp[8], up[8];
#pragma unroll
      for (int w = 0; w < 8; w++) {
        const uint32_t a = sb + SM_RING + (w >> 1) * ST1 + 32768 + (w & 1) * 8192 + lane * 4;
        gp[w] = lds_f32(a); up[w] = lds_f32(a + 128);
      }
      const float gsum = ((gp[0] + gp[1]) + (gp[2] + gp[3])) + ((gp[4] + gp[5]) + (gp[6] + gp[7]));
      const float usum = ((up[0] + up[1]) + (up[2] + up[3])) + ((up[4] + up[5]) + (up[6] + up[7]));
      const float act = rbf(silu_f(rbf(gsum))) * rbf(usum);
      TT(13);
      const uint32_t ap = pack2(act, __shfl_down_sync(0xffffffffu, act, 1));
      const uint32_t b00 = __shfl_sync(0xffffffffu, ap, 2 * t), b01 = __shfl_sync(0xffffffffu, ap, 2 * t + 8);
      const uint32_t b10 = __shfl_sync(0xffffffffu, ap, 2 * t + 16), b11 = __shfl_sync(0xffffffffu, ap, 2 * t + 24);
      float y[8][4];
#pragma unroll
      for (int mt = 0; mt < 8; mt++) {
        y[mt][0] = y[mt][1] = y[mt][2] = y[mt][3] = 0.f;
        mma16816(y[mt], WD + (mt * 2) * 4, b00, b01);
        mma16816(y[mt], WD + (mt * 2 + 1) * 4, b10, b11);
      }
#pragma unroll
      for (int e = 0; e < 2; e++) {
        const float v0 = t == 0 ? y[e][0] : t == 1 ? y[2 + e][0] : t == 2 ? y[4 + e][0] : y[6 + e][0];
        const float v1 = t == 0 ? y[e][2] : t == 1 ? y[2 + e][2] : t == 2 ? y[4 + e][2] : y[6 + e][2];
        const int f = 16 * warp + 2 * (2 * t + e) + (g >> 2);
        st_pkt16(&g_ypart[(f * NFFN + b) * 4 + (g & 3)], __float_as_uint(v0), __float_as_uint(v1), tag, 0);
      }
    }
    TSY(18);
    TT(14);
    {
      const int pw = warp - (warp > (b >> 4));
      if (warp != (b >> 4)) {
        const uint4* yp = &g_ypart[b * NFFN * 4 + pw * 64 + lane];
        uint4 v0, v1;
        int it = 0;
        { const uint32_t c1 = clock(); while ((uint32_t)clock() - c1 < (b < NFFN ? YD : YD + 1500)) {} }
        do { v0 = ld_pkt16(yp); v1 = ld_pkt16(yp + 32); spin_guard(it); }
        while (!(__all_sync(0xffffffffu, v0.z == tag && v1.z == tag)));
        float y0 = __uint_as_float(v0.x) + __uint_as_float(v1.x), y1 = __uint_as_float(v0.y) + __uint_as_float(v1.y);
#pragma unroll
        for (int o = 4; o <= 16; o <<= 1) { y0 += __shfl_xor_sync(0xffffffffu, y0, o); y1 += __shfl_xor_sync(0xffffffffu, y1, o); }
        if (lane < 4) sts64(sb + SM_YRED + pw * 32 + lane * 8, __float_as_uint(y0), __float_as_uint(y1));
      }
    }
    TT(15);
    if (warp != (b >> 4)) {
      nb_arrive(NB_CONS, 256);
    } else {
      nb_sync(NB_CONS, 256);
      float y0 = 0.f, y1 = 0.f;
      if (lane < 28) { const uint2 e = lds64(sb + SM_YRED + lane * 8); y0 = __uint_as_float(e.x); y1 = __uint_as_float(e.y); }
#pragma unroll
      for (int o = 4; o <= 16; o <<= 1) { y0 += __shfl_xor_sync(0xffffffffu, y0, o); y1 += __shfl_xor_sync(0xffffffffu, y1, o); }
      const int src = 2 * (t & 1);
      const float ya = __shfl_sync(0xffffffffu, y0, src), yb = __shfl_sync(0xffffffffu, y0, src + 1);
      const float yc = __shfl_sync(0xffffffffu, y1, src), yd = __shfl_sync(0xffffffffu, y1, src + 1);
      if (g == ((b >> 1) & 7) && (t >> 1) == (b & 1)) {
        const float rs = rbf(__uint_as_float(ent.x));
        const float sg = sigmoid_f(rs);
        const uint32_t sg2 = pack2(sg, sg);
        const uint32_t o0 = hadd2(xs0, hmul2(fgb0, hadd2(hs0, hmul2(pack2(ya, yb), sg2))));
        const uint32_t o1 = hadd2(xs1, hmul2(fgb1, hadd2(hs1, hmul2(pack2(yc, yd), sg2))));
        uint32_t* op = reinterpret_cast<uint32_t*>(p.out + (size_t)wrow * 1024) + fp;
        op[0] = o0; op[4] = o1;
      }
      if (b == 0) {
        if (lane < 8) st_relaxed(&p.sc->ticket[lane * 32], 0);
        st_relaxed(&p.sc->epoch[lane], tag);
      }
      if (lane == 0) TS(19);
    }
  }
}

typedef CUresult (*EncodeFn)(CUtensorMap*, CUtensorMapDataType, cuuint32_t, void*, const cuuint64_t*, const cuuint64_t*,
                             const cuuint32_t*, const cuuint32_t*, CUtensorMapInterleave, CUtensorMapSwizzle,
                             CUtensorMapL2promotion, CUtensorMapFloatOOBfill);

CUtensorMap make_map(EncodeFn enc, const void* ptr, uint64_t rows, uint64_t cols, uint32_t box_rows, uint32_t box_cols, CUtensorMapSwizzle sw) {
  CUtensorMap m;
  cuuint64_t dims[2] = {cols, rows};
  cuuint64_t strides[1] = {cols * 2};
  cuuint32_t box[2] = {box_cols, box_rows};
  cuuint32_t es[2] = {1, 1};
  enc(&m, CU_TENSOR_MAP_DATA_TYPE_BFLOAT16, 2, const_cast<void*>(ptr), dims, strides, box, es, CU_TENSOR_MAP_INTERLEAVE_NONE, sw,
      CU_TENSOR_MAP_L2_PROMOTION_L2_128B, CU_TENSOR_MAP_FLOAT_OOB_FILL_NONE);
  return m;
}

CUtensorMap make_map3(EncodeFn enc, const void* ptr, uint64_t rows, uint64_t cols, uint32_t box_rows, uint32_t box_blks) {
  CUtensorMap m;
  cuuint64_t dims[3] = {64, rows, cols / 64};
  cuuint64_t strides[2] = {cols * 2, 128};
  cuuint32_t box[3] = {64, box_rows, box_blks};
  cuuint32_t es[3] = {1, 1, 1};
  enc(&m, CU_TENSOR_MAP_DATA_TYPE_BFLOAT16, 3, const_cast<void*>(ptr), dims, strides, box, es, CU_TENSOR_MAP_INTERLEAVE_NONE,
      CU_TENSOR_MAP_SWIZZLE_128B, CU_TENSOR_MAP_L2_PROMOTION_L2_128B, CU_TENSOR_MAP_FLOAT_OOB_FILL_NONE);
  return m;
}

}

extern "C" void kernel_launch(void* const* d_in, const int* in_sizes, int n_in, void* d_out, int out_size) {
  (void)in_sizes; (void)n_in; (void)out_size;
  Params p;
  p.x = (const bf16*)d_in[0]; p.kc = (const bf16*)d_in[1]; p.vc = (const bf16*)d_in[2];
  p.wq = (const bf16*)d_in[3]; p.wo = (const bf16*)d_in[4]; p.w_r = (const bf16*)d_in[6];
  p.wg = (const bf16*)d_in[7]; p.wu = (const bf16*)d_in[8]; p.wd = (const bf16*)d_in[9];
  p.c = (const bf16*)d_in[10]; p.w_mod = (const bf16*)d_in[11]; p.out = (bf16*)d_out;

  void* fn = nullptr;
  cudaDriverEntryPointQueryResult st;
  cudaGetDriverEntryPoint("cuTensorMapEncodeTiled", &fn, cudaEnableDefault, &st);
  EncodeFn enc = (EncodeFn)fn;
  void* scp = nullptr;
  cudaGetSymbolAddress(&scp, g_scratch);
  p.sc = (Scratch*)scp;
  void *hp = p.sc->h, *op = p.sc->o;
  const CUtensorMapSwizzle S128 = CU_TENSOR_MAP_SWIZZLE_128B;
  CUtensorMap mH = make_map(enc, hp, 2048, 1024, 64, 64, S128);
  CUtensorMap mWq = make_map3(enc, p.wq, 1024, 4096, 64, 4);
  CUtensorMap mK = make_map(enc, p.kc, 8192, 128, 64, 64, S128);
  CUtensorMap mV = make_map(enc, p.vc, 8192, 128, 64, 64, S128);
  CUtensorMap mO = make_map(enc, op, 2048, 4096, 64, 64, S128);
  CUtensorMap mOs = make_map(enc, op, 2048, 4096, 16, 64, S128);
  CUtensorMap mWo = make_map3(enc, p.wo, 4096, 1024, 64, 2);
  CUtensorMap mX = make_map(enc, p.x, 2048, 1024, 64, 64, S128);
  CUtensorMap mOut = make_map(enc, p.out, 2048, 1024, 64, 64, S128);
  CUtensorMap mWg = make_map(enc, p.wg, 1024, 3584, 256, 32, CU_TENSOR_MAP_SWIZZLE_64B);
  CUtensorMap mWu = make_map(enc, p.wu, 1024, 3584, 256, 32, CU_TENSOR_MAP_SWIZZLE_64B);
  CUtensorMap mWd = make_map3(enc, p.wd, 3584, 1024, 32, 8);
  CUtensorMap mWm = make_map(enc, p.w_mod, 1024, 6144, 16, 256, CU_TENSOR_MAP_SWIZZLE_NONE);
  CUtensorMap mWh = make_map(enc, p.w_mod, 1024, 6144, 256, 32, CU_TENSOR_MAP_SWIZZLE_64B);
  CUtensorMap mWs = make_map(enc, p.w_mod, 1024, 6144, 128, 128, CU_TENSOR_MAP_SWIZZLE_NONE);
  cudaFuncSetAttribute(fused_kernel, cudaFuncAttributeMaxDynamicSharedMemorySize, SMEM_BYTES);
  fused_kernel<<<NCTA, NTHREADS, SMEM_BYTES>>>(p, mH, mWq, mK, mV, mO, mWo, mX, mOut, mWg, mWu, mWd, mWm, mWs, mWh, mOs);
}
```

```cpp
#include <cuda_runtime.h>
#include <cuda_bf16.h>
#include <cuda.h>
#include <stdint.h>
#include <stddef.h>

#define UPD 200
#define GATED 700
#define PFW 100
#define OP0 200
#define OP3 90
#define PLD 200
#define WL 3500
#define SPT 5000
#define HD 6000
#define YD 500
#define PEEL 1
#define WU1 12

namespace {

typedef __nv_bfloat16 bf16;

constexpr int NTHREADS = 384;
constexpr int NMAIN = 128;
constexpr int NCTA = 132;
constexpr int RS = 8, RV = 16 * RS + 64;
constexpr int NREP = 4;
constexpr int NFFN = 112;

constexpr uint32_t SM_RING = 0;
constexpr uint32_t ST1 = 49152;
constexpr uint32_t ST2 = 32768;
constexpr int NST2 = 6;
constexpr uint32_t SM_STASH = 196608;
constexpr uint32_t SM_MISC = 229376;
constexpr uint32_t BAR_FULL1 = SM_MISC + 0;
constexpr uint32_t BAR_EMPTY1 = SM_MISC + 40;
constexpr uint32_t BAR_FULL2 = SM_MISC + 0;
constexpr uint32_t BAR_EMPTY2 = SM_MISC + 48;
constexpr uint32_t BAR_STASH = SM_MISC + 160;
constexpr uint32_t BAR_SFREE = SM_MISC + 176;
constexpr uint32_t BAR_TFREE = SM_MISC + 184;
constexpr uint32_t BAR_FFN = SM_MISC + 192;
constexpr uint32_t BAR_VEC = SM_MISC + 208;
constexpr uint32_t BAR_RED = SM_MISC + 216;
constexpr uint32_t BAR_XH = SM_MISC + 152;
constexpr uint32_t BAR_HS = SM_MISC + 80;
constexpr uint32_t BAR_G = SM_MISC + 112;
constexpr uint32_t BAR_T1 = SM_MISC + 120;
constexpr uint32_t BAR_HF = SM_MISC + 128;
constexpr uint32_t BAR_X = SM_MISC + 136;
constexpr uint32_t BAR_OF = SM_MISC + 224;
constexpr uint32_t BAR_ROLE = SM_MISC + 240;
constexpr uint32_t SM_ROLE = SM_MISC + 248;
constexpr uint32_t SM_GA = SM_MISC + 256;
constexpr uint32_t SM_SCAL = SM_MISC + 512;
constexpr uint32_t SM_WROW = SM_MISC + 520;
constexpr uint32_t SM_AMAX = SM_MISC + 528;
constexpr uint32_t SM_YRED = SM_MISC + 656;
constexpr uint32_t SM_X2 = 2 * ST1, SM_OUT = 3 * ST1;
constexpr uint32_t SM_REC = SM_MISC + 1024;
constexpr uint32_t BAR_TAB = SM_MISC + 1000;
constexpr uint32_t BAR_CAND = SM_MISC + 880;
constexpr uint32_t SM_CAND = SM_MISC + 888;
constexpr uint32_t BAR_WH = SM_MISC + 960;
constexpr uint32_t SM_WSLAB = 2 * 49152 + 16384;
constexpr uint32_t SM_XROW = 2 * 49152;
constexpr uint32_t SM_RED = SM_MISC + 2048;
constexpr uint32_t SM_B1 = SM_MISC + 2048;
constexpr uint32_t SMEM_BYTES = 232448;

constexpr int NB_CONS = 1, NB_WIN = 2  , NB_OST = 4  , NB_AMAX = 6;

struct __align__(1024) Scratch {
  uint32_t epoch[32];
  uint32_t hflag[16 * 32];
  uint32_t oflag[64 * 32];
  uint2 vdone[4 * 16];
  uint32_t pad[96 + 512];
  uint32_t ticket[8 * 32];
  uint2 mod[3072];
  uint4 rec[2][NREP][2 * RV];
  uint4 lnst[1024];
  uint4 entry[8 * 16 * 8];
  uint4 cand[16 * 8 * 32];
  uint4 stats[16 * 8 * 128];
  uint4 ypart[128 * NFFN * 4];
  unsigned long long ts[NCTA * 64];
  uint16_t h[2048 * 1024];
  uint16_t o[2048 * 4096];
};
__device__ Scratch g_scratch;
#define g_epoch (p.sc->epoch[0])
#define g_hflag (p.sc->hflag)
#define g_oflag (p.sc->oflag)
#define g_mod (p.sc->mod)
#define g_entry (p.sc->entry)
#define g_cand (p.sc->cand)
#define g_stats (p.sc->stats)
#define g_ypart (p.sc->ypart)
#define g_vdone (p.sc->vdone)
#define g_lnst (p.sc->lnst)
#define g_rec (p.sc->rec)
#define g_ts (p.sc->ts)
#define g_h (p.sc->h)

struct Params {
  const bf16* w_mod; const bf16* c; Scratch* sc; const bf16* x; const bf16* w_r; bf16* out;
  const bf16* wq; const bf16* wo; const bf16* wg; const bf16* wu; const bf16* wd; const bf16* kc; const bf16* vc;
};

__device__ __forceinline__ uint32_t smem_u32(const void* p) { return (uint32_t)__cvta_generic_to_shared(p); }
__device__ __forceinline__ void mbar_init(uint32_t bar, uint32_t cnt) { asm volatile("mbarrier.init.shared::cta.b64 [%0], %1;" :: "r"(bar), "r"(cnt) : "memory"); }
__device__ __forceinline__ void mbar_expect_tx(uint32_t bar, uint32_t bytes) { asm volatile("mbarrier.arrive.expect_tx.shared::cta.b64 _, [%0], %1;" :: "r"(bar), "r"(bytes) : "memory"); }
__device__ __forceinline__ void mbar_arrive(uint32_t bar) { asm volatile("mbarrier.arrive.shared::cta.b64 _, [%0];" :: "r"(bar) : "memory"); }
__device__ __forceinline__ void mbar_arrive_cl(uint32_t cluster_addr) { asm volatile("mbarrier.arrive.shared::cluster.b64 _, [%0];" :: "r"(cluster_addr) : "memory"); }
__device__ __forceinline__ uint32_t mapa(uint32_t addr, uint32_t cta) { uint32_t r; asm("mapa.shared::cluster.u32 %0, %1, %2;" : "=r"(r) : "r"(addr), "r"(cta)); return r; }
__device__ __forceinline__ bool mbar_test(uint32_t bar, uint32_t parity) {
  uint32_t ok;
  asm volatile("{\n.reg .pred p;\nmbarrier.test_wait.parity.shared::cta.b64 p, [%1], %2;\nselp.u32 %0, 1, 0, p;\n}" : "=r"(ok) : "r"(bar), "r"(parity) : "memory");
  return ok;
}
constexpr int SPIN_LIMIT = 300000;
__device__ __forceinline__ void spin_guard(int& it) {
  asm volatile("{\n.reg .pred p;\n.reg .b64 z;\nadd.s32 %0, %0, 1;\nsetp.gt.s32 p, %0, %1;\nmov.b64 z, 0;\n@p st.volatile.global.u32 [z], %0;\n}" : "+r"(it) : "n"(SPIN_LIMIT));
}
__device__ __forceinline__ void mbar_wait_g(uint32_t bar, uint32_t parity) {
  asm volatile("{\n.reg .pred p, q;\n.reg .b32 c;\n.reg .b64 z;\nmov.b32 c, 0;\nmov.b64 z, 0;\nMW_LOOP:\n"
               "mbarrier.try_wait.parity.shared::cta.b64 p, [%0], %1;\nadd.s32 c, c, 1;\nsetp.gt.s32 q, c, %2;\n"
               "@q st.volatile.global.u32 [z], c;\n@!p bra MW_LOOP;\n}" :: "r"(bar), "r"(parity), "n"(SPIN_LIMIT) : "memory");
}
__device__ __forceinline__ void mbar_wait(uint32_t bar, uint32_t parity) {
  asm volatile("{\n.reg .pred p;\nMW_LOOP:\nmbarrier.try_wait.parity.shared::cta.b64 p, [%0], %1;\n@!p bra MW_LOOP;\n}" :: "r"(bar), "r"(parity) : "memory");
}
__device__ __forceinline__ void bb_fence(uint32_t v) {
  asm volatile("{\n.reg .pred p;\n.reg .u32 c;\nsetp.ne.u32 p, %0, 0;\n@p bra.uni BF_DONE;\nBF_LOOP:\nnanosleep.u32 1;\nmov.u32 c, %%clock;\nsetp.eq.u32 p, c, 0;\n@p bra.uni BF_LOOP;\nBF_DONE:\n}" :: "r"(v) : "memory");
}
__device__ __forceinline__ bool elect_one() {
  uint32_t pred;
  asm volatile("{\n.reg .pred P;\nelect.sync _|P, 0xffffffff;\nselp.u32 %0, 1, 0, P;\n}" : "=r"(pred));
  return pred;
}
__device__ __forceinline__ void tma_ld_hint(uint32_t dst, const CUtensorMap* m, int c0, int c1, uint32_t bar, uint64_t pol) {
  asm volatile("cp.async.bulk.tensor.2d.shared::cluster.global.mbarrier::complete_tx::bytes.L2::cache_hint [%0], [%1, {%3, %4}], [%2], %5;"
    :: "r"(dst), "l"(m), "r"(bar), "r"(c0), "r"(c1), "l"(pol) : "memory");
}
__device__ __forceinline__ void tma_ld_mc(uint32_t dst, const CUtensorMap* m, int c0, int c1, uint32_t bar) {
  asm volatile("cp.async.bulk.tensor.2d.shared::cluster.global.mbarrier::complete_tx::bytes.multicast::cluster [%0], [%1, {%3, %4}], [%2], %5;"
    :: "r"(dst), "l"(m), "r"(bar), "r"(c0), "r"(c1), "h"((uint16_t)3) : "memory");
}
__device__ __forceinline__ void tma_ld_mc_hint(uint32_t dst, const CUtensorMap* m, int c0, int c1, uint32_t bar, uint64_t pol) {
  asm volatile("cp.async.bulk.tensor.2d.shared::cluster.global.mbarrier::complete_tx::bytes.multicast::cluster.L2::cache_hint [%0], [%1, {%3, %4}], [%2], %5, %6;"
    :: "r"(dst), "l"(m), "r"(bar), "r"(c0), "r"(c1), "h"((uint16_t)3), "l"(pol) : "memory");
}
__device__ __forceinline__ void tma_ld3_hint(uint32_t dst, const CUtensorMap* m, int row, int blk, uint32_t bar, uint64_t pol) {
  asm volatile("cp.async.bulk.tensor.3d.shared::cluster.global.mbarrier::complete_tx::bytes.L2::cache_hint [%0], [%1, {0, %3, %4}], [%2], %5;"
    :: "r"(dst), "l"(m), "r"(bar), "r"(row), "r"(blk), "l"(pol) : "memory");
}
__device__ __forceinline__ void tma_st(const CUtensorMap* m, int c0, int c1, uint32_t src) {
  asm volatile("cp.async.bulk.tensor.2d.global.shared::cta.bulk_group [%0, {%2, %3}], [%1];" :: "l"(m), "r"(src), "r"(c0), "r"(c1) : "memory");
}
__device__ __forceinline__ void tma_prefetch_desc(const CUtensorMap* m) { asm volatile("prefetch.tensormap [%0];" :: "l"(m) : "memory"); }
__device__ __forceinline__ void l2_prefetch(const void* p, uint32_t bytes) { asm volatile("cp.async.bulk.prefetch.L2.global [%0], %1;" :: "l"(p), "r"(bytes) : "memory"); }
__device__ __forceinline__ void bulk_commit() { asm volatile("cp.async.bulk.commit_group;" ::: "memory"); }
__device__ __forceinline__ void bulk_wait_read() { asm volatile("cp.async.bulk.wait_group.read 0;" ::: "memory"); }
__device__ __forceinline__ void bulk_wait_all() { asm volatile("cp.async.bulk.wait_group 0;" ::: "memory"); }
__device__ __forceinline__ void fence_async_smem() { asm volatile("fence.proxy.async.shared::cta;" ::: "memory"); }
__device__ __forceinline__ void fence_async_global() { asm volatile("fence.proxy.async.global;" ::: "memory"); }
__device__ __forceinline__ void fence_acquire_gpu() { asm volatile("fence.acquire.gpu;" ::: "memory"); }
__device__ __forceinline__ void fence_release_gpu() { asm volatile("fence.release.gpu;" ::: "memory"); }
__device__ __forceinline__ void st_async_f32x4(uint32_t cluster_addr, const float* v, uint32_t cluster_bar) {
  asm volatile("st.async.weak.shared::cluster.mbarrier::complete_tx::bytes.v4.f32 [%0], {%1,%2,%3,%4}, [%5];"
    :: "r"(cluster_addr), "f"(v[0]), "f"(v[1]), "f"(v[2]), "f"(v[3]), "r"(cluster_bar) : "memory");
}
__device__ __forceinline__ void nb_sync(int id, int n) { asm volatile("bar.sync %0, %1;" :: "r"(id), "r"(n) : "memory"); }
__device__ __forceinline__ void nb_arrive(int id, int n) { asm volatile("bar.arrive %0, %1;" :: "r"(id), "r"(n) : "memory"); }
__device__ __forceinline__ void wg_fence() { asm volatile("wgmma.fence.sync.aligned;" ::: "memory"); }
__device__ __forceinline__ void wg_commit() { asm volatile("wgmma.commit_group.sync.aligned;" ::: "memory"); }
template <int N> __device__ __forceinline__ void wg_wait() { asm volatile("wgmma.wait_group.sync.aligned %0;" :: "n"(N) : "memory"); }
template <int N> __device__ __forceinline__ void reg_fence(float* a) {
#pragma unroll
  for (int i = 0; i < N; i++) asm volatile("" : "+f"(a[i]) :: "memory");
}
template <int N> __device__ __forceinline__ void reg_fence(uint32_t* a) {
#pragma unroll
  for (int i = 0; i < N; i++) asm volatile("" : "+r"(a[i]) :: "memory");
}
__device__ __forceinline__ uint64_t mk_desc(uint32_t addr, uint32_t lbo) {
  return (uint64_t)((addr & 0x3FFFF) >> 4) | ((uint64_t)(lbo >> 4) << 16) | ((uint64_t)(1024 >> 4) << 32) | (1ull << 62);
}

__device__ __forceinline__ uint64_t policy_evict_first() { uint64_t pol; asm("createpolicy.fractional.L2::evict_first.b64 %0, 1.0;" : "=l"(pol)); return pol; }
__device__ __forceinline__ uint32_t ld_relaxed(const uint32_t* p) { uint32_t v; asm volatile("ld.relaxed.gpu.global.u32 %0, [%1];" : "=r"(v) : "l"(p) : "memory"); return v; }
__device__ __forceinline__ void st_relaxed(uint32_t* p, uint32_t v) { asm volatile("st.relaxed.gpu.global.u32 [%0], %1;" :: "l"(p), "r"(v) : "memory"); }
__device__ __forceinline__ void red_add_relaxed(uint32_t* p, uint32_t v) { asm volatile("red.relaxed.gpu.global.add.u32 [%0], %1;" :: "l"(p), "r"(v) : "memory"); }
__device__ __forceinline__ uint2 ld_pkt8(const uint2* p) {
  uint2 v; asm volatile("{\n.reg .b64 t;\nld.relaxed.gpu.global.b64 t, [%2];\nmov.b64 {%0,%1}, t;\n}" : "=r"(v.x), "=r"(v.y) : "l"(p) : "memory"); return v;
}
__device__ __forceinline__ void st_pkt8(uint2* p, uint32_t a, uint32_t b) {
  asm volatile("{\n.reg .b64 t;\nmov.b64 t, {%1,%2};\nst.relaxed.gpu.global.b64 [%0], t;\n}" :: "l"(p), "r"(a), "r"(b) : "memory");
}
__device__ __forceinline__ uint4 ld_pkt16(const uint4* p) {
  uint4 v; asm volatile("{\n.reg .b128 t;\n.reg .b64 a, b;\nld.relaxed.gpu.global.b128 t, [%4];\nmov.b128 {a, b}, t;\nmov.b64 {%0,%1}, a;\nmov.b64 {%2,%3}, b;\n}"
    : "=r"(v.x), "=r"(v.y), "=r"(v.z), "=r"(v.w) : "l"(p) : "memory"); return v;
}
__device__ __forceinline__ void st_pkt16(uint4* p, uint32_t x, uint32_t y, uint32_t z, uint32_t w) {
  asm volatile("{\n.reg .b128 t;\n.reg .b64 a, b;\nmov.b64 a, {%1,%2};\nmov.b64 b, {%3,%4};\nmov.b128 t, {a, b};\nst.relaxed.gpu.global.b128 [%0], t;\n}"
    :: "l"(p), "r"(x), "r"(y), "r"(z), "r"(w) : "memory");
}
__device__ __forceinline__ void cp_async16(uint32_t dst, const void* src) { asm volatile("cp.async.cg.shared.global [%0], [%1], 16;" :: "r"(dst), "l"(src) : "memory"); }
__device__ __forceinline__ void cp_async_wait() { asm volatile("cp.async.wait_all;" ::: "memory"); }
__device__ __forceinline__ uint32_t lds32(uint32_t a) { uint32_t v; asm volatile("ld.shared.u32 %0, [%1];" : "=r"(v) : "r"(a) : "memory"); return v; }
__device__ __forceinline__ float lds_f32(uint32_t a) { float v; asm volatile("ld.shared.f32 %0, [%1];" : "=f"(v) : "r"(a) : "memory"); return v; }
__device__ __forceinline__ uint2 lds64(uint32_t a) { uint2 v; asm volatile("ld.shared.v2.u32 {%0,%1}, [%2];" : "=r"(v.x), "=r"(v.y) : "r"(a) : "memory"); return v; }
__device__ __forceinline__ uint4 lds128(uint32_t a) { uint4 v; asm volatile("ld.shared.v4.u32 {%0,%1,%2,%3}, [%4];" : "=r"(v.x), "=r"(v.y), "=r"(v.z), "=r"(v.w) : "r"(a) : "memory"); return v; }
__device__ __forceinline__ void sts32(uint32_t a, uint32_t v) { asm volatile("st.shared.u32 [%0], %1;" :: "r"(a), "r"(v) : "memory"); }
__device__ __forceinline__ void sts64(uint32_t a, uint32_t x, uint32_t y) { asm volatile("st.shared.v2.u32 [%0], {%1,%2};" :: "r"(a), "r"(x), "r"(y) : "memory"); }
__device__ __forceinline__ void sts128(uint32_t a, uint32_t x, uint32_t y, uint32_t z, uint32_t w) { asm volatile("st.shared.v4.u32 [%0], {%1,%2,%3,%4};" :: "r"(a), "r"(x), "r"(y), "r"(z), "r"(w) : "memory"); }
__device__ __forceinline__ void stsm4(uint32_t a, uint32_t x, uint32_t y, uint32_t z, uint32_t w) {
  asm volatile("stmatrix.sync.aligned.m8n8.x4.shared.b16 [%0], {%1,%2,%3,%4};" :: "r"(a), "r"(x), "r"(y), "r"(z), "r"(w) : "memory");
}
__device__ __forceinline__ void ldsm4(uint32_t a, uint32_t* r) {
  asm volatile("ldmatrix.sync.aligned.m8n8.x4.shared.b16 {%0,%1,%2,%3}, [%4];" : "=r"(r[0]), "=r"(r[1]), "=r"(r[2]), "=r"(r[3]) : "r"(a) : "memory");
}
__device__ __forceinline__ void ldsm4t(uint32_t a, uint32_t* r) {
  asm volatile("ldmatrix.sync.aligned.m8n8.x4.trans.shared.b16 {%0,%1,%2,%3}, [%4];" : "=r"(r[0]), "=r"(r[1]), "=r"(r[2]), "=r"(r[3]) : "r"(a) : "memory");
}
__device__ __forceinline__ void mma16816(float* d, const uint32_t* a, uint32_t b0, uint32_t b1) {
  asm volatile("mma.sync.aligned.m16n8k16.row.col.f32.bf16.bf16.f32 {%0,%1,%2,%3}, {%4,%5,%6,%7}, {%8,%9}, {%0,%1,%2,%3};"
    : "+f"(d[0]), "+f"(d[1]), "+f"(d[2]), "+f"(d[3]) : "r"(a[0]), "r"(a[1]), "r"(a[2]), "r"(a[3]), "r"(b0), "r"(b1));
}
__device__ __forceinline__ void mma1688(float* d, uint32_t a0, uint32_t a1, uint32_t b0) {
  asm volatile("mma.sync.aligned.m16n8k8.row.col.f32.bf16.bf16.f32 {%0,%1,%2,%3}, {%4,%5}, {%6}, {%0,%1,%2,%3};"
    : "+f"(d[0]), "+f"(d[1]), "+f"(d[2]), "+f"(d[3]) : "r"(a0), "r"(a1), "r"(b0));
}
__device__ __forceinline__ uint32_t pack2(float lo, float hi) { uint32_t r; asm("cvt.rn.bf16x2.f32 %0, %1, %2;" : "=r"(r) : "f"(hi), "f"(lo)); return r; }
__device__ __forceinline__ float lo2f(uint32_t v) { return __uint_as_float(v << 16); }
__device__ __forceinline__ float hi2f(uint32_t v) { return __uint_as_float(v & 0xffff0000u); }
__device__ __forceinline__ uint32_t hmul2(uint32_t a, uint32_t b) { uint32_t r; asm("mul.rn.bf16x2 %0, %1, %2;" : "=r"(r) : "r"(a), "r"(b)); return r; }
__device__ __forceinline__ uint32_t hadd2(uint32_t a, uint32_t b) { uint32_t r; asm("add.rn.bf16x2 %0, %1, %2;" : "=r"(r) : "r"(a), "r"(b)); return r; }
__device__ __forceinline__ uint32_t hsub2(uint32_t a, uint32_t b) { uint32_t r; asm("sub.rn.bf16x2 %0, %1, %2;" : "=r"(r) : "r"(a), "r"(b)); return r; }
__device__ __forceinline__ uint32_t hfma2(uint32_t a, uint32_t b, uint32_t c) { uint32_t r; asm("fma.rn.bf16x2 %0, %1, %2, %3;" : "=r"(r) : "r"(a), "r"(b), "r"(c)); return r; }
__device__ __forceinline__ float rbf(float v) { return lo2f(pack2(v, 0.f)); }
__device__ __forceinline__ float ex2(float v) { float r; asm("ex2.approx.ftz.f32 %0, %1;" : "=f"(r) : "f"(v)); return r; }
__device__ __forceinline__ float rcp_f(float v) { float r; asm("rcp.approx.ftz.f32 %0, %1;" : "=f"(r) : "f"(v)); return r; }
__device__ __forceinline__ float sqrt_f(float v) { float r; asm("sqrt.approx.ftz.f32 %0, %1;" : "=f"(r) : "f"(v)); return r; }
__device__ __forceinline__ float sigmoid_f(float v) { return rcp_f(1.f + ex2(-1.4426950408889634f * v)); }
__device__ __forceinline__ float silu_f(float v) { return v * sigmoid_f(v); }
constexpr uint32_t ONE2 = 0x3f803f80u;

#define R8(a,o) "+f"(a[o+0]), "+f"(a[o+1]), "+f"(a[o+2]), "+f"(a[o+3]), "+f"(a[o+4]), "+f"(a[o+5]), "+f"(a[o+6]), "+f"(a[o+7])
#define R64(a,o) R8(a,o), R8(a,o+8), R8(a,o+16), R8(a,o+24), R8(a,o+32), R8(a,o+40), R8(a,o+48), R8(a,o+56)
#define D64 "{%0,%1,%2,%3,%4,%5,%6,%7,%8,%9,%10,%11,%12,%13,%14,%15,%16,%17,%18,%19,%20,%21,%22,%23,%24,%25,%26,%27,%28,%29,%30,%31," \
            "%32,%33,%34,%35,%36,%37,%38,%39,%40,%41,%42,%43,%44,%45,%46,%47,%48,%49,%50,%51,%52,%53,%54,%55,%56,%57,%58,%59,%60,%61,%62,%63"
#define D128 D64 ",%64,%65,%66,%67,%68,%69,%70,%71,%72,%73,%74,%75,%76,%77,%78,%79,%80,%81,%82,%83,%84,%85,%86,%87,%88,%89,%90,%91,%92,%93,%94,%95," \
            "%96,%97,%98,%99,%100,%101,%102,%103,%104,%105,%106,%107,%108,%109,%110,%111,%112,%113,%114,%115,%116,%117,%118,%119,%120,%121,%122,%123,%124,%125,%126,%127"

template <int TB> __device__ __forceinline__ void wgmma_ss128(float* d, uint64_t da, uint64_t db, int acc) {
  asm volatile("{\n.reg .pred p;\nsetp.ne.b32 p, %66, 0;\nwgmma.mma_async.sync.aligned.m64n128k16.f32.bf16.bf16 " D64 "}, %64, %65, p, 1, 1, 0, %67;\n}"
    : R64(d, 0) : "l"(da), "l"(db), "r"(acc), "n"(TB));
}
template <int TB> __device__ __forceinline__ void wgmma_rs128(float* d, const uint32_t* a, uint64_t db, int acc) {
  asm volatile("{\n.reg .pred p;\nsetp.ne.b32 p, %69, 0;\nwgmma.mma_async.sync.aligned.m64n128k16.f32.bf16.bf16 " D64 "}, {%64,%65,%66,%67}, %68, p, 1, 1, %70;\n}"
    : R64(d, 0) : "r"(a[0]), "r"(a[1]), "r"(a[2]), "r"(a[3]), "l"(db), "r"(acc), "n"(TB));
}
template <int TB> __device__ __forceinline__ void wgmma_ss256(float* d, uint64_t da, uint64_t db, int acc) {
  asm volatile("{\n.reg .pred p;\nsetp.ne.b32 p, %130, 0;\nwgmma.mma_async.sync.aligned.m64n256k16.f32.bf16.bf16 " D128 "}, %128, %129, p, 1, 1, 0, %131;\n}"
    : R64(d, 0), R64(d, 64) : "l"(da), "l"(db), "r"(acc), "n"(TB));
}

#define W8(a,o) "=f"(a[o+0]), "=f"(a[o+1]), "=f"(a[o+2]), "=f"(a[o+3]), "=f"(a[o+4]), "=f"(a[o+5]), "=f"(a[o+6]), "=f"(a[o+7])
#define W64(a,o) W8(a,o), W8(a,o+8), W8(a,o+16), W8(a,o+24), W8(a,o+32), W8(a,o+40), W8(a,o+48), W8(a,o+56)
template <int TB> __device__ __forceinline__ void wgmma_ss128_z(float* d, uint64_t da, uint64_t db) {
  asm volatile("wgmma.mma_async.sync.aligned.m64n128k16.f32.bf16.bf16 " D64 "}, %64, %65, 0, 1, 1, 0, %66;"
    : W64(d, 0) : "l"(da), "l"(db), "n"(TB));
}
template <int TB> __device__ __forceinline__ void wgmma_rs128_z(float* d, const uint32_t* a, uint64_t db) {
  asm volatile("wgmma.mma_async.sync.aligned.m64n128k16.f32.bf16.bf16 " D64 "}, {%64,%65,%66,%67}, %68, 0, 1, 1, %69;"
    : W64(d, 0) : "r"(a[0]), "r"(a[1]), "r"(a[2]), "r"(a[3]), "l"(db), "n"(TB));
}
template <int TB> __device__ __forceinline__ void wgmma_ss256_z(float* d, uint64_t da, uint64_t db) {
  asm volatile("wgmma.mma_async.sync.aligned.m64n256k16.f32.bf16.bf16 " D128 "}, %128, %129, 0, 1, 1, 0, %130;"
    : W64(d, 0), W64(d, 64) : "l"(da), "l"(db), "n"(TB));
}

template <int TB> __device__ __forceinline__ void wgmma_rs256(float* d, const uint32_t* a, uint64_t db) {
  asm volatile("wgmma.mma_async.sync.aligned.m64n256k16.f32.bf16.bf16 " D128 "}, {%128,%129,%130,%131}, %132, 1, 1, 1, %133;"
    : R64(d, 0), R64(d, 64) : "r"(a[0]), "r"(a[1]), "r"(a[2]), "r"(a[3]), "l"(db), "n"(TB));
}
template <int TB> __device__ __forceinline__ void wgmma_rs256_z(float* d, const uint32_t* a, uint64_t db) {
  asm volatile("wgmma.mma_async.sync.aligned.m64n256k16.f32.bf16.bf16 " D128 "}, {%128,%129,%130,%131}, %132, 0, 1, 1, %133;"
    : W64(d, 0), W64(d, 64) : "r"(a[0]), "r"(a[1]), "r"(a[2]), "r"(a[3]), "l"(db), "n"(TB));
}
#define D32 "{%0,%1,%2,%3,%4,%5,%6,%7,%8,%9,%10,%11,%12,%13,%14,%15,%16,%17,%18,%19,%20,%21,%22,%23,%24,%25,%26,%27,%28,%29,%30,%31}"
__device__ __forceinline__ void wgmma_rs64(float* d, const uint32_t* a, uint64_t db) {
  asm volatile("wgmma.mma_async.sync.aligned.m64n64k16.f32.bf16.bf16 " D32 ", {%32,%33,%34,%35}, %36, 1, 1, 1, 0;"
    : R8(d, 0), R8(d, 8), R8(d, 16), R8(d, 24) : "r"(a[0]), "r"(a[1]), "r"(a[2]), "r"(a[3]), "l"(db));
}
__device__ __forceinline__ void wgmma_rs64_z(float* d, const uint32_t* a, uint64_t db) {
  asm volatile("wgmma.mma_async.sync.aligned.m64n64k16.f32.bf16.bf16 " D32 ", {%32,%33,%34,%35}, %36, 0, 1, 1, 0;"
    : W8(d, 0), W8(d, 8), W8(d, 16), W8(d, 24) : "r"(a[0]), "r"(a[1]), "r"(a[2]), "r"(a[3]), "l"(db));
}
__device__ __forceinline__ void issue_qk(float* S, const uint32_t* Q, uint64_t dk) {
  wgmma_rs64_z(S, Q, dk);
#pragma unroll
  for (int kk = 1; kk < 8; kk++) wgmma_rs64(S, Q + 4 * kk, dk + (kk >> 2) * 512 + (kk & 3) * 2);
}
__device__ __forceinline__ void issue_pv(float* O, const uint32_t* P, uint64_t dv, int acc) {
#pragma unroll
  for (int kk = 0; kk < 4; kk++) wgmma_rs128<1>(O, P + 4 * kk, dv + kk * 128, kk ? 1 : acc);
}

#define TS(i)
#define TSC(i)
#define TSX(i)
#define TSY(k) do { if ((tid & 127) == 0) TS((k) + 40 * wg); } while (0)
#define TT(k)
#define TV(k)
#define TR(k)
#define TQ(k)
#define TH(k)
#define TA(k)
#define TAFLUSH()

struct SoftmaxState { float c0, c1, l0, l1; bool shifted; };
constexpr float SM_SCALE = 0.08838834764831845f * 1.4426950408889634f;
__device__ __forceinline__ void softmax_start(SoftmaxState& z) { z.c0 = z.c1 = z.l0 = z.l1 = 0.f; z.shifted = false; }
__device__ __forceinline__ void softmax_half(float* S, uint32_t* P, float* O, SoftmaxState& z, bool first, uint32_t tag) {
  const float lo0 = z.l0, lo1 = z.l1;
  float lim = 1.2676506002282294e30f;
  const float low = first ? 8.673617379884035e-19f : 0.f;
  if (z.shifted) {
#pragma unroll
    for (int j = 0; j < 32; j++) S[j] += (j & 2) ? z.c1 : z.c0;
  }
#pragma unroll 1
  while (true) {
    bb_fence(tag);
#pragma unroll
    for (int j = 0; j < 8; j++) {
      const float p0 = ex2(S[4 * j]), p1 = ex2(S[4 * j + 1]), p2 = ex2(S[4 * j + 2]), p3 = ex2(S[4 * j + 3]);
      z.l0 += p0; z.l1 += p2; z.l0 += p1; z.l1 += p3;
      P[2 * j] = pack2(p0, p1); P[2 * j + 1] = pack2(p2, p3);
    }
    if (!__any_sync(0xffffffffu, !(z.l0 < lim && z.l1 < lim && fminf(z.l0, z.l1) >= low) && lim > 0.f)) break;
    float d0 = fmaxf(S[0], S[1]), d1 = fmaxf(S[2], S[3]);
#pragma unroll
    for (int j = 1; j < 8; j++) { d0 = fmaxf(d0, fmaxf(S[4 * j], S[4 * j + 1])); d1 = fmaxf(d1, fmaxf(S[4 * j + 2], S[4 * j + 3])); }
    d0 = fmaxf(d0, __shfl_xor_sync(0xffffffffu, d0, 1)); d1 = fmaxf(d1, __shfl_xor_sync(0xffffffffu, d1, 1));
    d0 = fmaxf(d0, __shfl_xor_sync(0xffffffffu, d0, 2)); d1 = fmaxf(d1, __shfl_xor_sync(0xffffffffu, d1, 2));
    if (!first) { d0 = fmaxf(d0, 0.f); d1 = fmaxf(d1, 0.f); }
    z.shifted = true;
    z.c0 -= d0; z.c1 -= d1;
#pragma unroll
    for (int j = 0; j < 32; j++) S[j] -= (j & 2) ? d1 : d0;
    const float a0 = first ? 1.f : ex2(-d0), a1 = first ? 1.f : ex2(-d1);
    z.l0 = lo0 * a0; z.l1 = lo1 * a1;
    lim = -1.f;
    wg_wait<0>();
    reg_fence<64>(O);
#pragma unroll
    for (int j = 0; j < 16; j++) { O[4 * j] *= a0; O[4 * j + 1] *= a0; O[4 * j + 2] *= a1; O[4 * j + 3] *= a1; }
  }
}

__device__ __forceinline__ void modulate_frags(uint32_t* A, const uint32_t* V, const uint4* R, const uint32_t* ln) {
#pragma unroll
  for (int kk = 0; kk < 4; kk++) {
    const uint4 sa = R[kk >> 1], c1 = R[2 + (kk >> 1)];
#pragma unroll
    for (int j = 0; j < 4; j++) {
      const uint32_t n = hfma2(V[4 * kk + j], ln[(j & 1) * 2 + 1], ln[(j & 1) * 2]);
      A[4 * kk + j] = (kk & 1) ? ((j & 2) ? hfma2(n, c1.w, sa.x) : hfma2(n, c1.z, sa.w)) : ((j & 2) ? hfma2(n, c1.y, sa.z) : hfma2(n, c1.x, sa.y));
    }
  }
}
__device__ __forceinline__ void publish_record(uint4* dst, uint32_t pk, int src, int vec, bool doit) {
  const int r = vec ? 0 : 12;
  const uint32_t x = __shfl_sync(0xffffffffu, pk, src + r), y = __shfl_sync(0xffffffffu, pk, src + ((r + 4) & 12));
  const uint32_t z = __shfl_sync(0xffffffffu, pk, src + ((r + 8) & 12)), w = __shfl_sync(0xffffffffu, pk, src + ((r + 12) & 12));
  if (doit) st_pkt16(dst, ~x, y, z, w);
}
__device__ __forceinline__ void put_record(uint32_t sb, int idx, const uint4& v) {
  sts128(sb + SM_STASH + idx * 16, ~v.x, v.y, v.z, v.w);
  sts128(sb + SM_STASH + 16384 + idx * 16, ~v.x, v.y, v.z, v.w);
}
__device__ __forceinline__ float mod_value(float v, int vec) {
  v = rbf(v);
  return (vec ? rbf(1.f + v) : v) * SM_SCALE;
}

__device__ __forceinline__ void row_rcp(float& l0, float& l1) {
  l0 += __shfl_xor_sync(0xffffffffu, l0, 1); l1 += __shfl_xor_sync(0xffffffffu, l1, 1);
  l0 += __shfl_xor_sync(0xffffffffu, l0, 2); l1 += __shfl_xor_sync(0xffffffffu, l1, 2);
  l0 = rcp_f(l0); l1 = rcp_f(l1);
}
__device__ __forceinline__ void stage_o(const float* O, float r0, float r1, uint32_t stsm_addr) {
#pragma unroll
  for (int kk = 0; kk < 8; kk++) {
    stsm4((stsm_addr + (kk >> 2) * 8192) ^ ((kk & 3) * 32),
          pack2(O[8 * kk + 0] * r0, O[8 * kk + 1] * r0), pack2(O[8 * kk + 2] * r1, O[8 * kk + 3] * r1),
          pack2(O[8 * kk + 4] * r0, O[8 * kk + 5] * r0), pack2(O[8 * kk + 6] * r1, O[8 * kk + 7] * r1));
  }
}

__global__ void __cluster_dims__(2, 1, 1) __launch_bounds__(NTHREADS, 1)
fused_kernel(const Params p, const __grid_constant__ CUtensorMap mH, const __grid_constant__ CUtensorMap mWq,
             const __grid_constant__ CUtensorMap mK, const __grid_constant__ CUtensorMap mV,
             const __grid_constant__ CUtensorMap mO, const __grid_constant__ CUtensorMap mWo,
             const __grid_constant__ CUtensorMap mX, const __grid_constant__ CUtensorMap mOut,
             const __grid_constant__ CUtensorMap mWg, const __grid_constant__ CUtensorMap mWu,
             const __grid_constant__ CUtensorMap mWd, const __grid_constant__ CUtensorMap mWm,
             const __grid_constant__ CUtensorMap mWs, const __grid_constant__ CUtensorMap mWh,
             const __grid_constant__ CUtensorMap mOs) {
  extern __shared__ __align__(1024) uint8_t smem_raw[];
  TH(0);
  const uint32_t sb = smem_u32(smem_raw);
  const int tid = threadIdx.x;
  const int b0 = blockIdx.x;
  const int lane = tid & 31;
  const int role = __shfl_sync(0xffffffffu, tid >> 8, 0);

  if (b0 >= NMAIN) {
    const uint32_t cs = clock();
    const uint32_t tag = ld_relaxed(&g_epoch) + 1;
    const int sp = b0 - NMAIN, vec = 2 + sp;
    const int warp = __shfl_sync(0xffffffffu, tid >> 5, 0);
    float* sc = reinterpret_cast<float*>(smem_raw + SM_STASH);
    float* red = reinterpret_cast<float*>(smem_raw + SM_STASH + 4096);
    const int ridx = (lane >> 3) * 2 * RV + (sp & 1) * RV + 16 * RS + (sp >> 1) * 16 + (warp & 1) * 8 + (lane & 7);
    if (warp < 8) st_pkt16(&g_rec[warp >> 2][0][ridx + (warp & 2) * 16], 0, 0, 0, 0);
#pragma unroll 1
    for (int i = tid; i < 1024; i += NTHREADS) sc[i] = rbf(silu_f(__bfloat162float(p.c[i])));
    if (tid == 0) {
      tma_prefetch_desc(&mWs);
      for (int s = 0; s < NST2; s++) { mbar_init(sb + BAR_FULL2 + 8 * s, 1); mbar_init(sb + BAR_EMPTY2 + 8 * s, 8); }
      fence_async_smem();
      while ((uint32_t)clock() - cs < SPT) {}
    }
    __syncthreads();
    int s = 0; uint32_t ph = 0;
    if (tid == 0) TS(0);
    if (warp == 8) {
      const uint64_t pol = policy_evict_first();
#pragma unroll 1
      for (int n = 0; n < 80; n++) {
        mbar_wait_g(sb + BAR_EMPTY2 + 8 * s, ph ^ 1);
        if (elect_one()) {
          mbar_expect_tx(sb + BAR_FULL2 + 8 * s, 32768);
          if (n < 16) {
            tma_ld_hint(sb + s * ST2, &mWs, (sp & 1) * 1024 + 512 + (n >> 3) * 256 + (sp >> 1) * 128, (n & 7) * 128, sb + BAR_FULL2 + 8 * s, pol);
          } else {
#pragma unroll
            for (int j = 0; j < 4; j++) tma_ld_hint(sb + s * ST2 + j * 8192, &mWm, vec * 1024 + j * 256, (n - 16) * 16, sb + BAR_FULL2 + 8 * s, pol);
          }
        }
        __syncwarp();
        if (++s == NST2) { s = 0; ph ^= 1; }
      }
    } else if (warp < 8) {
      float acc[8];
#pragma unroll
      for (int i = 0; i < 8; i++) acc[i] = 0.f;
      auto stage = [&](uint32_t a0, int da, const float* cp, int dc) {
        mbar_wait_g(sb + BAR_FULL2 + 8 * s, ph);
#pragma unroll
        for (int i = 0; i < 8; i++) {
          const uint4 v = lds128(a0 + s * ST2 + i * da);
          const float c = cp[i * dc];
          acc[0] = fmaf(lo2f(v.x), c, acc[0]); acc[1] = fmaf(hi2f(v.x), c, acc[1]);
          acc[2] = fmaf(lo2f(v.y), c, acc[2]); acc[3] = fmaf(hi2f(v.y), c, acc[3]);
          acc[4] = fmaf(lo2f(v.z), c, acc[4]); acc[5] = fmaf(hi2f(v.z), c, acc[5]);
          acc[6] = fmaf(lo2f(v.w), c, acc[6]); acc[7] = fmaf(hi2f(v.w), c, acc[7]);
        }
        if (__shfl_sync(0xffffffffu, lane, __float_as_uint(acc[7]) & 31) < 32 && lane == 0) mbar_arrive(sb + BAR_EMPTY2 + 8 * s);
        if (++s == NST2) { s = 0; ph ^= 1; }
      };
#pragma unroll 1
      for (int n = 0; n < 16; n++) {
        stage(sb + tid * 16, 4096, sc + (n & 7) * 128 + (tid >> 4), 16);
        if ((n & 7) == 7) {
          float* r2 = red + 2048 + (n & 8) * 256;
#pragma unroll
          for (int i = 0; i < 8; i++) { r2[tid * 8 + i] = acc[i]; acc[i] = 0.f; }
          nb_sync(NB_CONS, 256);
          if (warp < 2) {
            float v0 = 0.f, v1 = 0.f;
#pragma unroll 4
            for (int i = 0; i < 16; i++) { const float2 e = reinterpret_cast<const float2*>(r2)[i * 64 + tid]; v0 += e.x; v1 += e.y; }
            publish_record(&g_rec[tag & 1][0][ridx + (n >> 3) * 32], pack2(mod_value(v0, sp & 1), mod_value(v1, sp & 1)),
                           (lane & 4) * 4 + (lane & 3), sp & 1, true);
          }
          if (tid == 0) TS(1 + (n >> 3));
        }
      }
#pragma unroll 1
      for (int n = 0; n < 64; n++) {
        stage(sb + ((tid >> 5) & 3) * 8192 + (tid >> 7) * 4096 + (tid & 31) * 16, 512, sc + n * 16 + (tid >> 7) * 8, 1);
      }
#pragma unroll
      for (int i = 0; i < 8; i++) red[(tid >> 7) * 1024 + (tid & 127) * 8 + i] = acc[i];
    }
    __syncthreads();
    float dot = 0.f;
#pragma unroll 1
    for (int i = tid; i < 512; i += NTHREADS) {
      uint32_t v = pack2(red[2 * i] + red[1024 + 2 * i], red[2 * i + 1] + red[1024 + 2 * i + 1]);
      st_pkt8(&g_mod[vec * 512 + i], v, tag);
      if (vec == 4) v = hadd2(v, ONE2);
      const uint32_t wr = reinterpret_cast<const uint32_t*>(p.w_r)[i];
      dot = fmaf(lo2f(v), lo2f(wr), fmaf(hi2f(v), hi2f(wr), dot));
    }
#pragma unroll
    for (int o = 16; o; o >>= 1) dot += __shfl_xor_sync(0xffffffffu, dot, o);
    if (lane == 0) sc[warp] = dot;
    __syncthreads();
    if (tid == 0) {
      dot = 0.f;
      for (int w = 0; w < 12; w++) dot += sc[w];
      fence_release_gpu();
      st_pkt8(&g_vdone[(vec - 2) * 16], __float_as_uint(dot), tag);
      TS(11);
#pragma unroll 1
      for (int i = 0; i < 128; i++) {
        const int u = i * 4 + (b0 - NMAIN);
        l2_prefetch(p.wo + (size_t)((4 * ((u >> 4) & 7) + (u >> 7)) * 128 + (u & 15) * 8) * 1024, 16384);
        __nanosleep(PFW);
      }
    }
    return;
  }

  const uint32_t rank = b0 & 1;
  const bool slab = !(b0 & 32), late = b0 & 16;
  const uint32_t c0 = clock();
  if (tid == 352) TS(0);
  const uint32_t slab_addr = sb + SM_WSLAB + (tid >> 5) * 4096 + (lane & 3) * 128 + (lane & 4) * 16 + (((lane >> 3) ^ lane) & 3) * 16;
  auto load_slab = [&]() {
    const bf16* wp = p.w_mod + (size_t)(512 * rank + 2 * (tid & ~31) + 2 * (lane & 3) + ((lane >> 2) & 1)) * 6144 + 32 * (b0 >> 1) + 8 * (lane >> 3);
    const uint64_t pef = policy_evict_first();
#pragma unroll
    for (int i = 0; i < 8; i++)
      asm volatile("cp.async.cg.shared.global.L2::cache_hint [%0], [%1], 16, %2;"
        :: "r"(slab_addr + i * 512), "l"(wp + (size_t)i * 8 * 6144), "l"(pef) : "memory");
  };
  if (tid == 256) {
    mbar_init(sb + BAR_XH, 1);
    fence_async_smem();
    mbar_expect_tx(sb + BAR_XH, 32768);
#pragma unroll
    for (int i = 0; i < 2; i++)
      asm volatile("cp.async.bulk.shared::cluster.global.mbarrier::complete_tx::bytes [%0], [%1], 16384, [%2];"
        :: "r"(sb + SM_XROW + i * ST1), "l"(p.x + (size_t)b0 * 16384 + i * 8192), "r"(sb + BAR_XH) : "memory");
  }
  __syncwarp();
  uint32_t cw[8];
#pragma unroll
  for (int i = 0; i < 8; i++) cw[i] = 0;
  if (!role && slab) {
#pragma unroll
    for (int i = 0; i < 8; i++) cw[i] = ld_relaxed(reinterpret_cast<const uint32_t*>(p.c) + 256 * rank + (tid & ~28) + 4 * i);
  }
  uint32_t epoch = 0;
  if (!role) epoch = ld_relaxed(&p.sc->epoch[lane]);
  if (!role && slab && !late) load_slab();
#define TILE_ROLES() \
  mbar_wait(sb + BAR_ROLE, 0); \
  const int b = 2 * __shfl_sync(0xffffffffu, lds32(sb + SM_ROLE), 0) + rank; \
  const int rt = b >> 3;     \
  const int ct = b & 7;

  if (role) {
    asm volatile("setmaxnreg.dec.sync.aligned.u32 24;");
    const int warp = __shfl_sync(0xffffffffu, tid >> 5, 0);
    if (tid == 256) {
      mbar_init(sb + BAR_RED, 1); mbar_init(sb + BAR_WH, 1);
      for (int s = 0; s < 2; s++) mbar_init(sb + BAR_OF + 8 * s, 1);
      mbar_init(sb + BAR_ROLE, 1);
      for (int s = 0; s < 5; s++) { mbar_init(sb + BAR_FULL1 + 8 * s, 1); mbar_init(sb + BAR_EMPTY1 + 8 * s, 4); }
      for (int s = 0; s < 2; s++) { mbar_init(sb + BAR_STASH + 8 * s, 1); mbar_init(sb + BAR_X + 8 * s, 1); }
      for (int s = 0; s < 4; s++) mbar_init(sb + BAR_HS + 8 * s, 1);
      mbar_init(sb + BAR_G, 16); mbar_init(sb + BAR_T1, 1); mbar_init(sb + BAR_HF, 1);
      mbar_init(sb + BAR_SFREE, 4); mbar_init(sb + BAR_TFREE, 8);
      mbar_init(sb + BAR_FFN, 4); mbar_init(sb + BAR_FFN + 8, 2);
      mbar_init(sb + BAR_CAND, 1); mbar_init(sb + BAR_VEC, 32); for (int s = 0; s < 3; s++) mbar_init(sb + BAR_TAB + 8 * s, 32);
      mbar_expect_tx(sb + BAR_RED, 1024);
      mbar_expect_tx(sb + BAR_ROLE, 4);
      asm volatile("fence.mbarrier_init.release.cluster;" ::: "memory");
    }
    __syncwarp();
    asm volatile("barrier.cluster.arrive.relaxed.aligned;" ::: "memory");
    const int ridx = ((lane >> 1) & 3) * 2 * RV + (b0 >> 6) * RV + ((b0 >> 1) & 31) * RS + 2 * rank + (lane & 1) + (lane >> 3) * 4;
    if (warp == 11 && slab && lane < 2 * RS) { st_pkt16(&g_rec[0][0][ridx], 0, 0, 0, 0); st_pkt16(&g_rec[1][0][ridx], 0, 0, 0, 0); }
    if (tid == 256) {
      tma_prefetch_desc(&mWq); tma_prefetch_desc(&mX); tma_prefetch_desc(&mH); tma_prefetch_desc(&mK); tma_prefetch_desc(&mV); tma_prefetch_desc(&mOs);
    }
    uint32_t pairid = 0;
    if (tid == 320 && rank == 0) {
      uint32_t t;
      asm("mov.u32 %0, %%smid;" : "=r"(t));
      t >>= 1;
      uint32_t grp = ((0x73216540u >> (4 * ((t < 32 ? t : t < 60 ? 1 + (t - 32) % 7 : t < 62 ? t - 54 : 0) & 7))) & 7) - 1, slot;
      int it = 0;
      do {
        grp = (grp + 1) & 7;
        asm volatile("atom.relaxed.gpu.global.add.u32 %0, [%1], 1;" : "=r"(slot) : "l"(&p.sc->ticket[grp * 32]) : "memory");
        spin_guard(it);
      } while (slot >= 8);
      pairid = slot * 8 + grp;
    }
    __syncwarp();
    asm volatile("barrier.cluster.wait.aligned;" ::: "memory");
    if (tid == 320 && rank == 0) {
#pragma unroll
      for (int r = 0; r < 2; r++)
        asm volatile("st.async.weak.shared::cluster.mbarrier::complete_tx::bytes.b32 [%0], %1, [%2];"
          :: "r"(mapa(sb + SM_ROLE, r)), "r"(pairid), "r"(mapa(sb + BAR_ROLE, r)) : "memory");
    }
    __syncwarp();
    const uint32_t tag = ld_relaxed(&g_epoch) + 1;
    if (warp == 8) {
      TILE_ROLES();
      const int kvrow = (ct >> 1) * 2048 + 1536, arow = rt * 128 + rank * 64;
      const uint64_t pef = policy_evict_first();
#pragma unroll 1
      for (int pair = 0; pair < 2; pair++) {
        const int wblk = (4 * ct + 2 * pair) * 2;
        if (pair) { mbar_wait_g(sb + BAR_HF, 0); fence_async_global(); }
#pragma unroll 1
        for (int n = 0; n < 16; n++) {
          const uint32_t s = n & 3, st = sb + SM_RING + s * ST1, fb = sb + BAR_FULL1 + 8 * s;
          if (n == 2 && pair == 0) mbar_wait_g(sb + BAR_G, 0);
          mbar_wait_g(fb + (BAR_EMPTY1 - BAR_FULL1), ((n >> 2) & 1) ^ 1);
          if (elect_one()) {
            mbar_expect_tx(fb, 49152);
            if (pair) tma_ld_mc_hint(st + rank * 8192, &mH, n * 64, arow, fb, pef); else
            tma_ld_mc(st + rank * 8192, pair ? &mH : &mX, n * 64, arow, fb);
            tma_ld3_hint(st + 16384, &mWq, n * 64, wblk, fb, pef);
          }
          __syncwarp();
        }
#pragma unroll 1
        for (int n = 0; n < 16; n++) {
          const uint32_t s = n & 3, st = sb + SM_RING + s * ST1 + rank * 8192, fb = sb + BAR_FULL1 + 8 * s;
          const int h0 = n == 0 ? 0 : n == 15 ? 14 : n + 1, h1 = n == 0 ? 1 : n == 15 ? 15 : n - 1;
          mbar_wait_g(fb + (BAR_EMPTY1 - BAR_FULL1), ((n >> 2) & 1) ^ 1);
          if (elect_one()) {
            mbar_expect_tx(fb, 32768);
            tma_ld_mc(st, n == 15 ? &mV : &mK, rank * 64, kvrow + (h0 & 7) * 64, fb);
            tma_ld_mc(st + 16384, n == 0 ? &mK : &mV, rank * 64, kvrow + (h1 & 7) * 64, fb);
            if (n == 3 && pair == 1) mbar_arrive(sb + BAR_T1);
          }
          __syncwarp();
        }
      }
      {
        uint32_t s = 0, ph = 1;
#pragma unroll 1
        for (int half = 0; half < 2; half++) {
          mbar_wait_g(sb + BAR_OF + 8 * half, 0);
          fence_async_global();
#pragma unroll 1
          for (int n = 32 * half; n < 32 * half + 32; n++) {
            const uint32_t st = sb + SM_RING + s * ST1, fb = sb + BAR_FULL1 + 8 * s;
            const int k0 = ((n & 14) * 2 + (n >> 4)) * 128 + (n & 1) * 64;
            mbar_wait_g(n == 8 ? sb + BAR_SFREE : fb + (BAR_EMPTY1 - BAR_FULL1), n == 8 ? 0 : ph ^ (s >> 2));
            if (elect_one()) {
              mbar_expect_tx(fb, 32768);
              tma_ld_mc_hint(st + rank * 8192, &mO, k0, arow, fb, pef);
              tma_ld3_hint(st + 16384, &mWo, k0, 2 * ct, fb, pef);
            }
            __syncwarp();
            if (++s == 5 || n == 3) { s = 0; ph ^= 1; }
          }
        }
        if (b < NFFN) {
#pragma unroll 1
          for (s = 0; s < 2; s++) {
            mbar_wait_g(sb + BAR_EMPTY1 + 8 * s, 0);
            if (elect_one()) {
              mbar_expect_tx(sb + BAR_FFN + 8, 32768);
              tma_ld3_hint(sb + SM_RING + s * ST1, &mWd, b * 32, s * 8, sb + BAR_FFN + 8, pef);
            }
            __syncwarp();
          }
        }
      }
    } else if (warp <= 10) {
      const int w = warp - 9;
      if (slab && late && w == 0 && lane == 0) {
        tma_prefetch_desc(&mWh);
        mbar_expect_tx(sb + BAR_WH, 32768);
        while ((uint32_t)clock() - c0 < WL) {}
        const uint64_t pef = policy_evict_first();
#pragma unroll
        for (int i = 0; i < 2; i++) tma_ld_hint(sb + SM_WSLAB + i * 16384, &mWh, 32 * (b0 >> 1), 512 * rank + 256 * i, sb + BAR_WH, pef);
      }
      __syncwarp();
      TILE_ROLES();
      const uint32_t st = sb + SM_STASH + w * 16384;
#pragma unroll 1
      for (int j = 0; j < 2; j++) {
        nb_sync(NB_OST + w, 160);
        if (elect_one()) {
          fence_async_smem();
          tma_st(&mH, (2 * ct + j) * 64, rt * 128 + w * 64, st + 4096);
          bulk_commit();
          bulk_wait_read();
          mbar_arrive(sb + BAR_HS + 16 * w + 8 * j);
          if (j) {
            bulk_wait_all();
            fence_async_global();
            fence_release_gpu();
            red_add_relaxed(&g_hflag[rt * 32], 1);
          }
        }
        __syncwarp();
      }
#pragma unroll 1
      for (int r = 0; r < 4; r++) {
        nb_sync(NB_OST + w, 160);
        if (elect_one()) {
          fence_async_smem();
          const int hcol = (4 * ct + r) * 128;
#pragma unroll 1
          for (int i = 0; i < 8; i++) {
            tma_st(&mOs, hcol + (i & 4) * 16, rt * 128 + w * 64 + (i & 3) * 16, st + i * 2048);
            __nanosleep(r == 3 ? OP3 : OP0);
          }
          bulk_commit();
          bulk_wait_read();
          if (r < 2) {
            mbar_arrive(sb + BAR_STASH + 8 * w);
          } else if (r == 2) {
            mbar_expect_tx(sb + BAR_X + 8 * w, 16384);
            tma_ld_hint(st, &mX, ct * 128, rt * 128 + w * 64, sb + BAR_X + 8 * w, policy_evict_first());
            tma_ld_hint(st + 8192, &mX, ct * 128 + 64, rt * 128 + w * 64, sb + BAR_X + 8 * w, policy_evict_first());
          } else {
            mbar_arrive_cl(mapa(sb + BAR_SFREE, 0)); mbar_arrive_cl(mapa(sb + BAR_SFREE, 1));
          }
          bulk_wait_all();
          fence_async_global();
          fence_release_gpu();
          red_add_relaxed(&g_oflag[(rt * 4 + r) * 32], 1);
        }
        __syncwarp();
      }
      nb_sync(NB_OST + w, 160);
      int skip = -1;
      mbar_wait_g(sb + BAR_CAND, 0);
      const bool has_cand = (lds32(sb + SM_CAND) >> 6) == w;
      if (has_cand) {
        nb_sync(NB_WIN + w, 160);
        skip = (int)lds32(sb + SM_WROW + 4 * w) - (rt * 128 + w * 64);
      }
      if ((unsigned)skip >= 64u) {
        if (elect_one()) {
          fence_async_smem();
          tma_st(&mOut, ct * 128, rt * 128 + w * 64, sb + SM_OUT + w * 16384);
          tma_st(&mOut, ct * 128 + 64, rt * 128 + w * 64, sb + SM_OUT + w * 16384 + 8192);
          bulk_commit();
          bulk_wait_read();
        }
        __syncwarp();
      } else {
        uint4* dst = reinterpret_cast<uint4*>(p.out + (size_t)(rt * 128 + w * 64 + (lane >> 4)) * 1024 + ct * 128) + (lane & 15);
#pragma unroll 2
        for (int r = lane >> 4; r < 64; r += 2) {
          const uint4 v = lds128(sb + SM_OUT + w * 16384 + ((lane >> 3) & 1) * 8192 + r * 128 + (((lane ^ r) & 7) * 16));
          if (r != skip) *dst = v;
          dst += 256;
        }
      }
      if (!has_cand) nb_sync(NB_WIN + w, 160);
    } else {
      if (slab) {
        mbar_wait_g(sb + BAR_RED, 0);
        float v = 0.f;
#pragma unroll
        for (int w = 0; w < 8; w++) v += lds_f32(sb + SM_RED + w * 128 + lane * 4);
        v += __shfl_xor_sync(0xffffffffu, v, 16);
        v = mod_value(v, b0 >> 6);
        publish_record(&g_rec[tag & 1][0][ridx], pack2(v, __shfl_down_sync(0xffffffffu, v, 1)), 2 * (lane & 1), b0 >> 6, lane < 8);
        if (lane == 0) TS(1);
      }
      mbar_wait_g(sb + BAR_G, 0);
#pragma unroll 1
      for (int i = 1; i < 4; i++) {
        const uint4* mp = &g_rec[tag & 1][(b0 >> 1) & (NREP - 1)][i == 1 ? (8 + (lane >> 2)) * RS + (lane & 3) : 16 * RS - 64 + 32 * i + lane];
        uint4 v0, v1; int it = 0;
        while (true) {
          v0 = ld_pkt16(mp); v1 = ld_pkt16(mp + RV);
          if (v0.x != 0 && v1.x != 0) break;
          spin_guard(it); __nanosleep(PLD);
        }
        put_record(sb, 32 * i + lane, v0);
        put_record(sb, 128 + 32 * i + lane, v1);
        mbar_arrive(sb + BAR_TAB - 8 + 8 * i);
        if (lane == 0) {
          TS(3 + i + (i > 2));
          if (i == 1) l2_prefetch(((b0 & 64) ? p.vc : p.kc) + (size_t)(((b0 >> 4) & 3) * 2048 + 1536) * 128 + (b0 & 15) * 4096, 8192);
        }
        __syncwarp();
      }
      TILE_ROLES();
      if (lane == 0) {
        int it = 0;
        do { __nanosleep(500); spin_guard(it); } while (ld_relaxed(&g_hflag[rt * 32]) != tag * 16u);
        fence_acquire_gpu();
        mbar_arrive(sb + BAR_HF);
        if (b < NFFN) for (int i = 0; i < 8; i++) { __nanosleep(800); l2_prefetch(p.wd + (size_t)(b * 32 + i * 4) * 1024, 8192); }
      }
      __syncwarp();
      {
        uint2 v; int it = 0;
        do { __nanosleep(1000); v = ld_pkt8(&g_vdone[(lane & 3) * 16]); spin_guard(it); }
        while (!(v.y == tag));
        __syncwarp();
        fence_acquire_gpu();
        if (lane == 1 || lane == 2) sts32(sb + SM_SCAL + (2 - lane) * 4, v.x);
      }
#pragma unroll 1
      for (int i = 0; i < 2; i++) {
        const int q = i * 32 + lane, pi = ct * 64 + q;
        const uint32_t vga = g_mod[2 * 512 + pi].x, vsb = g_mod[3 * 512 + pi].x, vcb = g_mod[4 * 512 + pi].x, vgb = g_mod[5 * 512 + pi].x;
        const uint32_t wr = reinterpret_cast<const uint32_t*>(p.w_r)[pi];
        const uint32_t c1 = hadd2(vcb, ONE2);
        const float al = lo2f(c1) * lo2f(wr), ah = hi2f(c1) * hi2f(wr);
        const uint32_t o8 = (q & 3) * 8 + ((q >> 2) & 1) * 4;
        sts32(sb + SM_GA + (q >> 3) * 32 + o8, vga);
        sts128(sb + SM_REC + q * 16, c1, vsb, vgb, 0);
        const uint32_t ahi = pack2(al, ah), alo = pack2(al - lo2f(ahi), ah - hi2f(ahi));
        const uint32_t ba = sb + SM_B1 + (q >> 3) * 128 + o8;
        sts32(ba, ONE2); sts32(ba + 32, ahi); sts32(ba + 64, alo); sts32(ba + 96, 0);
      }
      if (lane == 0) TS(28);
      if (lane == 0) {
        tma_prefetch_desc(&mWo); tma_prefetch_desc(&mO); tma_prefetch_desc(&mOut); tma_prefetch_desc(&mWd); tma_prefetch_desc(&mWg); tma_prefetch_desc(&mWu);
#pragma unroll 1
        for (int r = 0; r < 4; r++) {
          int it = 0;
          do { __nanosleep(200); spin_guard(it); } while (ld_relaxed(&g_oflag[(rt * 4 + r) * 32]) != tag * 16u);
          if (r & 1) { fence_acquire_gpu(); mbar_arrive(sb + BAR_OF + 8 * (r >> 1)); }
          if (r == 1 && b < NFFN) {
            const uint64_t pef = policy_evict_first();
            mbar_wait_g(sb + BAR_T1, 0);
#pragma unroll 1
            for (int i = 0; i < 4; i++) {
              mbar_expect_tx(sb + BAR_FFN, 16384);
              tma_ld_hint(sb + SM_RING + i * ST1 + 32768, &mWg, b * 32, i * 256, sb + BAR_FFN, pef);
              __nanosleep(GATED);
            }
          }
        }
      }
      __syncwarp();
      if (b < NFFN) {
        mbar_wait_g(sb + BAR_TFREE, 0);
        const uint64_t pef = policy_evict_first();
#pragma unroll 1
        for (int i = 0; i < 5; i++) {
          if (i > 0 && lane == 0) {
            mbar_expect_tx(sb + BAR_FFN, 16384);
            tma_ld_hint(sb + SM_RING + (i - 1) * ST1 + 32768, &mWu, b * 32, (i - 1) * 256, sb + BAR_FFN, pef);
          }
          if (i < 4) {
#pragma unroll 1
            for (int j = 0; j < 8; j++) {
              asm volatile("prefetch.global.L2 [%0];" :: "l"(p.wu + (size_t)(i * 256 + j * 32 + lane) * 3584 + b * 32) : "memory");
              __nanosleep(UPD);
            }
            __nanosleep(500);
          }
        }
      }
      if (lane == 0) TS(29);
#pragma unroll 1
      for (int i = lane; i < 128; i += 32) st_pkt16(&g_stats[b * 128 + i], 0, 0, 0, 0);
      st_pkt16(&g_cand[b * 32 + lane], 0, 0, 0, 0);
      if (lane < 8) st_pkt16(&g_entry[(ct * 16 + rt) * 8 + lane], 0, 0, 0, 0);
#pragma unroll 1
      for (int i = lane; i < (b < NFFN ? 512 : 0); i += 32) st_pkt16(&g_ypart[((i >> 2) * NFFN + b) * 4 + (i & 3)], 0, 0, 0, 0);
      mbar_arrive(sb + BAR_VEC);
      uint4* const cp = &g_cand[b * 32 + lane];
      uint4* const ep = &g_entry[(ct * 16 + rt) * 8];
      nb_sync(NB_AMAX, 288);
      TV(0);
      const uint2 e = lds64(sb + SM_AMAX + (lane & 7) * 8);
      const int tmax = __reduce_max_sync(0xffffffffu, (int)e.x);
      const uint32_t row = ~tmax & 127;
      const int wl = row >> 4;
      const uint32_t xa = sb + SM_X2 + (row >> 6) * 16384 + (lane >> 4) * 8192 + (row & 63) * 128 + (lane & 3) * 4
                        + ((((lane >> 1) & 6) ^ (row & 7)) * 16);
      const uint32_t v0 = lds32(xa), v1 = lds32(xa ^ 16);
      if (lane == wl) st_pkt16(ep, (tmax | 127) - rt, rt * 128 + row, e.y, tag);
      st_pkt16(cp, v0, v1, tag, 0);
      if (lane == 0) { sts32(sb + SM_CAND, row); mbar_arrive(sb + BAR_CAND); }
      TV(1);
      if (lane == 0) TS(15);
    }
  } else {
    const int warp = tid >> 5;
    const int wg = warp >> 2, wq = warp & 3;
    const int g = lane >> 2, t = lane & 3;
    uint32_t tag;
    uint32_t ln[4];
    float acc[128];
    uint32_t bf[16];
    auto gemv = [&]() {
          if (late) mbar_wait(sb + BAR_WH, 0); else
          asm volatile("cp.async.wait_all;" ::: "memory");
          float d0[4] = {0.f, 0.f, 0.f, 0.f}, d1[4] = {0.f, 0.f, 0.f, 0.f};
#pragma unroll
          for (int i = 0; i < 8; i++) {
            const uint4 wv = lds128(slab_addr + i * 512);
            const uint32_t a[4] = {wv.x, wv.y, wv.z, wv.w};
            mma16816((i & 1) ? d1 : d0, a, bf[2 * i], bf[2 * i + 1]);
          }
#pragma unroll
          for (int i = 0; i < 4; i++) { d0[i] += d1[i]; d0[i] += __shfl_xor_sync(0xffffffffu, d0[i], 6); }
          const uint32_t dst = mapa(sb + SM_MISC, t & 1) - SM_MISC;
          if (!(lane & 6)) st_async_f32x4(dst + SM_RED + warp * 128 + rank * 64 + g * 8, d0, dst + BAR_RED);
          TH(4);
    };
    {
      asm volatile("barrier.cluster.arrive.relaxed.aligned;" ::: "memory");
      if (lane == 0) st_pkt16(&g_lnst[8 * b0 + warp], 0, 0, 0, 0);
      TH(1);
      asm volatile("setmaxnreg.inc.sync.aligned.u32 240;");
      TH(2);
#pragma unroll
      for (int i = 0; i < 8; i++) {
        const float sv = silu_f((g & 4) ? hi2f(cw[i]) : lo2f(cw[i]));
        const uint32_t sp = (g & 1) ? pack2(0.f, sv) : pack2(sv, 0.f);
        bf[2 * i] = (g & 2) ? 0 : sp; bf[2 * i + 1] = (g & 2) ? sp : 0;
      }
      asm volatile("barrier.cluster.wait.aligned;" ::: "memory");
#pragma unroll
      for (int i = 0; i < 128; i++) acc[i] = 0.f;
      reg_fence<128>(acc);
      tag = __shfl_sync(0xffffffffu, epoch, 0) + 1;
      TH(3);
      if (slab && !late) gemv();
      {
        {
          mbar_wait(sb + BAR_XH, 0);
          TH(5);
          float ds[4] = {0.f, 0.f, 0.f, 0.f}, dq[4][4];
#pragma unroll
          for (int i = 0; i < 4; i++) { dq[i][0] = dq[i][1] = dq[i][2] = dq[i][3] = 0.f; }
#pragma unroll
          for (int i = 0; i < 8; i++) {
            uint32_t a[4];
            ldsm4(sb + SM_XROW + wg * ST1 + wq * 4096 + ((lane >> 3) & 1) * 2048 + i * 256 + (lane >> 4) * 128 + (lane & 7) * 16, a);
            mma16816(ds, a, ONE2, ONE2);
            mma1688(dq[0], a[0], a[1], a[0]); mma1688(dq[1], a[0], a[1], a[1]);
            mma1688(dq[2], a[2], a[3], a[2]); mma1688(dq[3], a[2], a[3], a[3]);
          }
          const bool dg = t == (g >> 1);
          const float q0 = dg ? ((g & 1) ? dq[0][1] + dq[2][1] : dq[0][0] + dq[2][0]) : 0.f;
          const float q1 = dg ? ((g & 1) ? dq[1][3] + dq[3][3] : dq[1][2] + dq[3][2]) : 0.f;
          float q = ((lane & 1) ? q1 : q0) + __shfl_xor_sync(0xffffffffu, (lane & 1) ? q0 : q1, 1);
          float sm = (lane & 1) ? ds[2] : ds[0];
          q += __shfl_xor_sync(0xffffffffu, q, 2);
#pragma unroll
          for (int o = 4; o <= 16; o <<= 1) { q += __shfl_xor_sync(0xffffffffu, q, o); sm += __shfl_xor_sync(0xffffffffu, sm, o); }
          const float mean = sm * (1.f / 1024.f);
          const float rd = rcp_f(rbf(sqrt_f(rbf(rbf(fmaxf(fmaf(-mean, mean, q * (1.f / 1024.f)), 0.f)) + 1e-5f))));
          const float mean1 = __shfl_sync(0xffffffffu, mean, 1), rd1 = __shfl_sync(0xffffffffu, rd, 1);
          const uint32_t rh = pack2(rd, rd1);
          if (lane == 0) st_pkt16(&g_lnst[8 * b0 + warp], pack2(-rbf(mean) * lo2f(rh), -rbf(mean1) * hi2f(rh)), rh, 0, tag);
          TH(6);
          if (tid == 0) TS(2);
        }
      }
    }
    if (slab && late) gemv();
    TILE_ROLES();
    const uint32_t xa0 = sb + SM_RING + (warp * 16 + (lane & 15)) * 128 + (((lane >> 4) ^ (lane & 7)) * 16);
    uint32_t V[16];
    {
      const uint4* mp = &g_rec[tag & 1][(b0 >> 1) & (NREP - 1)][RV * wg + (lane >> 2) * RS + (lane & 3)];
      const uint4* lp = &g_lnst[(8 * rt + warp) * 8 + (g >> 1)];
      mbar_wait(sb + BAR_FULL1, 0);
#pragma unroll
      for (int kk = 0; kk < 4; kk++) ldsm4(xa0 ^ (kk * 32), V + 4 * kk);
      uint4 v0 = make_uint4(1, 0, 0, 0), l0, l1;
      int it = 0;
      while ((uint32_t)clock() - c0 < HD) {}
      do { if (wq == 0) v0 = ld_pkt16(mp);
           l0 = ld_pkt16(lp); l1 = ld_pkt16(lp + 4); spin_guard(it); }
        while (!(__all_sync(0xffffffffu, v0.x != 0 && l0.w == tag && l1.w == tag)));
      TH(7);
      if (wq == 0) put_record(sb, 128 * wg + lane, v0);
      const uint32_t sel = (g & 1) ? 0x3232 : 0x1010;
      ln[0] = __byte_perm(l0.x, 0, sel); ln[1] = __byte_perm(l0.y, 0, sel);
      ln[2] = __byte_perm(l1.x, 0, sel); ln[3] = __byte_perm(l1.y, 0, sel);
      __syncwarp();
      if (lane < 2) mbar_arrive_cl(mapa(sb + BAR_G, lane));
      nb_sync(NB_CONS, 256);
      if (tid == 0) TS(3);
      TH(13);
    }

    const uint32_t rel = mapa(sb + SM_MISC, lane & 1) - SM_MISC;
    const uint32_t stsm_addr = sb + SM_STASH + wg * 16384 + (wq * 16 + (lane & 15)) * 128 + (((lane >> 4) ^ (lane & 7)) * 16);

    uint32_t ph = 0;
    uint32_t X[32];
    {
      const uint32_t tab0 = sb + SM_STASH + wg * 16384 + t * 16;
      const uint64_t db0 = mk_desc(sb + SM_RING + 16384, 8192);
      uint32_t A[2][16];
      uint32_t xa[4];
#pragma unroll
      for (int kk = 0; kk < 4; kk++) xa[kk] = xa0 ^ (kk * 32);
      uint32_t tab = tab0;
      reg_fence<4>(xa);
      asm volatile("{\n.reg .pred p;\nsetp.eq.u32 p, %4, 0;\n@p ld.shared.v4.u32 {%0,%1,%2,%3}, [%5];\n}"
        : "+r"(ln[2]), "+r"(ln[0]), "+r"(ln[3]), "+r"(ln[1]) : "r"(tag), "r"(sb));
      int hs = 2 * ct;
      uint4 R[4];
#pragma unroll
      for (int kk = 0; kk < 4; kk++) R[kk] = lds128(tab + (kk >> 1) * 2048 + (kk & 1) * 64);
#pragma unroll 1
      for (int k4 = 0; k4 < 4; k4++) {
#pragma unroll
        for (int s = 0; s < 4; s++) {
          uint32_t* a = A[s & 1];
          const int sn = (s + 1) & 3;
          const uint32_t pn = (k4 + (s == 3)) & 1;
          modulate_frags(a, V, R, ln);
          if (hs == (s & 2)) {
            if (s & 1) mbar_wait(sb + BAR_HS + 16 * wg, 0);
#pragma unroll
            for (int kk = 0; kk < 4; kk++) stsm4((stsm_addr + 4096) ^ (kk * 32), a[4 * kk], a[4 * kk + 1], a[4 * kk + 2], a[4 * kk + 3]);
            nb_arrive(NB_OST + wg, 160);
          }
          if (s == 0 && k4 == 0) TH(8);
          TQ(3 * s);
          if (s == 0 && k4 == 0 && tid == 0) { TS(6); TSC(61); }
          wg_fence();
#pragma unroll
          for (int kk = 0; kk < 4; kk++) wgmma_rs256<1>(acc, a + 4 * kk, db0 + s * (ST1 >> 4) + kk * 128);
          wg_commit();
          if (s == 3) TQ(12);
          if (s == 3 && k4 < 3) mbar_wait(sb + BAR_TAB + 8 * k4, 0);
          if (s == 3) TQ(13);
#pragma unroll
          for (int kk = 0; kk < 4; kk++) R[kk] = lds128(tab + (s + 1) * 128 + (kk >> 1) * 2048 + (kk & 1) * 64);
          wg_wait<1>();
          if (k4 == 0) TH(9 + s);
          TQ(3 * s + 1);
          reg_fence<16>(A[(s & 1) ^ 1]);
          if ((tid & 127) < 2 && (s | k4)) mbar_arrive_cl(rel + BAR_EMPTY1 + 8 * ((s + 3) & 3));
          if (s < 3 || k4 < 3) {
            mbar_wait(sb + BAR_FULL1 + 8 * sn, pn);
            TQ(3 * s + 2);
#pragma unroll
            for (int kk = 0; kk < 4; kk++) ldsm4(xa[kk] + sn * ST1, V + 4 * kk);
          }
        }
        tab += 512; hs -= 4;
      }
      mbar_wait(sb + BAR_HS + 16 * wg + 8, 0);
      wg_wait<0>();
      reg_fence<128>(acc);
    }
#pragma unroll 1
    for (int pair = 0; pair < 2; pair++) {
      uint32_t Q[32];
      TR(0);
      {
        if ((tid & 127) < 2) mbar_arrive_cl(rel + BAR_EMPTY1 + 8 * 3);
        if (pair == 1) mbar_wait(sb + BAR_STASH + 8 * wg, 1);
#pragma unroll
        for (int i = 0; i < 32; i++) Q[i] = pack2(acc[2 * i], acc[2 * i + 1]);
        const uint32_t qs = sb + SM_STASH + wg * 16384 + wq * 2048 + lane * 16;
#pragma unroll
        for (int i = 0; i < 8; i++)
          sts128(qs + (i & 3) * 512 + (i >> 2) * 8192, pack2(acc[64 + 8 * i], acc[65 + 8 * i]), pack2(acc[66 + 8 * i], acc[67 + 8 * i]),
                 pack2(acc[68 + 8 * i], acc[69 + 8 * i]), pack2(acc[70 + 8 * i], acc[71 + 8 * i]));
      }
      if (tid == 0) TS(8 + pair * 2);
      TR(1);
      float O[64], SL[32], SH[32];
      uint32_t PL[16], PH[16];
      SoftmaxState z;
      const uint64_t d0 = mk_desc(sb + SM_RING, 8192);
      {
        mbar_wait(sb + BAR_FULL1, ph);
        wg_fence();
        issue_qk(SL, Q, d0);
        wg_commit();
        issue_qk(SH, Q, d0 + 1024);
        wg_commit();
#pragma unroll
        for (int i = 0; i < 64; i++) O[i] = 0.f;
        reg_fence<64>(O);
        wg_wait<1>();
        reg_fence<32>(SL);
        softmax_start(z);
        softmax_half(SL, PL, O, z, true, tag);
        wg_wait<0>();
        reg_fence<32>(SH);
        if ((tid & 127) < 2) mbar_arrive_cl(rel + BAR_EMPTY1);
      }
      float lp0 = 0.f, lp1 = 0.f;
      uint32_t dB = (uint32_t)d0 + 1 * (ST1 >> 4), dA = (uint32_t)d0 + 2 * (ST1 >> 4);
      const uint32_t dBx = dB ^ ((uint32_t)d0 + 3 * (ST1 >> 4)), dAx = dA ^ (uint32_t)d0;
      uint32_t so = 0;
      bool ready = false;
#pragma unroll 1
      for (int i = 0; i < 7; i++) {
        TA(0);
        TR(2 + i);
        if (!ready) mbar_wait(sb + BAR_FULL1 + 8 + so, ph);
        TA(1);
        TA(2);
        wg_fence();
        issue_qk(SL, Q, (d0 & 0xffffffff00000000ull) | dB);
        if (i == 4) {
          __syncwarp();
          stage_o(O, lp0, lp1, stsm_addr);
        }
        wg_fence();
        issue_pv(O, PL, ((d0 & 0xffffffff00000000ull) | dB) + 1024, i != 4);
        wg_commit();
        if (i == 4) {
          nb_arrive(NB_OST + wg, 160);
        }
        TA(3);
        ph ^= i & 1;
        ready = mbar_test(sb + BAR_FULL1 + 16 - so, ph);
        softmax_half(SH, PH, O, z, false, tag);
        TA(4);
        wg_wait<0>();
        TA(5);
        reg_fence<32>(SL); reg_fence<16>(PL);
        if ((tid & 127) < 2) mbar_arrive_cl(rel + BAR_EMPTY1 + 8 + so);
        if (!ready) mbar_wait(sb + BAR_FULL1 + 16 - so, ph);
        TA(6);
        wg_fence();
        issue_qk(SH, Q, (d0 & 0xffffffff00000000ull) | dA);
        wg_commit();
        issue_pv(O, PH, ((d0 & 0xffffffff00000000ull) | dA) + 1024, 1);
        wg_commit();
        if (i == 2) {
          wg_wait<1>();
          reg_fence<32>(Q);
          const uint32_t qs = sb + SM_STASH + wg * 16384 + wq * 2048 + lane * 16;
#pragma unroll
          for (int j = 0; j < 8; j++) { const uint4 v = lds128(qs + (j & 3) * 512 + (j >> 2) * 8192); Q[4 * j] = v.x; Q[4 * j + 1] = v.y; Q[4 * j + 2] = v.z; Q[4 * j + 3] = v.w; }
        }
        TA(10);
        if (i == 3) { lp0 = z.l0; lp1 = z.l1; row_rcp(lp0, lp1); softmax_start(z); }
        TA(7);
        so ^= 16; dB ^= dBx; dA ^= dAx;
        ready = mbar_test(sb + BAR_FULL1 + 8 + so, ph);
        softmax_half(SL, PL, O, z, i == 3, tag);
        TA(8);
        wg_wait<0>();
        TA(9);
        reg_fence<32>(SH); reg_fence<16>(PH); reg_fence<64>(O); reg_fence<32>(Q);
        if ((tid & 127) < 2) mbar_arrive_cl(rel + BAR_EMPTY1 + so);
      }
      TAFLUSH();
      TR(9);
      {
        if (!ready) mbar_wait(sb + BAR_FULL1 + 8 * 3, ph);
        ph ^= 1;
        const uint64_t dv = d0 + 3 * (ST1 >> 4);
        wg_fence();
        issue_pv(O, PL, dv, 1);
        wg_commit();
        bb_fence(tag);
        softmax_half(SH, PH, O, z, false, tag);
        wg_fence();
        issue_pv(O, PH, dv + 1024, 1);
        wg_commit();
        TR(10);
        row_rcp(z.l0, z.l1);
        mbar_wait(sb + (pair ? BAR_X : BAR_STASH) + 8 * wg, 0);
#pragma unroll
        for (int kk = 0; kk < 8; kk++) ldsm4((stsm_addr + (kk >> 2) * 8192) ^ ((kk & 3) * 32), X + 4 * kk);
        reg_fence<32>(X);
        __syncwarp();
        wg_wait<0>();
        reg_fence<64>(O);
        TR(11);
        if ((tid & 127) < 2) mbar_arrive_cl(rel + BAR_EMPTY1 + 8 * 3);
        stage_o(O, z.l0, z.l1, stsm_addr);
        nb_arrive(NB_OST + wg, 160);
      }
      TR(12);
      if (tid == 0) { TS(9 + pair * 2); TSC(62); }
      if (pair == 1) break;
      {
        mbar_wait(sb + BAR_FULL1, ph);
        const uint64_t da = mk_desc(sb + SM_RING + wg * 8192, 16), db = mk_desc(sb + SM_RING + 16384, 8192);
        wg_fence();
        wgmma_ss256_z<1>(acc, da, db);
#pragma unroll
        for (int kk = 1; kk < 4; kk++) wgmma_ss256<1>(acc, da + kk * 2, db + kk * 128, 1);
        wg_commit();
      }
#pragma unroll 1
      for (int kt = 1; kt < 16; kt++) {
        const uint32_t s = kt & 3;
        if (s == 0) ph ^= 1;
        mbar_wait(sb + BAR_FULL1 + 8 * s, ph);
        const uint32_t st = sb + SM_RING + s * ST1;
        const uint64_t da = mk_desc(st + wg * 8192, 16), db = mk_desc(st + 16384, 8192);
        wg_fence();
#pragma unroll
        for (int kk = 0; kk < 4; kk++) wgmma_ss256<1>(acc, da + kk * 2, db + kk * 128, 1);
        wg_commit();
        wg_wait<1>();
        if ((tid & 127) < 2) mbar_arrive_cl(rel + BAR_EMPTY1 + 8 * ((s + 3) & 3));
      }
      ph ^= 1;
      wg_wait<0>();
      reg_fence<128>(acc);
      TR(13);
    }

    uint4 WG[16], WU[16];
    const int fp = 64 * warp + 8 * g + t;
    uint32_t fsb0, fsb1, fcb0, fcb1, fgb0, fgb1;
    const uint32_t gu_base = sb + SM_RING + (warp >> 1) * ST1 + 32768 + (warp & 1) * 8192;
    const uint32_t gu_addr = gu_base + t * 128 + (g & 1) * 64 + ((g >> 1) ^ t) * 16;
    {
      const uint64_t da0 = mk_desc(sb + SM_RING + __shfl_sync(0xffffffffu, wg, 0) * 8192, 16), db0 = mk_desc(sb + SM_RING + 16384, 8192);
#pragma unroll
      for (int n = 0; n < 4 + 5 * PEEL; n++) {
        const int s = n < 4 ? n : (n - 4) % 5;
        mbar_wait(sb + BAR_FULL1 + 8 * s, n < 4 ? 0 : ((n - 4) / 5 + (s < 4)) & 1);
        if (n < 4) TSX(40 + wg * 6 + n);
        const uint64_t da = da0 + s * (ST1 >> 4), db = db0 + s * (ST1 >> 4);
        wg_fence();
        if (n == 0) wgmma_ss128_z<1>(acc, da, db); else wgmma_ss128<1>(acc, da, db, 1);
#pragma unroll
        for (int kk = 1; kk < 4; kk++) wgmma_ss128<1>(acc, da + kk * 2, db + kk * 128, 1);
        wg_commit();
        if (n == 0 && b < NFFN) mbar_wait(sb + BAR_FFN, 0);
        {
          constexpr int NT = 4 + 5 * PEEL, F0 = NT > 16 ? NT - 16 : 0;
#pragma unroll
          for (int i = 0; i < 16; i++) if (F0 + i * (NT - F0) / 16 == n) WG[i] = lds128(gu_addr + i * 512);
        }
        if (n > 0) {
          wg_wait<1>();
          if ((tid & 127) < 2) mbar_arrive_cl(rel + BAR_EMPTY1 + 8 * (n == 4 ? 3 : s ? s - 1 : 4));
        }
      }
      TSX(44 + wg * 6);
      {
        uint32_t dep = 0;
#pragma unroll
        for (int i = 0; i < 16; i++) dep ^= WG[i].x;
        if (__shfl_sync(0xffffffffu, tag, dep & 31) == tag && lane == 2) mbar_arrive(sb + BAR_TFREE);
      }
      {
        uint32_t so = 0, sp = 4 * 8, par = PEEL + 1;
#pragma unroll 1
        for (int n = 4 + 5 * PEEL; n < 64; n++) {
          mbar_wait(sb + BAR_FULL1 + so, (par + (so >> 5)) & 1);
          const uint64_t da = da0 + so * (ST1 >> 7), db = db0 + so * (ST1 >> 7);
          wg_fence();
#pragma unroll
          for (int kk = 0; kk < 4; kk++) wgmma_ss128<1>(acc, da + kk * 2, db + kk * 128, 1);
          wg_commit();
          wg_wait<1>();
          if ((tid & 127) < 2) mbar_arrive_cl(rel + BAR_EMPTY1 + sp);
          sp = so; so += 8;
          if (so == 40) { so = 0; par++; }
        }
      }
    }
    mbar_wait(sb + BAR_VEC, 0);
    const int lrow = warp * 16 + g;
    uint2 ga[8], b1[8];
#pragma unroll
    for (int kk = 0; kk < 8; kk++) { ga[kk] = lds64(sb + SM_GA + kk * 32 + t * 8); b1[kk] = lds64(sb + SM_B1 + min(g, 3) * 32 + t * 8 + kk * 128); }
    uint4* const stp = &g_stats[b * 128 + lrow + 8 * t];
    bb_fence(tag);
    wg_wait<0>();
    reg_fence<64>(acc);
    if (tid == 0) { TS(12); TSC(63); }

    TT(0);
    {
      float d1[4] = {0.f, 0.f, 0.f, 0.f}, d2[4] = {0.f, 0.f, 0.f, 0.f}, d3[4] = {0.f, 0.f, 0.f, 0.f};
      float d4[4] = {0.f, 0.f, 0.f, 0.f}, d5[4] = {0.f, 0.f, 0.f, 0.f};
#pragma unroll
      for (int kk = 0; kk < 8; kk++) {
        uint32_t* x = X + 4 * kk;
        x[0] = hfma2(ga[kk].x, pack2(acc[8 * kk + 0], acc[8 * kk + 1]), x[0]);
        x[1] = hfma2(ga[kk].x, pack2(acc[8 * kk + 2], acc[8 * kk + 3]), x[1]);
        x[2] = hfma2(ga[kk].y, pack2(acc[8 * kk + 4], acc[8 * kk + 5]), x[2]);
        x[3] = hfma2(ga[kk].y, pack2(acc[8 * kk + 6], acc[8 * kk + 7]), x[3]);
        mma16816(d1, x, b1[kk].x, b1[kk].y);
        mma1688(d2, x[0], x[1], x[0]); mma1688(d3, x[0], x[1], x[1]);
        mma1688(d4, x[2], x[3], x[2]); mma1688(d5, x[2], x[3], x[3]);
      }
      const int qb = lane & 28;
      const float q0 = __shfl_sync(0xffffffffu, (g & 1) ? d2[1] + d4[1] : d2[0] + d4[0], qb | (g >> 1));
      const float q1 = __shfl_sync(0xffffffffu, (g & 1) ? d3[3] + d5[3] : d3[2] + d5[2], qb | (g >> 1));
      const float e0 = __shfl_xor_sync(0xffffffffu, t ? d1[0] : d1[3], 1);
      const float e1 = __shfl_sync(0xffffffffu, d1[2], qb);
      if (t < 2) st_pkt16(stp, __float_as_uint(t ? e1 : d1[0]), __float_as_uint(t ? q1 : q0),
                          __float_as_uint((t ? d1[2] : d1[1]) + e0), tag);
    }
    {
      const uint2* mp = &g_mod[3 * 512 + fp];
      fsb0 = ld_pkt8(mp).x; fsb1 = ld_pkt8(mp + 4).x; fcb0 = ld_pkt8(mp + 512).x; fcb1 = ld_pkt8(mp + 516).x;
      fgb0 = ld_pkt8(mp + 1024).x; fgb1 = ld_pkt8(mp + 1028).x;
    }
    TSY(13);
    TT(1);
    float mb, rd, den, br;
    {
      const uint4* sp = &g_stats[(rt * 8 + 4 * (t & 1)) * 128 + lrow + 4 * (t & 2)];
      mbar_wait(sb + BAR_EMPTY1 + 8 * 3, 0);
#pragma unroll
      for (int kk = 0; kk < 8; kk++) stsm4((stsm_addr - SM_STASH + SM_X2 + (kk >> 2) * 8192) ^ ((kk & 3) * 32), X[4 * kk], X[4 * kk + 1], X[4 * kk + 2], X[4 * kk + 3]);
      if (b < NFFN) mbar_wait(sb + BAR_FFN, 1);
#pragma unroll
      for (int i = 0; i < WU1; i++) WU[i] = lds128(gu_addr + i * 512);
      bb_fence(tag);
      TT(2);
      uint4 v0, v1, v2, v3;
      int it = 0;
      do { v0 = ld_pkt16(sp); v1 = ld_pkt16(sp + 128); v2 = ld_pkt16(sp + 256); v3 = ld_pkt16(sp + 384); spin_guard(it); }
        while (!(__all_sync(0xffffffffu, v0.w == tag && v1.w == tag && v2.w == tag && v3.w == tag)));
      TT(3);
      float sm = (__uint_as_float(v0.x) + __uint_as_float(v1.x)) + (__uint_as_float(v2.x) + __uint_as_float(v3.x));
      float sq = (__uint_as_float(v0.y) + __uint_as_float(v1.y)) + (__uint_as_float(v2.y) + __uint_as_float(v3.y));
      float dt = (__uint_as_float(v0.z) + __uint_as_float(v1.z)) + (__uint_as_float(v2.z) + __uint_as_float(v3.z));
      sm += __shfl_xor_sync(0xffffffffu, sm, 1); sq += __shfl_xor_sync(0xffffffffu, sq, 1); dt += __shfl_xor_sync(0xffffffffu, dt, 1);
      const uint2 scal = lds64(sb + SM_SCAL);
      const float mu = sm * (1.f / 1024.f);
      mb = rbf(mu);
      den = rbf(sqrt_f(rbf(rbf(fmaxf(fmaf(-mu, mu, sq * (1.f / 1024.f)), 0.f)) + 1e-5f)));
      rd = rcp_f(den);
      br = fmaf(fmaf(-mb, __uint_as_float(scal.x), dt), rd, __uint_as_float(scal.y));
    }
    TSY(14);
    TT(4);
    {
      const int rb = __float_as_int(br);
      const int key = ((rb ^ ((rb >> 31) & 0x7fffffff)) | 127) - (lrow + 4 * (t & 2));
      if (key == __reduce_max_sync(0xffffffffu, key)) sts64(sb + SM_AMAX + warp * 8, (uint32_t)key, pack2(mb, den));
      __syncwarp();
      nb_arrive(NB_AMAX, 288);
    }
    TT(5);
    const uint4* ep = &g_entry[(warp * 16 + (lane & 15)) * 8];
    const uint32_t slot = sb + SM_STASH + wg * 8192 + (tid & 127) * 16;
    cp_async16(slot, ep);
    {
      const float rh = rbf(rd);
      const uint32_t u = pack2(-mb * rh, rh);
      const int qb = lane & 28;
      const uint32_t u0 = __shfl_sync(0xffffffffu, u, qb), u1 = __shfl_sync(0xffffffffu, u, qb | 2);
      const uint32_t m0 = __byte_perm(u0, 0, 0x1010), h0 = __byte_perm(u0, 0, 0x3232);
      const uint32_t m1 = __byte_perm(u1, 0, 0x1010), h1 = __byte_perm(u1, 0, 0x3232);
#pragma unroll
      for (int j = 0; j < 16; j++) {
        const uint4 rec = lds128(sb + SM_REC + (4 * j + t) * 16);
        X[2 * j] = hfma2(rec.z, hfma2(hfma2(X[2 * j], h0, m0), rec.x, rec.y), X[2 * j]);
        X[2 * j + 1] = hfma2(rec.z, hfma2(hfma2(X[2 * j + 1], h1, m1), rec.x, rec.y), X[2 * j + 1]);
      }
#pragma unroll
      for (int kk = 0; kk < 8; kk++) stsm4((stsm_addr - SM_STASH + SM_OUT + (kk >> 2) * 8192) ^ ((kk & 3) * 32), X[4 * kk], X[4 * kk + 1], X[4 * kk + 2], X[4 * kk + 3]);
    }
    cp_async_wait();
    uint4 ent = lds128(slot);
    TSY(16);
    TT(6);
    int wrow;
    uint32_t xs0, xs1, hs0, hs1;
    uint32_t WD[64];
    const uint32_t wd_addr = sb + SM_RING + wg * ST1 + wq * 8192 + ((lane & 7) + ((lane >> 4) << 3)) * 128 + ((((lane >> 3) & 1) ^ (lane & 7)) * 16);
    {
      int gmax;
      auto leader = [&]() {
        gmax = __reduce_max_sync(0xffffffffu, ent.w == tag ? (int)ent.x : (int)0x8000000f);
        return ~gmax & 15;
      };
      int wt = leader(), it = 0;
      TT(7);
      nb_arrive(NB_OST + wg, 160);
      TT(8);
      cp_async16(slot + 2048, &g_cand[(wt * 8 + warp) * 32 + lane]);
      if (ent.w != tag) cp_async16(slot, ep);
#pragma unroll
      for (int i = WU1; i < 16; i++) WU[i] = lds128(gu_addr + i * 512);
      if (b < NFFN) mbar_wait(sb + BAR_FFN + 8, 0);
#pragma unroll
      for (int mt = 0; mt < 8; mt++)
#pragma unroll
        for (int s = 0; s < 2; s++) ldsm4t((wd_addr + (mt >> 2) * 4096 + s * 2048) ^ ((mt & 3) * 32), WD + (mt * 2 + s) * 4);
      cp_async_wait();
      uint4 v = lds128(slot + 2048);
      ent = lds128(slot);
      TT(9);
      while (true) {
        const int have = wt;
        wt = leader();
        if (__all_sync(0xffffffffu, ent.w == tag && have == wt && v.z == tag)) break;
        v = ld_pkt16(&g_cand[(wt * 8 + warp) * 32 + lane]);
        if (ent.w != tag) ent = ld_pkt16(ep);
        spin_guard(it);
      }
      TT(10);
      ent.x = gmax ^ ((gmax >> 31) & 0x7fffffff);
      wrow = __shfl_sync(0xffffffffu, ent.y, wt); ent.z = __shfl_sync(0xffffffffu, ent.z, wt);
      xs0 = v.x; xs1 = v.y;
      const uint32_t mm = __byte_perm(ent.z, 0, 0x1010);
      const float rs = rcp_f(hi2f(ent.z));
      const uint32_t e0 = hsub2(xs0, mm), e1 = hsub2(xs1, mm);
      hs0 = hfma2(pack2(lo2f(e0) * rs, hi2f(e0) * rs), hadd2(fcb0, ONE2), fsb0);
      hs1 = hfma2(pack2(lo2f(e1) * rs, hi2f(e1) * rs), hadd2(fcb1, ONE2), fsb1);
    }
    if ((tid & 127) == 0) sts32(sb + SM_WROW + 4 * wg, wrow);
    nb_arrive(NB_WIN + wg, 160);
    TSY(17);
    TT(11);
    if (b < NFFN) {
      float da[4][4];
#pragma unroll
      for (int i = 0; i < 4; i++) { da[i][0] = da[i][1] = da[i][2] = da[i][3] = 0.f; }
      const uint32_t selv = ((g & 1) ? 0x1044 : 0x4410) + ((g & 4) ? ((g & 1) ? 0x2200 : 0x0022) : 0);
      const uint32_t sel0 = (g & 2) ? 0x4444 : selv, sel1 = (g & 2) ? selv : 0x4444;
#pragma unroll
      for (int s = 0; s < 16; s++) {
        const uint32_t v = __shfl_sync(0xffffffffu, (s & 1) ? hs1 : hs0, 4 * (s >> 1) + t);
        const uint32_t b0 = __byte_perm(v, 0, sel0), b1 = __byte_perm(v, 0, sel1);
        const uint32_t a0[4] = {WG[s].x, WG[s].y, WG[s].z, WG[s].w};
        const uint32_t a1[4] = {WU[s].x, WU[s].y, WU[s].z, WU[s].w};
        mma16816(da[(s & 1) * 2], a0, b0, b1);
        mma16816(da[(s & 1) * 2 + 1], a1, b0, b1);
      }
      {
        float v[4];
#pragma unroll
        for (int i = 0; i < 4; i++) {
          const float vg = da[0][i] + da[2][i], vu = da[1][i] + da[3][i];
          v[i] = ((g & 1) ? vu : vg) + __shfl_xor_sync(0xffffffffu, (g & 1) ? vg : vu, 6);
        }
        if ((t >> 1) == (g & 1))
          sts128(gu_base + (g & 1) * 128 + (g >> 1) * 32 + (t & 1) * 16, __float_as_uint(v[0]), __float_as_uint(v[1]), __float_as_uint(v[2]), __float_as_uint(v[3]));
      }
      TT(12);
      nb_sync(NB_CONS, 256);
      float gp[8], up[8];
#pragma unroll
      for (int w = 0; w < 8; w++) {
        const uint32_t a = sb + SM_RING + (w >> 1) * ST1 + 32768 + (w & 1) * 8192 + lane * 4;
        gp[w] = lds_f32(a); up[w] = lds_f32(a + 128);
      }
      const float gsum = ((gp[0] + gp[1]) + (gp[2] + gp[3])) + ((gp[4] + gp[5]) + (gp[6] + gp[7]));
      const float usum = ((up[0] + up[1]) + (up[2] + up[3])) + ((up[4] + up[5]) + (up[6] + up[7]));
      const float act = rbf(silu_f(rbf(gsum))) * rbf(usum);
      TT(13);
      const uint32_t ap = pack2(act, __shfl_down_sync(0xffffffffu, act, 1));
      const uint32_t b00 = __shfl_sync(0xffffffffu, ap, 2 * t), b01 = __shfl_sync(0xffffffffu, ap, 2 * t + 8);
      const uint32_t b10 = __shfl_sync(0xffffffffu, ap, 2 * t + 16), b11 = __shfl_sync(0xffffffffu, ap, 2 * t + 24);
      float y[8][4];
#pragma unroll
      for (int mt = 0; mt < 8; mt++) {
        y[mt][0] = y[mt][1] = y[mt][2] = y[mt][3] = 0.f;
        mma16816(y[mt], WD + (mt * 2) * 4, b00, b01);
        mma16816(y[mt], WD + (mt * 2 + 1) * 4, b10, b11);
      }
#pragma unroll
      for (int e = 0; e < 2; e++) {
        const float v0 = t == 0 ? y[e][0] : t == 1 ? y[2 + e][0] : t == 2 ? y[4 + e][0] : y[6 + e][0];
        const float v1 = t == 0 ? y[e][2] : t == 1 ? y[2 + e][2] : t == 2 ? y[4 + e][2] : y[6 + e][2];
        const int f = 16 * warp + 2 * (2 * t + e) + (g >> 2);
        st_pkt16(&g_ypart[(f * NFFN + b) * 4 + (g & 3)], __float_as_uint(v0), __float_as_uint(v1), tag, 0);
      }
    }
    TSY(18);
    TT(14);
    {
      const int pw = warp - (warp > (b >> 4));
      if (warp != (b >> 4)) {
        const uint4* yp = &g_ypart[b * NFFN * 4 + pw * 64 + lane];
        uint4 v0, v1;
        int it = 0;
        { const uint32_t c1 = clock(); while ((uint32_t)clock() - c1 < (b < NFFN ? YD : YD + 1500)) {} }
        do { v0 = ld_pkt16(yp); v1 = ld_pkt16(yp + 32); spin_guard(it); }
        while (!(__all_sync(0xffffffffu, v0.z == tag && v1.z == tag)));
        float y0 = __uint_as_float(v0.x) + __uint_as_float(v1.x), y1 = __uint_as_float(v0.y) + __uint_as_float(v1.y);
#pragma unroll
        for (int o = 4; o <= 16; o <<= 1) { y0 += __shfl_xor_sync(0xffffffffu, y0, o); y1 += __shfl_xor_sync(0xffffffffu, y1, o); }
        if (lane < 4) sts64(sb + SM_YRED + pw * 32 + lane * 8, __float_as_uint(y0), __float_as_uint(y1));
      }
    }
    TT(15);
    if (warp != (b >> 4)) {
      nb_arrive(NB_CONS, 256);
    } else {
      nb_sync(NB_CONS, 256);
      float y0 = 0.f, y1 = 0.f;
      if (lane < 28) { const uint2 e = lds64(sb + SM_YRED + lane * 8); y0 = __uint_as_float(e.x); y1 = __uint_as_float(e.y); }
#pragma unroll
      for (int o = 4; o <= 16; o <<= 1) { y0 += __shfl_xor_sync(0xffffffffu, y0, o); y1 += __shfl_xor_sync(0xffffffffu, y1, o); }
      const int src = 2 * (t & 1);
      const float ya = __shfl_sync(0xffffffffu, y0, src), yb = __shfl_sync(0xffffffffu, y0, src + 1);
      const float yc = __shfl_sync(0xffffffffu, y1, src), yd = __shfl_sync(0xffffffffu, y1, src + 1);
      if (g == ((b >> 1) & 7) && (t >> 1) == (b & 1)) {
        const float rs = rbf(__uint_as_float(ent.x));
        const float sg = sigmoid_f(rs);
        const uint32_t sg2 = pack2(sg, sg);
        const uint32_t o0 = hadd2(xs0, hmul2(fgb0, hadd2(hs0, hmul2(pack2(ya, yb), sg2))));
        const uint32_t o1 = hadd2(xs1, hmul2(fgb1, hadd2(hs1, hmul2(pack2(yc, yd), sg2))));
        uint32_t* op = reinterpret_cast<uint32_t*>(p.out + (size_t)wrow * 1024) + fp;
        op[0] = o0; op[4] = o1;
      }
      if (b == 0) {
        if (lane < 8) st_relaxed(&p.sc->ticket[lane * 32], 0);
        st_relaxed(&p.sc->epoch[lane], tag);
      }
      if (lane == 0) TS(19);
    }
  }
}

typedef CUresult (*EncodeFn)(CUtensorMap*, CUtensorMapDataType, cuuint32_t, void*, const cuuint64_t*, const cuuint64_t*,
                             const cuuint32_t*, const cuuint32_t*, CUtensorMapInterleave, CUtensorMapSwizzle,
                             CUtensorMapL2promotion, CUtensorMapFloatOOBfill);

CUtensorMap make_map(EncodeFn enc, const void* ptr, uint64_t rows, uint64_t cols, uint32_t box_rows, uint32_t box_cols, CUtensorMapSwizzle sw) {
  CUtensorMap m;
  cuuint64_t dims[2] = {cols, rows};
  cuuint64_t strides[1] = {cols * 2};
  cuuint32_t box[2] = {box_cols, box_rows};
  cuuint32_t es[2] = {1, 1};
  enc(&m, CU_TENSOR_MAP_DATA_TYPE_BFLOAT16, 2, const_cast<void*>(ptr), dims, strides, box, es, CU_TENSOR_MAP_INTERLEAVE_NONE, sw,
      CU_TENSOR_MAP_L2_PROMOTION_L2_128B, CU_TENSOR_MAP_FLOAT_OOB_FILL_NONE);
  return m;
}

CUtensorMap make_map3(EncodeFn enc, const void* ptr, uint64_t rows, uint64_t cols, uint32_t box_rows, uint32_t box_blks) {
  CUtensorMap m;
  cuuint64_t dims[3] = {64, rows, cols / 64};
  cuuint64_t strides[2] = {cols * 2, 128};
  cuuint32_t box[3] = {64, box_rows, box_blks};
  cuuint32_t es[3] = {1, 1, 1};
  enc(&m, CU_TENSOR_MAP_DATA_TYPE_BFLOAT16, 3, const_cast<void*>(ptr), dims, strides, box, es, CU_TENSOR_MAP_INTERLEAVE_NONE,
      CU_TENSOR_MAP_SWIZZLE_128B, CU_TENSOR_MAP_L2_PROMOTION_L2_128B, CU_TENSOR_MAP_FLOAT_OOB_FILL_NONE);
  return m;
}

}

extern "C" void kernel_launch(void* const* d_in, const int* in_sizes, int n_in, void* d_out, int out_size) {
  (void)in_sizes; (void)n_in; (void)out_size;
  Params p;
  p.x = (const bf16*)d_in[0]; p.kc = (const bf16*)d_in[1]; p.vc = (const bf16*)d_in[2];
  p.wq = (const bf16*)d_in[3]; p.wo = (const bf16*)d_in[4]; p.w_r = (const bf16*)d_in[6];
  p.wg = (const bf16*)d_in[7]; p.wu = (const bf16*)d_in[8]; p.wd = (const bf16*)d_in[9];
  p.c = (const bf16*)d_in[10]; p.w_mod = (const bf16*)d_in[11]; p.out = (bf16*)d_out;

  void* fn = nullptr;
  cudaDriverEntryPointQueryResult st;
  cudaGetDriverEntryPoint("cuTensorMapEncodeTiled", &fn, cudaEnableDefault, &st);
  EncodeFn enc = (EncodeFn)fn;
  void* scp = nullptr;
  cudaGetSymbolAddress(&scp, g_scratch);
  p.sc = (Scratch*)scp;
  void *hp = p.sc->h, *op = p.sc->o;
  const CUtensorMapSwizzle S128 = CU_TENSOR_MAP_SWIZZLE_128B;
  CUtensorMap mH = make_map(enc, hp, 2048, 1024, 64, 64, S128);
  CUtensorMap mWq = make_map3(enc, p.wq, 1024, 4096, 64, 4);
  CUtensorMap mK = make_map(enc, p.kc, 8192, 128, 64, 64, S128);
  CUtensorMap mV = make_map(enc, p.vc, 8192, 128, 64, 64, S128);
  CUtensorMap mO = make_map(enc, op, 2048, 4096, 64, 64, S128);
  CUtensorMap mOs = make_map(enc, op, 2048, 4096, 16, 64, S128);
  CUtensorMap mWo = make_map3(enc, p.wo, 4096, 1024, 64, 2);
  CUtensorMap mX = make_map(enc, p.x, 2048, 1024, 64, 64, S128);
  CUtensorMap mOut = make_map(enc, p.out, 2048, 1024, 64, 64, S128);
  CUtensorMap mWg = make_map(enc, p.wg, 1024, 3584, 256, 32, CU_TENSOR_MAP_SWIZZLE_64B);
  CUtensorMap mWu = make_map(enc, p.wu, 1024, 3584, 256, 32, CU_TENSOR_MAP_SWIZZLE_64B);
  CUtensorMap mWd = make_map3(enc, p.wd, 3584, 1024, 32, 8);
  CUtensorMap mWm = make_map(enc, p.w_mod, 1024, 6144, 16, 256, CU_TENSOR_MAP_SWIZZLE_NONE);
  CUtensorMap mWh = make_map(enc, p.w_mod, 1024, 6144, 256, 32, CU_TENSOR_MAP_SWIZZLE_64B);
  CUtensorMap mWs = make_map(enc, p.w_mod, 1024, 6144, 128, 128, CU_TENSOR_MAP_SWIZZLE_NONE);
  cudaFuncSetAttribute(fused_kernel, cudaFuncAttributeMaxDynamicSharedMemorySize, SMEM_BYTES);
  fused_kernel<<<NCTA, NTHREADS, SMEM_BYTES>>>(p, mH, mWq, mK, mV, mO, mWo, mX, mOut, mWg, mWu, mWd, mWm, mWs, mWh, mOs);
}
```

```cpp
#include <cuda_runtime.h>
#include <cuda_bf16.h>
#include <cuda.h>
#include <stdint.h>
#include <stddef.h>

#define UPD 200
#define GATED 700
#define PFW 100
#define OP0 200
#define OP3 90
#define PLD 200
#define WL 3500
#define SPT 5000
#define HD 6000
#define YD 300
#define PEEL 1
#define WU1 12

namespace {

typedef __nv_bfloat16 bf16;

constexpr int NTHREADS = 384;
constexpr int NMAIN = 128;
constexpr int NCTA = 132;
constexpr int RS = 8, RV = 16 * RS + 64;
constexpr int NREP = 4;
constexpr int NFFN = 112;

constexpr uint32_t SM_RING = 0;
constexpr uint32_t ST1 = 49152;
constexpr uint32_t ST2 = 32768;
constexpr int NST2 = 6;
constexpr uint32_t SM_STASH = 196608;
constexpr uint32_t SM_MISC = 229376;
constexpr uint32_t BAR_FULL1 = SM_MISC + 0;
constexpr uint32_t BAR_EMPTY1 = SM_MISC + 40;
constexpr uint32_t BAR_FULL2 = SM_MISC + 0;
constexpr uint32_t BAR_EMPTY2 = SM_MISC + 48;
constexpr uint32_t BAR_STASH = SM_MISC + 160;
constexpr uint32_t BAR_SFREE = SM_MISC + 176;
constexpr uint32_t BAR_TFREE = SM_MISC + 184;
constexpr uint32_t BAR_FFN = SM_MISC + 192;
constexpr uint32_t BAR_VEC = SM_MISC + 208;
constexpr uint32_t BAR_RED = SM_MISC + 216;
constexpr uint32_t BAR_XH = SM_MISC + 152;
constexpr uint32_t BAR_HS = SM_MISC + 80;
constexpr uint32_t BAR_G = SM_MISC + 112;
constexpr uint32_t BAR_T1 = SM_MISC + 120;
constexpr uint32_t BAR_HF = SM_MISC + 128;
constexpr uint32_t BAR_X = SM_MISC + 136;
constexpr uint32_t BAR_OF = SM_MISC + 224;
constexpr uint32_t BAR_ROLE = SM_MISC + 240;
constexpr uint32_t SM_ROLE = SM_MISC + 248;
constexpr uint32_t SM_GA = SM_MISC + 256;
constexpr uint32_t SM_SCAL = SM_MISC + 512;
constexpr uint32_t SM_WROW = SM_MISC + 520;
constexpr uint32_t SM_AMAX = SM_MISC + 528;
constexpr uint32_t SM_X2 = 2 * ST1, SM_OUT = 3 * ST1;
constexpr uint32_t SM_REC = SM_MISC + 1024;
constexpr uint32_t BAR_TAB = SM_MISC + 1000;
constexpr uint32_t BAR_CAND = SM_MISC + 880;
constexpr uint32_t SM_CAND = SM_MISC + 888;
constexpr uint32_t BAR_WH = SM_MISC + 960;
constexpr uint32_t SM_WSLAB = 2 * 49152 + 16384;
constexpr uint32_t SM_XROW = 2 * 49152;
constexpr uint32_t SM_RED = SM_MISC + 2048;
constexpr uint32_t SM_B1 = SM_MISC + 2048;
constexpr uint32_t SMEM_BYTES = 232448;

constexpr int NB_CONS = 1, NB_WIN = 2  , NB_OST = 4  , NB_AMAX = 6;

struct __align__(1024) Scratch {
  uint32_t epoch[32];
  uint32_t hflag[16 * 32];
  uint32_t oflag[64 * 32];
  uint2 vdone[4 * 16];
  uint32_t pad[96 + 512];
  uint32_t ticket[8 * 32];
  uint2 mod[3072];
  uint4 rec[2][NREP][2 * RV];
  uint4 lnst[1024];
  uint4 entry[8 * 16 * 8];
  uint4 cand[16 * 8 * 32];
  uint4 stats[16 * 8 * 128];
  uint4 ypart[2 * 64 * NFFN * 4];
  unsigned long long ts[NCTA * 64];
  uint16_t h[2048 * 1024];
  uint16_t o[2048 * 4096];
};
__device__ Scratch g_scratch;
#define g_epoch (p.sc->epoch[0])
#define g_hflag (p.sc->hflag)
#define g_oflag (p.sc->oflag)
#define g_mod (p.sc->mod)
#define g_entry (p.sc->entry)
#define g_cand (p.sc->cand)
#define g_stats (p.sc->stats)
#define g_ypart (p.sc->ypart)
#define g_vdone (p.sc->vdone)
#define g_lnst (p.sc->lnst)
#define g_rec (p.sc->rec)
#define g_ts (p.sc->ts)
#define g_h (p.sc->h)

struct Params {
  const bf16* w_mod; const bf16* c; Scratch* sc; const bf16* x; const bf16* w_r; bf16* out;
  const bf16* wq; const bf16* wo; const bf16* wg; const bf16* wu; const bf16* wd; const bf16* kc; const bf16* vc;
};

__device__ __forceinline__ uint32_t smem_u32(const void* p) { return (uint32_t)__cvta_generic_to_shared(p); }
__device__ __forceinline__ void mbar_init(uint32_t bar, uint32_t cnt) { asm volatile("mbarrier.init.shared::cta.b64 [%0], %1;" :: "r"(bar), "r"(cnt) : "memory"); }
__device__ __forceinline__ void mbar_expect_tx(uint32_t bar, uint32_t bytes) { asm volatile("mbarrier.arrive.expect_tx.shared::cta.b64 _, [%0], %1;" :: "r"(bar), "r"(bytes) : "memory"); }
__device__ __forceinline__ void mbar_arrive(uint32_t bar) { asm volatile("mbarrier.arrive.shared::cta.b64 _, [%0];" :: "r"(bar) : "memory"); }
__device__ __forceinline__ void mbar_arrive_cl(uint32_t cluster_addr) { asm volatile("mbarrier.arrive.shared::cluster.b64 _, [%0];" :: "r"(cluster_addr) : "memory"); }
__device__ __forceinline__ uint32_t mapa(uint32_t addr, uint32_t cta) { uint32_t r; asm("mapa.shared::cluster.u32 %0, %1, %2;" : "=r"(r) : "r"(addr), "r"(cta)); return r; }
__device__ __forceinline__ bool mbar_test(uint32_t bar, uint32_t parity) {
  uint32_t ok;
  asm volatile("{\n.reg .pred p;\nmbarrier.test_wait.parity.shared::cta.b64 p, [%1], %2;\nselp.u32 %0, 1, 0, p;\n}" : "=r"(ok) : "r"(bar), "r"(parity) : "memory");
  return ok;
}
constexpr int SPIN_LIMIT = 300000;
__device__ __forceinline__ void spin_guard(int& it) {
  asm volatile("{\n.reg .pred p;\n.reg .b64 z;\nadd.s32 %0, %0, 1;\nsetp.gt.s32 p, %0, %1;\nmov.b64 z, 0;\n@p st.volatile.global.u32 [z], %0;\n}" : "+r"(it) : "n"(SPIN_LIMIT));
}
__device__ __forceinline__ void mbar_wait_g(uint32_t bar, uint32_t parity) {
  asm volatile("{\n.reg .pred p, q;\n.reg .b32 c;\n.reg .b64 z;\nmov.b32 c, 0;\nmov.b64 z, 0;\nMW_LOOP:\n"
               "mbarrier.try_wait.parity.shared::cta.b64 p, [%0], %1;\nadd.s32 c, c, 1;\nsetp.gt.s32 q, c, %2;\n"
               "@q st.volatile.global.u32 [z], c;\n@!p bra MW_LOOP;\n}" :: "r"(bar), "r"(parity), "n"(SPIN_LIMIT) : "memory");
}
__device__ __forceinline__ void mbar_wait(uint32_t bar, uint32_t parity) {
  asm volatile("{\n.reg .pred p;\nMW_LOOP:\nmbarrier.try_wait.parity.shared::cta.b64 p, [%0], %1;\n@!p bra MW_LOOP;\n}" :: "r"(bar), "r"(parity) : "memory");
}
__device__ __forceinline__ void bb_fence(uint32_t v) {
  asm volatile("{\n.reg .pred p;\n.reg .u32 c;\nsetp.ne.u32 p, %0, 0;\n@p bra.uni BF_DONE;\nBF_LOOP:\nnanosleep.u32 1;\nmov.u32 c, %%clock;\nsetp.eq.u32 p, c, 0;\n@p bra.uni BF_LOOP;\nBF_DONE:\n}" :: "r"(v) : "memory");
}
__device__ __forceinline__ bool elect_one() {
  uint32_t pred;
  asm volatile("{\n.reg .pred P;\nelect.sync _|P, 0xffffffff;\nselp.u32 %0, 1, 0, P;\n}" : "=r"(pred));
  return pred;
}
__device__ __forceinline__ void tma_ld_hint(uint32_t dst, const CUtensorMap* m, int c0, int c1, uint32_t bar, uint64_t pol) {
  asm volatile("cp.async.bulk.tensor.2d.shared::cluster.global.mbarrier::complete_tx::bytes.L2::cache_hint [%0], [%1, {%3, %4}], [%2], %5;"
    :: "r"(dst), "l"(m), "r"(bar), "r"(c0), "r"(c1), "l"(pol) : "memory");
}
__device__ __forceinline__ void tma_ld_mc(uint32_t dst, const CUtensorMap* m, int c0, int c1, uint32_t bar) {
  asm volatile("cp.async.bulk.tensor.2d.shared::cluster.global.mbarrier::complete_tx::bytes.multicast::cluster [%0], [%1, {%3, %4}], [%2], %5;"
    :: "r"(dst), "l"(m), "r"(bar), "r"(c0), "r"(c1), "h"((uint16_t)3) : "memory");
}
__device__ __forceinline__ void tma_ld_mc_hint(uint32_t dst, const CUtensorMap* m, int c0, int c1, uint32_t bar, uint64_t pol) {
  asm volatile("cp.async.bulk.tensor.2d.shared::cluster.global.mbarrier::complete_tx::bytes.multicast::cluster.L2::cache_hint [%0], [%1, {%3, %4}], [%2], %5, %6;"
    :: "r"(dst), "l"(m), "r"(bar), "r"(c0), "r"(c1), "h"((uint16_t)3), "l"(pol) : "memory");
}
__device__ __forceinline__ void tma_ld3_hint(uint32_t dst, const CUtensorMap* m, int row, int blk, uint32_t bar, uint64_t pol) {
  asm volatile("cp.async.bulk.tensor.3d.shared::cluster.global.mbarrier::complete_tx::bytes.L2::cache_hint [%0], [%1, {0, %3, %4}], [%2], %5;"
    :: "r"(dst), "l"(m), "r"(bar), "r"(row), "r"(blk), "l"(pol) : "memory");
}
__device__ __forceinline__ void tma_st(const CUtensorMap* m, int c0, int c1, uint32_t src) {
  asm volatile("cp.async.bulk.tensor.2d.global.shared::cta.bulk_group [%0, {%2, %3}], [%1];" :: "l"(m), "r"(src), "r"(c0), "r"(c1) : "memory");
}
__device__ __forceinline__ void tma_prefetch_desc(const CUtensorMap* m) { asm volatile("prefetch.tensormap [%0];" :: "l"(m) : "memory"); }
__device__ __forceinline__ void l2_prefetch(const void* p, uint32_t bytes) { asm volatile("cp.async.bulk.prefetch.L2.global [%0], %1;" :: "l"(p), "r"(bytes) : "memory"); }
__device__ __forceinline__ void bulk_commit() { asm volatile("cp.async.bulk.commit_group;" ::: "memory"); }
__device__ __forceinline__ void bulk_wait_read() { asm volatile("cp.async.bulk.wait_group.read 0;" ::: "memory"); }
__device__ __forceinline__ void bulk_wait_all() { asm volatile("cp.async.bulk.wait_group 0;" ::: "memory"); }
__device__ __forceinline__ void fence_async_smem() { asm volatile("fence.proxy.async.shared::cta;" ::: "memory"); }
__device__ __forceinline__ void fence_async_global() { asm volatile("fence.proxy.async.global;" ::: "memory"); }
__device__ __forceinline__ void fence_acquire_gpu() { asm volatile("fence.acquire.gpu;" ::: "memory"); }
__device__ __forceinline__ void fence_release_gpu() { asm volatile("fence.release.gpu;" ::: "memory"); }
__device__ __forceinline__ void st_async_f32x4(uint32_t cluster_addr, const float* v, uint32_t cluster_bar) {
  asm volatile("st.async.weak.shared::cluster.mbarrier::complete_tx::bytes.v4.f32 [%0], {%1,%2,%3,%4}, [%5];"
    :: "r"(cluster_addr), "f"(v[0]), "f"(v[1]), "f"(v[2]), "f"(v[3]), "r"(cluster_bar) : "memory");
}
__device__ __forceinline__ void nb_sync(int id, int n) { asm volatile("bar.sync %0, %1;" :: "r"(id), "r"(n) : "memory"); }
__device__ __forceinline__ void nb_arrive(int id, int n) { asm volatile("bar.arrive %0, %1;" :: "r"(id), "r"(n) : "memory"); }
__device__ __forceinline__ void wg_fence() { asm volatile("wgmma.fence.sync.aligned;" ::: "memory"); }
__device__ __forceinline__ void wg_commit() { asm volatile("wgmma.commit_group.sync.aligned;" ::: "memory"); }
template <int N> __device__ __forceinline__ void wg_wait() { asm volatile("wgmma.wait_group.sync.aligned %0;" :: "n"(N) : "memory"); }
template <int N> __device__ __forceinline__ void reg_fence(float* a) {
#pragma unroll
  for (int i = 0; i < N; i++) asm volatile("" : "+f"(a[i]) :: "memory");
}
template <int N> __device__ __forceinline__ void reg_fence(uint32_t* a) {
#pragma unroll
  for (int i = 0; i < N; i++) asm volatile("" : "+r"(a[i]) :: "memory");
}
__device__ __forceinline__ uint64_t mk_desc(uint32_t addr, uint32_t lbo) {
  return (uint64_t)((addr & 0x3FFFF) >> 4) | ((uint64_t)(lbo >> 4) << 16) | ((uint64_t)(1024 >> 4) << 32) | (1ull << 62);
}

__device__ __forceinline__ uint64_t policy_evict_first() { uint64_t pol; asm("createpolicy.fractional.L2::evict_first.b64 %0, 1.0;" : "=l"(pol)); return pol; }
__device__ __forceinline__ uint32_t ld_relaxed(const uint32_t* p) { uint32_t v; asm volatile("ld.relaxed.gpu.global.u32 %0, [%1];" : "=r"(v) : "l"(p) : "memory"); return v; }
__device__ __forceinline__ void st_relaxed(uint32_t* p, uint32_t v) { asm volatile("st.relaxed.gpu.global.u32 [%0], %1;" :: "l"(p), "r"(v) : "memory"); }
__device__ __forceinline__ void red_add_relaxed(uint32_t* p, uint32_t v) { asm volatile("red.relaxed.gpu.global.add.u32 [%0], %1;" :: "l"(p), "r"(v) : "memory"); }
__device__ __forceinline__ uint2 ld_pkt8(const uint2* p) {
  uint2 v; asm volatile("{\n.reg .b64 t;\nld.relaxed.gpu.global.b64 t, [%2];\nmov.b64 {%0,%1}, t;\n}" : "=r"(v.x), "=r"(v.y) : "l"(p) : "memory"); return v;
}
__device__ __forceinline__ uint4 ld_pkt8x2(const uint4* p) {
  uint4 v; asm volatile("{\n.reg .b64 a, b;\nld.relaxed.gpu.global.v2.b64 {a, b}, [%4];\nmov.b64 {%0,%1}, a;\nmov.b64 {%2,%3}, b;\n}"
    : "=r"(v.x), "=r"(v.y), "=r"(v.z), "=r"(v.w) : "l"(p) : "memory"); return v;
}
__device__ __forceinline__ void st_pkt8(uint2* p, uint32_t a, uint32_t b) {
  asm volatile("{\n.reg .b64 t;\nmov.b64 t, {%1,%2};\nst.relaxed.gpu.global.b64 [%0], t;\n}" :: "l"(p), "r"(a), "r"(b) : "memory");
}
__device__ __forceinline__ uint4 ld_pkt16(const uint4* p) {
  uint4 v; asm volatile("{\n.reg .b128 t;\n.reg .b64 a, b;\nld.relaxed.gpu.global.b128 t, [%4];\nmov.b128 {a, b}, t;\nmov.b64 {%0,%1}, a;\nmov.b64 {%2,%3}, b;\n}"
    : "=r"(v.x), "=r"(v.y), "=r"(v.z), "=r"(v.w) : "l"(p) : "memory"); return v;
}
__device__ __forceinline__ void st_pkt16(uint4* p, uint32_t x, uint32_t y, uint32_t z, uint32_t w) {
  asm volatile("{\n.reg .b128 t;\n.reg .b64 a, b;\nmov.b64 a, {%1,%2};\nmov.b64 b, {%3,%4};\nmov.b128 t, {a, b};\nst.relaxed.gpu.global.b128 [%0], t;\n}"
    :: "l"(p), "r"(x), "r"(y), "r"(z), "r"(w) : "memory");
}
__device__ __forceinline__ void cp_async16(uint32_t dst, const void* src) { asm volatile("cp.async.cg.shared.global [%0], [%1], 16;" :: "r"(dst), "l"(src) : "memory"); }
__device__ __forceinline__ void cp_async_wait() { asm volatile("cp.async.wait_all;" ::: "memory"); }
__device__ __forceinline__ uint32_t lds32(uint32_t a) { uint32_t v; asm volatile("ld.shared.u32 %0, [%1];" : "=r"(v) : "r"(a) : "memory"); return v; }
__device__ __forceinline__ float lds_f32(uint32_t a) { float v; asm volatile("ld.shared.f32 %0, [%1];" : "=f"(v) : "r"(a) : "memory"); return v; }
__device__ __forceinline__ uint2 lds64(uint32_t a) { uint2 v; asm volatile("ld.shared.v2.u32 {%0,%1}, [%2];" : "=r"(v.x), "=r"(v.y) : "r"(a) : "memory"); return v; }
__device__ __forceinline__ uint4 lds128(uint32_t a) { uint4 v; asm volatile("ld.shared.v4.u32 {%0,%1,%2,%3}, [%4];" : "=r"(v.x), "=r"(v.y), "=r"(v.z), "=r"(v.w) : "r"(a) : "memory"); return v; }
__device__ __forceinline__ void sts32(uint32_t a, uint32_t v) { asm volatile("st.shared.u32 [%0], %1;" :: "r"(a), "r"(v) : "memory"); }
__device__ __forceinline__ void sts64(uint32_t a, uint32_t x, uint32_t y) { asm volatile("st.shared.v2.u32 [%0], {%1,%2};" :: "r"(a), "r"(x), "r"(y) : "memory"); }
__device__ __forceinline__ void sts128(uint32_t a, uint32_t x, uint32_t y, uint32_t z, uint32_t w) { asm volatile("st.shared.v4.u32 [%0], {%1,%2,%3,%4};" :: "r"(a), "r"(x), "r"(y), "r"(z), "r"(w) : "memory"); }
__device__ __forceinline__ void stsm4(uint32_t a, uint32_t x, uint32_t y, uint32_t z, uint32_t w) {
  asm volatile("stmatrix.sync.aligned.m8n8.x4.shared.b16 [%0], {%1,%2,%3,%4};" :: "r"(a), "r"(x), "r"(y), "r"(z), "r"(w) : "memory");
}
__device__ __forceinline__ void ldsm4(uint32_t a, uint32_t* r) {
  asm volatile("ldmatrix.sync.aligned.m8n8.x4.shared.b16 {%0,%1,%2,%3}, [%4];" : "=r"(r[0]), "=r"(r[1]), "=r"(r[2]), "=r"(r[3]) : "r"(a) : "memory");
}
__device__ __forceinline__ void ldsm4t(uint32_t a, uint32_t* r) {
  asm volatile("ldmatrix.sync.aligned.m8n8.x4.trans.shared.b16 {%0,%1,%2,%3}, [%4];" : "=r"(r[0]), "=r"(r[1]), "=r"(r[2]), "=r"(r[3]) : "r"(a) : "memory");
}
__device__ __forceinline__ void mma16816(float* d, const uint32_t* a, uint32_t b0, uint32_t b1) {
  asm volatile("mma.sync.aligned.m16n8k16.row.col.f32.bf16.bf16.f32 {%0,%1,%2,%3}, {%4,%5,%6,%7}, {%8,%9}, {%0,%1,%2,%3};"
    : "+f"(d[0]), "+f"(d[1]), "+f"(d[2]), "+f"(d[3]) : "r"(a[0]), "r"(a[1]), "r"(a[2]), "r"(a[3]), "r"(b0), "r"(b1));
}
__device__ __forceinline__ void mma1688(float* d, uint32_t a0, uint32_t a1, uint32_t b0) {
  asm volatile("mma.sync.aligned.m16n8k8.row.col.f32.bf16.bf16.f32 {%0,%1,%2,%3}, {%4,%5}, {%6}, {%0,%1,%2,%3};"
    : "+f"(d[0]), "+f"(d[1]), "+f"(d[2]), "+f"(d[3]) : "r"(a0), "r"(a1), "r"(b0));
}
__device__ __forceinline__ uint32_t pack2(float lo, float hi) { uint32_t r; asm("cvt.rn.bf16x2.f32 %0, %1, %2;" : "=r"(r) : "f"(hi), "f"(lo)); return r; }
__device__ __forceinline__ float lo2f(uint32_t v) { return __uint_as_float(v << 16); }
__device__ __forceinline__ float hi2f(uint32_t v) { return __uint_as_float(v & 0xffff0000u); }
__device__ __forceinline__ uint32_t hmul2(uint32_t a, uint32_t b) { uint32_t r; asm("mul.rn.bf16x2 %0, %1, %2;" : "=r"(r) : "r"(a), "r"(b)); return r; }
__device__ __forceinline__ uint32_t hadd2(uint32_t a, uint32_t b) { uint32_t r; asm("add.rn.bf16x2 %0, %1, %2;" : "=r"(r) : "r"(a), "r"(b)); return r; }
__device__ __forceinline__ uint32_t hsub2(uint32_t a, uint32_t b) { uint32_t r; asm("sub.rn.bf16x2 %0, %1, %2;" : "=r"(r) : "r"(a), "r"(b)); return r; }
__device__ __forceinline__ uint32_t hfma2(uint32_t a, uint32_t b, uint32_t c) { uint32_t r; asm("fma.rn.bf16x2 %0, %1, %2, %3;" : "=r"(r) : "r"(a), "r"(b), "r"(c)); return r; }
__device__ __forceinline__ float rbf(float v) { return lo2f(pack2(v, 0.f)); }
__device__ __forceinline__ float ex2(float v) { float r; asm("ex2.approx.ftz.f32 %0, %1;" : "=f"(r) : "f"(v)); return r; }
__device__ __forceinline__ float rcp_f(float v) { float r; asm("rcp.approx.ftz.f32 %0, %1;" : "=f"(r) : "f"(v)); return r; }
__device__ __forceinline__ float sqrt_f(float v) { float r; asm("sqrt.approx.ftz.f32 %0, %1;" : "=f"(r) : "f"(v)); return r; }
__device__ __forceinline__ float sigmoid_f(float v) { return rcp_f(1.f + ex2(-1.4426950408889634f * v)); }
__device__ __forceinline__ float silu_f(float v) { return v * sigmoid_f(v); }
constexpr uint32_t ONE2 = 0x3f803f80u;

#define R8(a,o) "+f"(a[o+0]), "+f"(a[o+1]), "+f"(a[o+2]), "+f"(a[o+3]), "+f"(a[o+4]), "+f"(a[o+5]), "+f"(a[o+6]), "+f"(a[o+7])
#define R64(a,o) R8(a,o), R8(a,o+8), R8(a,o+16), R8(a,o+24), R8(a,o+32), R8(a,o+40), R8(a,o+48), R8(a,o+56)
#define D64 "{%0,%1,%2,%3,%4,%5,%6,%7,%8,%9,%10,%11,%12,%13,%14,%15,%16,%17,%18,%19,%20,%21,%22,%23,%24,%25,%26,%27,%28,%29,%30,%31," \
            "%32,%33,%34,%35,%36,%37,%38,%39,%40,%41,%42,%43,%44,%45,%46,%47,%48,%49,%50,%51,%52,%53,%54,%55,%56,%57,%58,%59,%60,%61,%62,%63"
#define D128 D64 ",%64,%65,%66,%67,%68,%69,%70,%71,%72,%73,%74,%75,%76,%77,%78,%79,%80,%81,%82,%83,%84,%85,%86,%87,%88,%89,%90,%91,%92,%93,%94,%95," \
            "%96,%97,%98,%99,%100,%101,%102,%103,%104,%105,%106,%107,%108,%109,%110,%111,%112,%113,%114,%115,%116,%117,%118,%119,%120,%121,%122,%123,%124,%125,%126,%127"

template <int TB> __device__ __forceinline__ void wgmma_ss128(float* d, uint64_t da, uint64_t db, int acc) {
  asm volatile("{\n.reg .pred p;\nsetp.ne.b32 p, %66, 0;\nwgmma.mma_async.sync.aligned.m64n128k16.f32.bf16.bf16 " D64 "}, %64, %65, p, 1, 1, 0, %67;\n}"
    : R64(d, 0) : "l"(da), "l"(db), "r"(acc), "n"(TB));
}
template <int TB> __device__ __forceinline__ void wgmma_rs128(float* d, const uint32_t* a, uint64_t db, int acc) {
  asm volatile("{\n.reg .pred p;\nsetp.ne.b32 p, %69, 0;\nwgmma.mma_async.sync.aligned.m64n128k16.f32.bf16.bf16 " D64 "}, {%64,%65,%66,%67}, %68, p, 1, 1, %70;\n}"
    : R64(d, 0) : "r"(a[0]), "r"(a[1]), "r"(a[2]), "r"(a[3]), "l"(db), "r"(acc), "n"(TB));
}
template <int TB> __device__ __forceinline__ void wgmma_ss256(float* d, uint64_t da, uint64_t db, int acc) {
  asm volatile("{\n.reg .pred p;\nsetp.ne.b32 p, %130, 0;\nwgmma.mma_async.sync.aligned.m64n256k16.f32.bf16.bf16 " D128 "}, %128, %129, p, 1, 1, 0, %131;\n}"
    : R64(d, 0), R64(d, 64) : "l"(da), "l"(db), "r"(acc), "n"(TB));
}

#define W8(a,o) "=f"(a[o+0]), "=f"(a[o+1]), "=f"(a[o+2]), "=f"(a[o+3]), "=f"(a[o+4]), "=f"(a[o+5]), "=f"(a[o+6]), "=f"(a[o+7])
#define W64(a,o) W8(a,o), W8(a,o+8), W8(a,o+16), W8(a,o+24), W8(a,o+32), W8(a,o+40), W8(a,o+48), W8(a,o+56)
template <int TB> __device__ __forceinline__ void wgmma_ss128_z(float* d, uint64_t da, uint64_t db) {
  asm volatile("wgmma.mma_async.sync.aligned.m64n128k16.f32.bf16.bf16 " D64 "}, %64, %65, 0, 1, 1, 0, %66;"
    : W64(d, 0) : "l"(da), "l"(db), "n"(TB));
}
template <int TB> __device__ __forceinline__ void wgmma_rs128_z(float* d, const uint32_t* a, uint64_t db) {
  asm volatile("wgmma.mma_async.sync.aligned.m64n128k16.f32.bf16.bf16 " D64 "}, {%64,%65,%66,%67}, %68, 0, 1, 1, %69;"
    : W64(d, 0) : "r"(a[0]), "r"(a[1]), "r"(a[2]), "r"(a[3]), "l"(db), "n"(TB));
}
template <int TB> __device__ __forceinline__ void wgmma_ss256_z(float* d, uint64_t da, uint64_t db) {
  asm volatile("wgmma.mma_async.sync.aligned.m64n256k16.f32.bf16.bf16 " D128 "}, %128, %129, 0, 1, 1, 0, %130;"
    : W64(d, 0), W64(d, 64) : "l"(da), "l"(db), "n"(TB));
}

template <int TB> __device__ __forceinline__ void wgmma_rs256(float* d, const uint32_t* a, uint64_t db) {
  asm volatile("wgmma.mma_async.sync.aligned.m64n256k16.f32.bf16.bf16 " D128 "}, {%128,%129,%130,%131}, %132, 1, 1, 1, %133;"
    : R64(d, 0), R64(d, 64) : "r"(a[0]), "r"(a[1]), "r"(a[2]), "r"(a[3]), "l"(db), "n"(TB));
}
template <int TB> __device__ __forceinline__ void wgmma_rs256_z(float* d, const uint32_t* a, uint64_t db) {
  asm volatile("wgmma.mma_async.sync.aligned.m64n256k16.f32.bf16.bf16 " D128 "}, {%128,%129,%130,%131}, %132, 0, 1, 1, %133;"
    : W64(d, 0), W64(d, 64) : "r"(a[0]), "r"(a[1]), "r"(a[2]), "r"(a[3]), "l"(db), "n"(TB));
}
#define D32 "{%0,%1,%2,%3,%4,%5,%6,%7,%8,%9,%10,%11,%12,%13,%14,%15,%16,%17,%18,%19,%20,%21,%22,%23,%24,%25,%26,%27,%28,%29,%30,%31}"
__device__ __forceinline__ void wgmma_rs64(float* d, const uint32_t* a, uint64_t db) {
  asm volatile("wgmma.mma_async.sync.aligned.m64n64k16.f32.bf16.bf16 " D32 ", {%32,%33,%34,%35}, %36, 1, 1, 1, 0;"
    : R8(d, 0), R8(d, 8), R8(d, 16), R8(d, 24) : "r"(a[0]), "r"(a[1]), "r"(a[2]), "r"(a[3]), "l"(db));
}
__device__ __forceinline__ void wgmma_rs64_z(float* d, const uint32_t* a, uint64_t db) {
  asm volatile("wgmma.mma_async.sync.aligned.m64n64k16.f32.bf16.bf16 " D32 ", {%32,%33,%34,%35}, %36, 0, 1, 1, 0;"
    : W8(d, 0), W8(d, 8), W8(d, 16), W8(d, 24) : "r"(a[0]), "r"(a[1]), "r"(a[2]), "r"(a[3]), "l"(db));
}
__device__ __forceinline__ void issue_qk(float* S, const uint32_t* Q, uint64_t dk) {
  wgmma_rs64_z(S, Q, dk);
#pragma unroll
  for (int kk = 1; kk < 8; kk++) wgmma_rs64(S, Q + 4 * kk, dk + (kk >> 2) * 512 + (kk & 3) * 2);
}
__device__ __forceinline__ void issue_pv(float* O, const uint32_t* P, uint64_t dv, int acc) {
#pragma unroll
  for (int kk = 0; kk < 4; kk++) wgmma_rs128<1>(O, P + 4 * kk, dv + kk * 128, kk ? 1 : acc);
}

#define TS(i)
#define TSC(i)
#define TSX(i)
#define TSY(k) do { if ((tid & 127) == 0) TS((k) + 40 * wg); } while (0)
#define TT(k)
#define TV(k)
#define TR(k)
#define TQ(k)
#define TH(k)
#define TA(k)
#define TAFLUSH()

struct SoftmaxState { float c0, c1, l0, l1; bool shifted; };
constexpr float SM_SCALE = 0.08838834764831845f * 1.4426950408889634f;
__device__ __forceinline__ void softmax_start(SoftmaxState& z) { z.c0 = z.c1 = z.l0 = z.l1 = 0.f; z.shifted = false; }
__device__ __forceinline__ void softmax_half(float* S, uint32_t* P, float* O, SoftmaxState& z, bool first, uint32_t tag) {
  const float lo0 = z.l0, lo1 = z.l1;
  float lim = 1.2676506002282294e30f;
  const float low = first ? 8.673617379884035e-19f : 0.f;
  if (z.shifted) {
#pragma unroll
    for (int j = 0; j < 32; j++) S[j] += (j & 2) ? z.c1 : z.c0;
  }
#pragma unroll 1
  while (true) {
    bb_fence(tag);
#pragma unroll
    for (int j = 0; j < 8; j++) {
      const float p0 = ex2(S[4 * j]), p1 = ex2(S[4 * j + 1]), p2 = ex2(S[4 * j + 2]), p3 = ex2(S[4 * j + 3]);
      z.l0 += p0; z.l1 += p2; z.l0 += p1; z.l1 += p3;
      P[2 * j] = pack2(p0, p1); P[2 * j + 1] = pack2(p2, p3);
    }
    if (!__any_sync(0xffffffffu, !(z.l0 < lim && z.l1 < lim && fminf(z.l0, z.l1) >= low) && lim > 0.f)) break;
    float d0 = fmaxf(S[0], S[1]), d1 = fmaxf(S[2], S[3]);
#pragma unroll
    for (int j = 1; j < 8; j++) { d0 = fmaxf(d0, fmaxf(S[4 * j], S[4 * j + 1])); d1 = fmaxf(d1, fmaxf(S[4 * j + 2], S[4 * j + 3])); }
    d0 = fmaxf(d0, __shfl_xor_sync(0xffffffffu, d0, 1)); d1 = fmaxf(d1, __shfl_xor_sync(0xffffffffu, d1, 1));
    d0 = fmaxf(d0, __shfl_xor_sync(0xffffffffu, d0, 2)); d1 = fmaxf(d1, __shfl_xor_sync(0xffffffffu, d1, 2));
    if (!first) { d0 = fmaxf(d0, 0.f); d1 = fmaxf(d1, 0.f); }
    z.shifted = true;
    z.c0 -= d0; z.c1 -= d1;
#pragma unroll
    for (int j = 0; j < 32; j++) S[j] -= (j & 2) ? d1 : d0;
    const float a0 = first ? 1.f : ex2(-d0), a1 = first ? 1.f : ex2(-d1);
    z.l0 = lo0 * a0; z.l1 = lo1 * a1;
    lim = -1.f;
    wg_wait<0>();
    reg_fence<64>(O);
#pragma unroll
    for (int j = 0; j < 16; j++) { O[4 * j] *= a0; O[4 * j + 1] *= a0; O[4 * j + 2] *= a1; O[4 * j + 3] *= a1; }
  }
}

__device__ __forceinline__ void modulate_frags(uint32_t* A, const uint32_t* V, const uint4* R, const uint32_t* ln) {
#pragma unroll
  for (int kk = 0; kk < 4; kk++) {
    const uint4 sa = R[kk >> 1], c1 = R[2 + (kk >> 1)];
#pragma unroll
    for (int j = 0; j < 4; j++) {
      const uint32_t n = hfma2(V[4 * kk + j], ln[(j & 1) * 2 + 1], ln[(j & 1) * 2]);
      A[4 * kk + j] = (kk & 1) ? ((j & 2) ? hfma2(n, c1.w, sa.x) : hfma2(n, c1.z, sa.w)) : ((j & 2) ? hfma2(n, c1.y, sa.z) : hfma2(n, c1.x, sa.y));
    }
  }
}
__device__ __forceinline__ void publish_record(uint4* dst, uint32_t pk, int src, int vec, bool doit) {
  const int r = vec ? 0 : 12;
  const uint32_t x = __shfl_sync(0xffffffffu, pk, src + r), y = __shfl_sync(0xffffffffu, pk, src + ((r + 4) & 12));
  const uint32_t z = __shfl_sync(0xffffffffu, pk, src + ((r + 8) & 12)), w = __shfl_sync(0xffffffffu, pk, src + ((r + 12) & 12));
  if (doit) st_pkt16(dst, ~x, y, z, w);
}
__device__ __forceinline__ void put_record(uint32_t sb, int idx, const uint4& v) {
  sts128(sb + SM_STASH + idx * 16, ~v.x, v.y, v.z, v.w);
  sts128(sb + SM_STASH + 16384 + idx * 16, ~v.x, v.y, v.z, v.w);
}
__device__ __forceinline__ float mod_value(float v, int vec) {
  v = rbf(v);
  return (vec ? rbf(1.f + v) : v) * SM_SCALE;
}

__device__ __forceinline__ void row_rcp(float& l0, float& l1) {
  l0 += __shfl_xor_sync(0xffffffffu, l0, 1); l1 += __shfl_xor_sync(0xffffffffu, l1, 1);
  l0 += __shfl_xor_sync(0xffffffffu, l0, 2); l1 += __shfl_xor_sync(0xffffffffu, l1, 2);
  l0 = rcp_f(l0); l1 = rcp_f(l1);
}
__device__ __forceinline__ void stage_o(const float* O, float r0, float r1, uint32_t stsm_addr) {
#pragma unroll
  for (int kk = 0; kk < 8; kk++) {
    stsm4((stsm_addr + (kk >> 2) * 8192) ^ ((kk & 3) * 32),
          pack2(O[8 * kk + 0] * r0, O[8 * kk + 1] * r0), pack2(O[8 * kk + 2] * r1, O[8 * kk + 3] * r1),
          pack2(O[8 * kk + 4] * r0, O[8 * kk + 5] * r0), pack2(O[8 * kk + 6] * r1, O[8 * kk + 7] * r1));
  }
}

__global__ void __cluster_dims__(2, 1, 1) __launch_bounds__(NTHREADS, 1)
fused_kernel(const Params p, const __grid_constant__ CUtensorMap mH, const __grid_constant__ CUtensorMap mWq,
             const __grid_constant__ CUtensorMap mK, const __grid_constant__ CUtensorMap mV,
             const __grid_constant__ CUtensorMap mO, const __grid_constant__ CUtensorMap mWo,
             const __grid_constant__ CUtensorMap mX, const __grid_constant__ CUtensorMap mOut,
             const __grid_constant__ CUtensorMap mWg, const __grid_constant__ CUtensorMap mWu,
             const __grid_constant__ CUtensorMap mWd, const __grid_constant__ CUtensorMap mWm,
             const __grid_constant__ CUtensorMap mWs, const __grid_constant__ CUtensorMap mWh,
             const __grid_constant__ CUtensorMap mOs) {
  extern __shared__ __align__(1024) uint8_t smem_raw[];
  TH(0);
  const uint32_t sb = smem_u32(smem_raw);
  const int tid = threadIdx.x;
  const int b0 = blockIdx.x;
  const int lane = tid & 31;
  const int role = __shfl_sync(0xffffffffu, tid >> 8, 0);

  if (b0 >= NMAIN) {
    const uint32_t cs = clock();
    const uint32_t tag = ld_relaxed(&g_epoch) + 1;
    const int sp = b0 - NMAIN, vec = 2 + sp;
    const int warp = __shfl_sync(0xffffffffu, tid >> 5, 0);
    float* sc = reinterpret_cast<float*>(smem_raw + SM_STASH);
    float* red = reinterpret_cast<float*>(smem_raw + SM_STASH + 4096);
    const int ridx = (lane >> 3) * 2 * RV + (sp & 1) * RV + 16 * RS + (sp >> 1) * 16 + (warp & 1) * 8 + (lane & 7);
    if (warp < 8) st_pkt16(&g_rec[warp >> 2][0][ridx + (warp & 2) * 16], 0, 0, 0, 0);
#pragma unroll 1
    for (int i = tid; i < 1024; i += NTHREADS) sc[i] = rbf(silu_f(__bfloat162float(p.c[i])));
    if (tid == 0) {
      tma_prefetch_desc(&mWs);
      for (int s = 0; s < NST2; s++) { mbar_init(sb + BAR_FULL2 + 8 * s, 1); mbar_init(sb + BAR_EMPTY2 + 8 * s, 8); }
      fence_async_smem();
      while ((uint32_t)clock() - cs < SPT) {}
    }
    __syncthreads();
    int s = 0; uint32_t ph = 0;
    if (tid == 0) TS(0);
    if (warp == 8) {
      const uint64_t pol = policy_evict_first();
#pragma unroll 1
      for (int n = 0; n < 80; n++) {
        mbar_wait_g(sb + BAR_EMPTY2 + 8 * s, ph ^ 1);
        if (elect_one()) {
          mbar_expect_tx(sb + BAR_FULL2 + 8 * s, 32768);
          if (n < 16) {
            tma_ld_hint(sb + s * ST2, &mWs, (sp & 1) * 1024 + 512 + (n >> 3) * 256 + (sp >> 1) * 128, (n & 7) * 128, sb + BAR_FULL2 + 8 * s, pol);
          } else {
#pragma unroll
            for (int j = 0; j < 4; j++) tma_ld_hint(sb + s * ST2 + j * 8192, &mWm, vec * 1024 + j * 256, (n - 16) * 16, sb + BAR_FULL2 + 8 * s, pol);
          }
        }
        __syncwarp();
        if (++s == NST2) { s = 0; ph ^= 1; }
      }
    } else if (warp < 8) {
      float acc[8];
#pragma unroll
      for (int i = 0; i < 8; i++) acc[i] = 0.f;
      auto stage = [&](uint32_t a0, int da, const float* cp, int dc) {
        mbar_wait_g(sb + BAR_FULL2 + 8 * s, ph);
#pragma unroll
        for (int i = 0; i < 8; i++) {
          const uint4 v = lds128(a0 + s * ST2 + i * da);
          const float c = cp[i * dc];
          acc[0] = fmaf(lo2f(v.x), c, acc[0]); acc[1] = fmaf(hi2f(v.x), c, acc[1]);
          acc[2] = fmaf(lo2f(v.y), c, acc[2]); acc[3] = fmaf(hi2f(v.y), c, acc[3]);
          acc[4] = fmaf(lo2f(v.z), c, acc[4]); acc[5] = fmaf(hi2f(v.z), c, acc[5]);
          acc[6] = fmaf(lo2f(v.w), c, acc[6]); acc[7] = fmaf(hi2f(v.w), c, acc[7]);
        }
        if (__shfl_sync(0xffffffffu, lane, __float_as_uint(acc[7]) & 31) < 32 && lane == 0) mbar_arrive(sb + BAR_EMPTY2 + 8 * s);
        if (++s == NST2) { s = 0; ph ^= 1; }
      };
#pragma unroll 1
      for (int n = 0; n < 16; n++) {
        stage(sb + tid * 16, 4096, sc + (n & 7) * 128 + (tid >> 4), 16);
        if ((n & 7) == 7) {
          float* r2 = red + 2048 + (n & 8) * 256;
#pragma unroll
          for (int i = 0; i < 8; i++) { r2[tid * 8 + i] = acc[i]; acc[i] = 0.f; }
          nb_sync(NB_CONS, 256);
          if (warp < 2) {
            float v0 = 0.f, v1 = 0.f;
#pragma unroll 4
            for (int i = 0; i < 16; i++) { const float2 e = reinterpret_cast<const float2*>(r2)[i * 64 + tid]; v0 += e.x; v1 += e.y; }
            publish_record(&g_rec[tag & 1][0][ridx + (n >> 3) * 32], pack2(mod_value(v0, sp & 1), mod_value(v1, sp & 1)),
                           (lane & 4) * 4 + (lane & 3), sp & 1, true);
          }
          if (tid == 0) TS(1 + (n >> 3));
        }
      }
#pragma unroll 1
      for (int n = 0; n < 64; n++) {
        stage(sb + ((tid >> 5) & 3) * 8192 + (tid >> 7) * 4096 + (tid & 31) * 16, 512, sc + n * 16 + (tid >> 7) * 8, 1);
      }
#pragma unroll
      for (int i = 0; i < 8; i++) red[(tid >> 7) * 1024 + (tid & 127) * 8 + i] = acc[i];
    }
    __syncthreads();
    float dot = 0.f;
#pragma unroll 1
    for (int i = tid; i < 512; i += NTHREADS) {
      uint32_t v = pack2(red[2 * i] + red[1024 + 2 * i], red[2 * i + 1] + red[1024 + 2 * i + 1]);
      st_pkt8(&g_mod[vec * 512 + i], v, tag);
      if (vec == 4) v = hadd2(v, ONE2);
      const uint32_t wr = reinterpret_cast<const uint32_t*>(p.w_r)[i];
      dot = fmaf(lo2f(v), lo2f(wr), fmaf(hi2f(v), hi2f(wr), dot));
    }
#pragma unroll
    for (int o = 16; o; o >>= 1) dot += __shfl_xor_sync(0xffffffffu, dot, o);
    if (lane == 0) sc[warp] = dot;
    __syncthreads();
    if (tid == 0) {
      dot = 0.f;
      for (int w = 0; w < 12; w++) dot += sc[w];
      fence_release_gpu();
      st_pkt8(&g_vdone[(vec - 2) * 16], __float_as_uint(dot), tag);
      TS(11);
#pragma unroll 1
      for (int i = 0; i < 128; i++) {
        const int u = i * 4 + (b0 - NMAIN);
        l2_prefetch(p.wo + (size_t)((4 * ((u >> 4) & 7) + (u >> 7)) * 128 + (u & 15) * 8) * 1024, 16384);
        __nanosleep(PFW);
      }
    }
    return;
  }

  const uint32_t rank = b0 & 1;
  const bool slab = !(b0 & 32), late = b0 & 16;
  const uint32_t c0 = clock();
  if (tid == 352) TS(0);
  const uint32_t slab_addr = sb + SM_WSLAB + (tid >> 5) * 4096 + (lane & 3) * 128 + (lane & 4) * 16 + (((lane >> 3) ^ lane) & 3) * 16;
  auto load_slab = [&]() {
    const bf16* wp = p.w_mod + (size_t)(512 * rank + 2 * (tid & ~31) + 2 * (lane & 3) + ((lane >> 2) & 1)) * 6144 + 32 * (b0 >> 1) + 8 * (lane >> 3);
    const uint64_t pef = policy_evict_first();
#pragma unroll
    for (int i = 0; i < 8; i++)
      asm volatile("cp.async.cg.shared.global.L2::cache_hint [%0], [%1], 16, %2;"
        :: "r"(slab_addr + i * 512), "l"(wp + (size_t)i * 8 * 6144), "l"(pef) : "memory");
  };
  if (tid == 256) {
    mbar_init(sb + BAR_XH, 1);
    fence_async_smem();
    mbar_expect_tx(sb + BAR_XH, 32768);
#pragma unroll
    for (int i = 0; i < 2; i++)
      asm volatile("cp.async.bulk.shared::cluster.global.mbarrier::complete_tx::bytes [%0], [%1], 16384, [%2];"
        :: "r"(sb + SM_XROW + i * ST1), "l"(p.x + (size_t)b0 * 16384 + i * 8192), "r"(sb + BAR_XH) : "memory");
  }
  __syncwarp();
  uint32_t cw[8];
#pragma unroll
  for (int i = 0; i < 8; i++) cw[i] = 0;
  if (!role && slab) {
#pragma unroll
    for (int i = 0; i < 8; i++) cw[i] = ld_relaxed(reinterpret_cast<const uint32_t*>(p.c) + 256 * rank + (tid & ~28) + 4 * i);
  }
  uint32_t epoch = 0;
  if (!role) epoch = ld_relaxed(&p.sc->epoch[lane]);
  if (!role && slab && !late) load_slab();
#define TILE_ROLES() \
  mbar_wait(sb + BAR_ROLE, 0); \
  const int b = 2 * __shfl_sync(0xffffffffu, lds32(sb + SM_ROLE), 0) + rank; \
  const int rt = b >> 3;     \
  const int ct = b & 7;

  if (role) {
    asm volatile("setmaxnreg.dec.sync.aligned.u32 24;");
    const int warp = __shfl_sync(0xffffffffu, tid >> 5, 0);
    if (tid == 256) {
      mbar_init(sb + BAR_RED, 1); mbar_init(sb + BAR_WH, 1);
      for (int s = 0; s < 2; s++) mbar_init(sb + BAR_OF + 8 * s, 1);
      mbar_init(sb + BAR_ROLE, 1);
      for (int s = 0; s < 5; s++) { mbar_init(sb + BAR_FULL1 + 8 * s, 1); mbar_init(sb + BAR_EMPTY1 + 8 * s, 4); }
      for (int s = 0; s < 2; s++) { mbar_init(sb + BAR_STASH + 8 * s, 1); mbar_init(sb + BAR_X + 8 * s, 1); }
      for (int s = 0; s < 4; s++) mbar_init(sb + BAR_HS + 8 * s, 1);
      mbar_init(sb + BAR_G, 16); mbar_init(sb + BAR_T1, 1); mbar_init(sb + BAR_HF, 1);
      mbar_init(sb + BAR_SFREE, 4); mbar_init(sb + BAR_TFREE, 8);
      mbar_init(sb + BAR_FFN, 4); mbar_init(sb + BAR_FFN + 8, 2);
      mbar_init(sb + BAR_CAND, 1); mbar_init(sb + BAR_VEC, 32); for (int s = 0; s < 3; s++) mbar_init(sb + BAR_TAB + 8 * s, 32);
      mbar_expect_tx(sb + BAR_RED, 1024);
      mbar_expect_tx(sb + BAR_ROLE, 4);
      asm volatile("fence.mbarrier_init.release.cluster;" ::: "memory");
    }
    __syncwarp();
    asm volatile("barrier.cluster.arrive.relaxed.aligned;" ::: "memory");
    const int ridx = ((lane >> 1) & 3) * 2 * RV + (b0 >> 6) * RV + ((b0 >> 1) & 31) * RS + 2 * rank + (lane & 1) + (lane >> 3) * 4;
    if (warp == 11 && slab && lane < 2 * RS) { st_pkt16(&g_rec[0][0][ridx], 0, 0, 0, 0); st_pkt16(&g_rec[1][0][ridx], 0, 0, 0, 0); }
    if (tid == 256) {
      tma_prefetch_desc(&mWq); tma_prefetch_desc(&mX); tma_prefetch_desc(&mH); tma_prefetch_desc(&mK); tma_prefetch_desc(&mV); tma_prefetch_desc(&mOs);
    }
    uint32_t pairid = 0;
    if (tid == 320 && rank == 0) {
      uint32_t t;
      asm("mov.u32 %0, %%smid;" : "=r"(t));
      t >>= 1;
      uint32_t grp = ((0x73216540u >> (4 * ((t < 32 ? t : t < 60 ? 1 + (t - 32) % 7 : t < 62 ? t - 54 : 0) & 7))) & 7) - 1, slot;
      int it = 0;
      do {
        grp = (grp + 1) & 7;
        asm volatile("atom.relaxed.gpu.global.add.u32 %0, [%1], 1;" : "=r"(slot) : "l"(&p.sc->ticket[grp * 32]) : "memory");
        spin_guard(it);
      } while (slot >= 8);
      pairid = slot * 8 + grp;
    }
    __syncwarp();
    asm volatile("barrier.cluster.wait.aligned;" ::: "memory");
    if (tid == 320 && rank == 0) {
#pragma unroll
      for (int r = 0; r < 2; r++)
        asm volatile("st.async.weak.shared::cluster.mbarrier::complete_tx::bytes.b32 [%0], %1, [%2];"
          :: "r"(mapa(sb + SM_ROLE, r)), "r"(pairid), "r"(mapa(sb + BAR_ROLE, r)) : "memory");
    }
    __syncwarp();
    const uint32_t tag = ld_relaxed(&g_epoch) + 1;
    if (warp == 8) {
      TILE_ROLES();
      const int kvrow = (ct >> 1) * 2048 + 1536, arow = rt * 128 + rank * 64;
      const uint64_t pef = policy_evict_first();
#pragma unroll 1
      for (int pair = 0; pair < 2; pair++) {
        const int wblk = (4 * ct + 2 * pair) * 2;
        if (pair) { mbar_wait_g(sb + BAR_HF, 0); fence_async_global(); }
#pragma unroll 1
        for (int n = 0; n < 16; n++) {
          const uint32_t s = n & 3, st = sb + SM_RING + s * ST1, fb = sb + BAR_FULL1 + 8 * s;
          if (n == 2 && pair == 0) mbar_wait_g(sb + BAR_G, 0);
          mbar_wait_g(fb + (BAR_EMPTY1 - BAR_FULL1), ((n >> 2) & 1) ^ 1);
          if (elect_one()) {
            mbar_expect_tx(fb, 49152);
            if (pair) tma_ld_mc_hint(st + rank * 8192, &mH, n * 64, arow, fb, pef); else
            tma_ld_mc(st + rank * 8192, pair ? &mH : &mX, n * 64, arow, fb);
            tma_ld3_hint(st + 16384, &mWq, n * 64, wblk, fb, pef);
          }
          __syncwarp();
        }
#pragma unroll 1
        for (int n = 0; n < 16; n++) {
          const uint32_t s = n & 3, st = sb + SM_RING + s * ST1 + rank * 8192, fb = sb + BAR_FULL1 + 8 * s;
          const int h0 = n == 0 ? 0 : n == 15 ? 14 : n + 1, h1 = n == 0 ? 1 : n == 15 ? 15 : n - 1;
          mbar_wait_g(fb + (BAR_EMPTY1 - BAR_FULL1), ((n >> 2) & 1) ^ 1);
          if (elect_one()) {
            mbar_expect_tx(fb, 32768);
            tma_ld_mc(st, n == 15 ? &mV : &mK, rank * 64, kvrow + (h0 & 7) * 64, fb);
            tma_ld_mc(st + 16384, n == 0 ? &mK : &mV, rank * 64, kvrow + (h1 & 7) * 64, fb);
            if (n == 3 && pair == 1) mbar_arrive(sb + BAR_T1);
          }
          __syncwarp();
        }
      }
      {
        uint32_t s = 0, ph = 1;
#pragma unroll 1
        for (int half = 0; half < 2; half++) {
          mbar_wait_g(sb + BAR_OF + 8 * half, 0);
          fence_async_global();
#pragma unroll 1
          for (int n = 32 * half; n < 32 * half + 32; n++) {
            const uint32_t st = sb + SM_RING + s * ST1, fb = sb + BAR_FULL1 + 8 * s;
            const int k0 = ((n & 14) * 2 + (n >> 4)) * 128 + (n & 1) * 64;
            mbar_wait_g(n == 8 ? sb + BAR_SFREE : fb + (BAR_EMPTY1 - BAR_FULL1), n == 8 ? 0 : ph ^ (s >> 2));
            if (elect_one()) {
              mbar_expect_tx(fb, 32768);
              tma_ld_mc_hint(st + rank * 8192, &mO, k0, arow, fb, pef);
              tma_ld3_hint(st + 16384, &mWo, k0, 2 * ct, fb, pef);
            }
            __syncwarp();
            if (++s == 5 || n == 3) { s = 0; ph ^= 1; }
          }
        }
        if (b < NFFN) {
#pragma unroll 1
          for (s = 0; s < 2; s++) {
            mbar_wait_g(sb + BAR_EMPTY1 + 8 * s, 0);
            if (elect_one()) {
              mbar_expect_tx(sb + BAR_FFN + 8, 32768);
              tma_ld3_hint(sb + SM_RING + s * ST1, &mWd, b * 32, s * 8, sb + BAR_FFN + 8, pef);
            }
            __syncwarp();
          }
        }
      }
    } else if (warp <= 10) {
      const int w = warp - 9;
      if (slab && late && w == 0 && lane == 0) {
        tma_prefetch_desc(&mWh);
        mbar_expect_tx(sb + BAR_WH, 32768);
        while ((uint32_t)clock() - c0 < WL) {}
        const uint64_t pef = policy_evict_first();
#pragma unroll
        for (int i = 0; i < 2; i++) tma_ld_hint(sb + SM_WSLAB + i * 16384, &mWh, 32 * (b0 >> 1), 512 * rank + 256 * i, sb + BAR_WH, pef);
      }
      __syncwarp();
      TILE_ROLES();
      const uint32_t st = sb + SM_STASH + w * 16384;
#pragma unroll 1
      for (int j = 0; j < 2; j++) {
        nb_sync(NB_OST + w, 160);
        if (elect_one()) {
          fence_async_smem();
          tma_st(&mH, (2 * ct + j) * 64, rt * 128 + w * 64, st + 4096);
          bulk_commit();
          bulk_wait_read();
          mbar_arrive(sb + BAR_HS + 16 * w + 8 * j);
          if (j) {
            bulk_wait_all();
            fence_async_global();
            fence_release_gpu();
            red_add_relaxed(&g_hflag[rt * 32], 1);
          }
        }
        __syncwarp();
      }
#pragma unroll 1
      for (int r = 0; r < 4; r++) {
        nb_sync(NB_OST + w, 160);
        if (elect_one()) {
          fence_async_smem();
          const int hcol = (4 * ct + r) * 128;
#pragma unroll 1
          for (int i = 0; i < 8; i++) {
            tma_st(&mOs, hcol + (i & 4) * 16, rt * 128 + w * 64 + (i & 3) * 16, st + i * 2048);
            __nanosleep(r == 3 ? OP3 : OP0);
          }
          bulk_commit();
          bulk_wait_read();
          if (r < 2) {
            mbar_arrive(sb + BAR_STASH + 8 * w);
          } else if (r == 2) {
            mbar_expect_tx(sb + BAR_X + 8 * w, 16384);
            tma_ld_hint(st, &mX, ct * 128, rt * 128 + w * 64, sb + BAR_X + 8 * w, policy_evict_first());
            tma_ld_hint(st + 8192, &mX, ct * 128 + 64, rt * 128 + w * 64, sb + BAR_X + 8 * w, policy_evict_first());
          } else {
            mbar_arrive_cl(mapa(sb + BAR_SFREE, 0)); mbar_arrive_cl(mapa(sb + BAR_SFREE, 1));
          }
          bulk_wait_all();
          fence_async_global();
          fence_release_gpu();
          red_add_relaxed(&g_oflag[(rt * 4 + r) * 32], 1);
        }
        __syncwarp();
      }
      nb_sync(NB_OST + w, 160);
      int skip = -1;
      mbar_wait_g(sb + BAR_CAND, 0);
      const bool has_cand = (lds32(sb + SM_CAND) >> 6) == w;
      if (has_cand) {
        nb_sync(NB_WIN + w, 160);
        skip = (int)lds32(sb + SM_WROW + 4 * w) - (rt * 128 + w * 64);
      }
      if ((unsigned)skip >= 64u) {
        if (elect_one()) {
          fence_async_smem();
          tma_st(&mOut, ct * 128, rt * 128 + w * 64, sb + SM_OUT + w * 16384);
          tma_st(&mOut, ct * 128 + 64, rt * 128 + w * 64, sb + SM_OUT + w * 16384 + 8192);
          bulk_commit();
          bulk_wait_read();
        }
        __syncwarp();
      } else {
        uint4* dst = reinterpret_cast<uint4*>(p.out + (size_t)(rt * 128 + w * 64 + (lane >> 4)) * 1024 + ct * 128) + (lane & 15);
#pragma unroll 2
        for (int r = lane >> 4; r < 64; r += 2) {
          const uint4 v = lds128(sb + SM_OUT + w * 16384 + ((lane >> 3) & 1) * 8192 + r * 128 + (((lane ^ r) & 7) * 16));
          if (r != skip) *dst = v;
          dst += 256;
        }
      }
      if (!has_cand) nb_sync(NB_WIN + w, 160);
    } else {
      if (slab) {
        mbar_wait_g(sb + BAR_RED, 0);
        float v = 0.f;
#pragma unroll
        for (int w = 0; w < 8; w++) v += lds_f32(sb + SM_RED + w * 128 + lane * 4);
        v += __shfl_xor_sync(0xffffffffu, v, 16);
        v = mod_value(v, b0 >> 6);
        publish_record(&g_rec[tag & 1][0][ridx], pack2(v, __shfl_down_sync(0xffffffffu, v, 1)), 2 * (lane & 1), b0 >> 6, lane < 8);
        if (lane == 0) TS(1);
      }
      mbar_wait_g(sb + BAR_G, 0);
#pragma unroll 1
      for (int i = 1; i < 4; i++) {
        const uint4* mp = &g_rec[tag & 1][(b0 >> 1) & (NREP - 1)][i == 1 ? (8 + (lane >> 2)) * RS + (lane & 3) : 16 * RS - 64 + 32 * i + lane];
        uint4 v0, v1; int it = 0;
        while (true) {
          v0 = ld_pkt16(mp); v1 = ld_pkt16(mp + RV);
          if (v0.x != 0 && v1.x != 0) break;
          spin_guard(it); __nanosleep(PLD);
        }
        put_record(sb, 32 * i + lane, v0);
        put_record(sb, 128 + 32 * i + lane, v1);
        mbar_arrive(sb + BAR_TAB - 8 + 8 * i);
        if (lane == 0) {
          TS(3 + i + (i > 2));
          if (i == 1) l2_prefetch(((b0 & 64) ? p.vc : p.kc) + (size_t)(((b0 >> 4) & 3) * 2048 + 1536) * 128 + (b0 & 15) * 4096, 8192);
        }
        __syncwarp();
      }
      TILE_ROLES();
      if (lane == 0) {
        int it = 0;
        do { __nanosleep(500); spin_guard(it); } while (ld_relaxed(&g_hflag[rt * 32]) != tag * 16u);
        fence_acquire_gpu();
        mbar_arrive(sb + BAR_HF);
        if (b < NFFN) for (int i = 0; i < 8; i++) { __nanosleep(800); l2_prefetch(p.wd + (size_t)(b * 32 + i * 4) * 1024, 8192); }
      }
      __syncwarp();
      {
        uint2 v; int it = 0;
        do { __nanosleep(1000); v = ld_pkt8(&g_vdone[(lane & 3) * 16]); spin_guard(it); }
        while (!(v.y == tag));
        __syncwarp();
        fence_acquire_gpu();
        if (lane == 1 || lane == 2) sts32(sb + SM_SCAL + (2 - lane) * 4, v.x);
      }
#pragma unroll 1
      for (int i = 0; i < 2; i++) {
        const int q = i * 32 + lane, pi = ct * 64 + q;
        const uint32_t vga = g_mod[2 * 512 + pi].x, vsb = g_mod[3 * 512 + pi].x, vcb = g_mod[4 * 512 + pi].x, vgb = g_mod[5 * 512 + pi].x;
        const uint32_t wr = reinterpret_cast<const uint32_t*>(p.w_r)[pi];
        const uint32_t c1 = hadd2(vcb, ONE2);
        const float al = lo2f(c1) * lo2f(wr), ah = hi2f(c1) * hi2f(wr);
        const uint32_t o8 = (q & 3) * 8 + ((q >> 2) & 1) * 4;
        sts32(sb + SM_GA + (q >> 3) * 32 + o8, vga);
        sts128(sb + SM_REC + q * 16, c1, vsb, vgb, 0);
        const uint32_t ahi = pack2(al, ah), alo = pack2(al - lo2f(ahi), ah - hi2f(ahi));
        const uint32_t ba = sb + SM_B1 + (q >> 3) * 128 + o8;
        sts32(ba, ONE2); sts32(ba + 32, ahi); sts32(ba + 64, alo); sts32(ba + 96, 0);
      }
      if (lane == 0) TS(28);
      if (lane == 0) {
        tma_prefetch_desc(&mWo); tma_prefetch_desc(&mO); tma_prefetch_desc(&mOut); tma_prefetch_desc(&mWd); tma_prefetch_desc(&mWg); tma_prefetch_desc(&mWu);
#pragma unroll 1
        for (int r = 0; r < 4; r++) {
          int it = 0;
          do { __nanosleep(200); spin_guard(it); } while (ld_relaxed(&g_oflag[(rt * 4 + r) * 32]) != tag * 16u);
          if (r & 1) { fence_acquire_gpu(); mbar_arrive(sb + BAR_OF + 8 * (r >> 1)); }
          if (r == 1 && b < NFFN) {
            const uint64_t pef = policy_evict_first();
            mbar_wait_g(sb + BAR_T1, 0);
#pragma unroll 1
            for (int i = 0; i < 4; i++) {
              mbar_expect_tx(sb + BAR_FFN, 16384);
              tma_ld_hint(sb + SM_RING + i * ST1 + 32768, &mWg, b * 32, i * 256, sb + BAR_FFN, pef);
              __nanosleep(GATED);
            }
          }
        }
      }
      __syncwarp();
      if (b < NFFN) {
        mbar_wait_g(sb + BAR_TFREE, 0);
        const uint64_t pef = policy_evict_first();
#pragma unroll 1
        for (int i = 0; i < 5; i++) {
          if (i > 0 && lane == 0) {
            mbar_expect_tx(sb + BAR_FFN, 16384);
            tma_ld_hint(sb + SM_RING + (i - 1) * ST1 + 32768, &mWu, b * 32, (i - 1) * 256, sb + BAR_FFN, pef);
          }
          if (i < 4) {
#pragma unroll 1
            for (int j = 0; j < 8; j++) {
              asm volatile("prefetch.global.L2 [%0];" :: "l"(p.wu + (size_t)(i * 256 + j * 32 + lane) * 3584 + b * 32) : "memory");
              __nanosleep(UPD);
            }
            __nanosleep(500);
          }
        }
      }
      if (lane == 0) TS(29);
#pragma unroll 1
      for (int i = lane; i < 128; i += 32) st_pkt16(&g_stats[b * 128 + i], 0, 0, 0, 0);
      st_pkt16(&g_cand[b * 32 + lane], 0, 0, 0, 0);
      if (lane < 8) st_pkt16(&g_entry[(ct * 16 + rt) * 8 + lane], 0, 0, 0, 0);
#pragma unroll 1
      for (int i = lane; i < (b < NFFN ? 512 : 0); i += 32) st_pkt16(&g_ypart[((i >> 2) * NFFN + b) * 4 + (i & 3)], 0, 0, 0, 0);
      mbar_arrive(sb + BAR_VEC);
      uint4* const cp = &g_cand[b * 32 + lane];
      uint4* const ep = &g_entry[(ct * 16 + rt) * 8];
      nb_sync(NB_AMAX, 288);
      TV(0);
      const uint2 e = lds64(sb + SM_AMAX + (lane & 7) * 8);
      const int tmax = __reduce_max_sync(0xffffffffu, (int)e.x);
      const uint32_t row = ~tmax & 127;
      const int wl = row >> 4;
      const uint32_t xa = sb + SM_X2 + (row >> 6) * 16384 + (lane >> 4) * 8192 + (row & 63) * 128 + (lane & 3) * 4
                        + ((((lane >> 1) & 6) ^ (row & 7)) * 16);
      const uint32_t v0 = lds32(xa), v1 = lds32(xa ^ 16);
      if (lane == wl) st_pkt16(ep, (tmax | 127) - rt, rt * 128 + row, e.y, tag);
      st_pkt16(cp, v0, v1, tag, 0);
      if (lane == 0) { sts32(sb + SM_CAND, row); mbar_arrive(sb + BAR_CAND); }
      TV(1);
      if (lane == 0) TS(15);
    }
  } else {
    const int warp = tid >> 5;
    const int wg = warp >> 2, wq = warp & 3;
    const int g = lane >> 2, t = lane & 3;
    uint32_t tag;
    uint32_t ln[4];
    float acc[128];
    uint32_t bf[16];
    auto gemv = [&]() {
          if (late) mbar_wait(sb + BAR_WH, 0); else
          asm volatile("cp.async.wait_all;" ::: "memory");
          float d0[4] = {0.f, 0.f, 0.f, 0.f}, d1[4] = {0.f, 0.f, 0.f, 0.f};
#pragma unroll
          for (int i = 0; i < 8; i++) {
            const uint4 wv = lds128(slab_addr + i * 512);
            const uint32_t a[4] = {wv.x, wv.y, wv.z, wv.w};
            mma16816((i & 1) ? d1 : d0, a, bf[2 * i], bf[2 * i + 1]);
          }
#pragma unroll
          for (int i = 0; i < 4; i++) { d0[i] += d1[i]; d0[i] += __shfl_xor_sync(0xffffffffu, d0[i], 6); }
          const uint32_t dst = mapa(sb + SM_MISC, t & 1) - SM_MISC;
          if (!(lane & 6)) st_async_f32x4(dst + SM_RED + warp * 128 + rank * 64 + g * 8, d0, dst + BAR_RED);
          TH(4);
    };
    {
      asm volatile("barrier.cluster.arrive.relaxed.aligned;" ::: "memory");
      if (lane == 0) st_pkt16(&g_lnst[8 * b0 + warp], 0, 0, 0, 0);
      TH(1);
      asm volatile("setmaxnreg.inc.sync.aligned.u32 240;");
      TH(2);
#pragma unroll
      for (int i = 0; i < 8; i++) {
        const float sv = silu_f((g & 4) ? hi2f(cw[i]) : lo2f(cw[i]));
        const uint32_t sp = (g & 1) ? pack2(0.f, sv) : pack2(sv, 0.f);
        bf[2 * i] = (g & 2) ? 0 : sp; bf[2 * i + 1] = (g & 2) ? sp : 0;
      }
      asm volatile("barrier.cluster.wait.aligned;" ::: "memory");
#pragma unroll
      for (int i = 0; i < 128; i++) acc[i] = 0.f;
      reg_fence<128>(acc);
      tag = __shfl_sync(0xffffffffu, epoch, 0) + 1;
      TH(3);
      if (slab && !late) gemv();
      {
        {
          mbar_wait(sb + BAR_XH, 0);
          TH(5);
          float ds[4] = {0.f, 0.f, 0.f, 0.f}, dq[4][4];
#pragma unroll
          for (int i = 0; i < 4; i++) { dq[i][0] = dq[i][1] = dq[i][2] = dq[i][3] = 0.f; }
#pragma unroll
          for (int i = 0; i < 8; i++) {
            uint32_t a[4];
            ldsm4(sb + SM_XROW + wg * ST1 + wq * 4096 + ((lane >> 3) & 1) * 2048 + i * 256 + (lane >> 4) * 128 + (lane & 7) * 16, a);
            mma16816(ds, a, ONE2, ONE2);
            mma1688(dq[0], a[0], a[1], a[0]); mma1688(dq[1], a[0], a[1], a[1]);
            mma1688(dq[2], a[2], a[3], a[2]); mma1688(dq[3], a[2], a[3], a[3]);
          }
          const bool dg = t == (g >> 1);
          const float q0 = dg ? ((g & 1) ? dq[0][1] + dq[2][1] : dq[0][0] + dq[2][0]) : 0.f;
          const float q1 = dg ? ((g & 1) ? dq[1][3] + dq[3][3] : dq[1][2] + dq[3][2]) : 0.f;
          float q = ((lane & 1) ? q1 : q0) + __shfl_xor_sync(0xffffffffu, (lane & 1) ? q0 : q1, 1);
          float sm = (lane & 1) ? ds[2] : ds[0];
          q += __shfl_xor_sync(0xffffffffu, q, 2);
#pragma unroll
          for (int o = 4; o <= 16; o <<= 1) { q += __shfl_xor_sync(0xffffffffu, q, o); sm += __shfl_xor_sync(0xffffffffu, sm, o); }
          const float mean = sm * (1.f / 1024.f);
          const float rd = rcp_f(rbf(sqrt_f(rbf(rbf(fmaxf(fmaf(-mean, mean, q * (1.f / 1024.f)), 0.f)) + 1e-5f))));
          const float mean1 = __shfl_sync(0xffffffffu, mean, 1), rd1 = __shfl_sync(0xffffffffu, rd, 1);
          const uint32_t rh = pack2(rd, rd1);
          if (lane == 0) st_pkt16(&g_lnst[8 * b0 + warp], pack2(-rbf(mean) * lo2f(rh), -rbf(mean1) * hi2f(rh)), rh, 0, tag);
          TH(6);
          if (tid == 0) TS(2);
        }
      }
    }
    if (slab && late) gemv();
    TILE_ROLES();
    const uint32_t xa0 = sb + SM_RING + (warp * 16 + (lane & 15)) * 128 + (((lane >> 4) ^ (lane & 7)) * 16);
    uint32_t V[16];
    {
      const uint4* mp = &g_rec[tag & 1][(b0 >> 1) & (NREP - 1)][RV * wg + (lane >> 2) * RS + (lane & 3)];
      const uint4* lp = &g_lnst[(8 * rt + warp) * 8 + (g >> 1)];
      mbar_wait(sb + BAR_FULL1, 0);
#pragma unroll
      for (int kk = 0; kk < 4; kk++) ldsm4(xa0 ^ (kk * 32), V + 4 * kk);
      uint4 v0 = make_uint4(1, 0, 0, 0), l0, l1;
      int it = 0;
      while ((uint32_t)clock() - c0 < HD) {}
      do { if (wq == 0) v0 = ld_pkt16(mp);
           l0 = ld_pkt16(lp); l1 = ld_pkt16(lp + 4); spin_guard(it); }
        while (!(__all_sync(0xffffffffu, v0.x != 0 && l0.w == tag && l1.w == tag)));
      TH(7);
      if (wq == 0) put_record(sb, 128 * wg + lane, v0);
      const uint32_t sel = (g & 1) ? 0x3232 : 0x1010;
      ln[0] = __byte_perm(l0.x, 0, sel); ln[1] = __byte_perm(l0.y, 0, sel);
      ln[2] = __byte_perm(l1.x, 0, sel); ln[3] = __byte_perm(l1.y, 0, sel);
      __syncwarp();
      if (lane < 2) mbar_arrive_cl(mapa(sb + BAR_G, lane));
      nb_sync(NB_CONS, 256);
      if (tid == 0) TS(3);
      TH(13);
    }

    const uint32_t rel = mapa(sb + SM_MISC, lane & 1) - SM_MISC;
    const uint32_t stsm_addr = sb + SM_STASH + wg * 16384 + (wq * 16 + (lane & 15)) * 128 + (((lane >> 4) ^ (lane & 7)) * 16);

    uint32_t ph = 0;
    uint32_t X[32];
    {
      const uint32_t tab0 = sb + SM_STASH + wg * 16384 + t * 16;
      const uint64_t db0 = mk_desc(sb + SM_RING + 16384, 8192);
      uint32_t A[2][16];
      uint32_t xa[4];
#pragma unroll
      for (int kk = 0; kk < 4; kk++) xa[kk] = xa0 ^ (kk * 32);
      uint32_t tab = tab0;
      reg_fence<4>(xa);
      asm volatile("{\n.reg .pred p;\nsetp.eq.u32 p, %4, 0;\n@p ld.shared.v4.u32 {%0,%1,%2,%3}, [%5];\n}"
        : "+r"(ln[2]), "+r"(ln[0]), "+r"(ln[3]), "+r"(ln[1]) : "r"(tag), "r"(sb));
      int hs = 2 * ct;
      uint4 R[4];
#pragma unroll
      for (int kk = 0; kk < 4; kk++) R[kk] = lds128(tab + (kk >> 1) * 2048 + (kk & 1) * 64);
#pragma unroll 1
      for (int k4 = 0; k4 < 4; k4++) {
#pragma unroll
        for (int s = 0; s < 4; s++) {
          uint32_t* a = A[s & 1];
          const int sn = (s + 1) & 3;
          const uint32_t pn = (k4 + (s == 3)) & 1;
          modulate_frags(a, V, R, ln);
          if (hs == (s & 2)) {
            if (s & 1) mbar_wait(sb + BAR_HS + 16 * wg, 0);
#pragma unroll
            for (int kk = 0; kk < 4; kk++) stsm4((stsm_addr + 4096) ^ (kk * 32), a[4 * kk], a[4 * kk + 1], a[4 * kk + 2], a[4 * kk + 3]);
            nb_arrive(NB_OST + wg, 160);
          }
          if (s == 0 && k4 == 0) TH(8);
          TQ(3 * s);
          if (s == 0 && k4 == 0 && tid == 0) { TS(6); TSC(61); }
          wg_fence();
#pragma unroll
          for (int kk = 0; kk < 4; kk++) wgmma_rs256<1>(acc, a + 4 * kk, db0 + s * (ST1 >> 4) + kk * 128);
          wg_commit();
          if (s == 3) TQ(12);
          if (s == 3 && k4 < 3) mbar_wait(sb + BAR_TAB + 8 * k4, 0);
          if (s == 3) TQ(13);
#pragma unroll
          for (int kk = 0; kk < 4; kk++) R[kk] = lds128(tab + (s + 1) * 128 + (kk >> 1) * 2048 + (kk & 1) * 64);
          wg_wait<1>();
          if (k4 == 0) TH(9 + s);
          TQ(3 * s + 1);
          reg_fence<16>(A[(s & 1) ^ 1]);
          if ((tid & 127) < 2 && (s | k4)) mbar_arrive_cl(rel + BAR_EMPTY1 + 8 * ((s + 3) & 3));
          if (s < 3 || k4 < 3) {
            mbar_wait(sb + BAR_FULL1 + 8 * sn, pn);
            TQ(3 * s + 2);
#pragma unroll
            for (int kk = 0; kk < 4; kk++) ldsm4(xa[kk] + sn * ST1, V + 4 * kk);
          }
        }
        tab += 512; hs -= 4;
      }
      mbar_wait(sb + BAR_HS + 16 * wg + 8, 0);
      wg_wait<0>();
      reg_fence<128>(acc);
    }
#pragma unroll 1
    for (int pair = 0; pair < 2; pair++) {
      uint32_t Q[32];
      TR(0);
      {
        if ((tid & 127) < 2) mbar_arrive_cl(rel + BAR_EMPTY1 + 8 * 3);
        if (pair == 1) mbar_wait(sb + BAR_STASH + 8 * wg, 1);
#pragma unroll
        for (int i = 0; i < 32; i++) Q[i] = pack2(acc[2 * i], acc[2 * i + 1]);
        const uint32_t qs = sb + SM_STASH + wg * 16384 + wq * 2048 + lane * 16;
#pragma unroll
        for (int i = 0; i < 8; i++)
          sts128(qs + (i & 3) * 512 + (i >> 2) * 8192, pack2(acc[64 + 8 * i], acc[65 + 8 * i]), pack2(acc[66 + 8 * i], acc[67 + 8 * i]),
                 pack2(acc[68 + 8 * i], acc[69 + 8 * i]), pack2(acc[70 + 8 * i], acc[71 + 8 * i]));
      }
      if (tid == 0) TS(8 + pair * 2);
      TR(1);
      float O[64], SL[32], SH[32];
      uint32_t PL[16], PH[16];
      SoftmaxState z;
      const uint64_t d0 = mk_desc(sb + SM_RING, 8192);
      {
        mbar_wait(sb + BAR_FULL1, ph);
        wg_fence();
        issue_qk(SL, Q, d0);
        wg_commit();
        issue_qk(SH, Q, d0 + 1024);
        wg_commit();
#pragma unroll
        for (int i = 0; i < 64; i++) O[i] = 0.f;
        reg_fence<64>(O);
        wg_wait<1>();
        reg_fence<32>(SL);
        softmax_start(z);
        softmax_half(SL, PL, O, z, true, tag);
        wg_wait<0>();
        reg_fence<32>(SH);
        if ((tid & 127) < 2) mbar_arrive_cl(rel + BAR_EMPTY1);
      }
      float lp0 = 0.f, lp1 = 0.f;
      uint32_t dB = (uint32_t)d0 + 1 * (ST1 >> 4), dA = (uint32_t)d0 + 2 * (ST1 >> 4);
      const uint32_t dBx = dB ^ ((uint32_t)d0 + 3 * (ST1 >> 4)), dAx = dA ^ (uint32_t)d0;
      uint32_t so = 0;
      bool ready = false;
#pragma unroll 1
      for (int i = 0; i < 7; i++) {
        TA(0);
        TR(2 + i);
        if (!ready) mbar_wait(sb + BAR_FULL1 + 8 + so, ph);
        TA(1);
        TA(2);
        wg_fence();
        issue_qk(SL, Q, (d0 & 0xffffffff00000000ull) | dB);
        if (i == 4) {
          __syncwarp();
          stage_o(O, lp0, lp1, stsm_addr);
        }
        wg_fence();
        issue_pv(O, PL, ((d0 & 0xffffffff00000000ull) | dB) + 1024, i != 4);
        wg_commit();
        if (i == 4) {
          nb_arrive(NB_OST + wg, 160);
        }
        TA(3);
        ph ^= i & 1;
        ready = mbar_test(sb + BAR_FULL1 + 16 - so, ph);
        softmax_half(SH, PH, O, z, false, tag);
        TA(4);
        wg_wait<0>();
        TA(5);
        reg_fence<32>(SL); reg_fence<16>(PL);
        if ((tid & 127) < 2) mbar_arrive_cl(rel + BAR_EMPTY1 + 8 + so);
        if (!ready) mbar_wait(sb + BAR_FULL1 + 16 - so, ph);
        TA(6);
        wg_fence();
        issue_qk(SH, Q, (d0 & 0xffffffff00000000ull) | dA);
        wg_commit();
        issue_pv(O, PH, ((d0 & 0xffffffff00000000ull) | dA) + 1024, 1);
        wg_commit();
        if (i == 2) {
          wg_wait<1>();
          reg_fence<32>(Q);
          const uint32_t qs = sb + SM_STASH + wg * 16384 + wq * 2048 + lane * 16;
#pragma unroll
          for (int j = 0; j < 8; j++) { const uint4 v = lds128(qs + (j & 3) * 512 + (j >> 2) * 8192); Q[4 * j] = v.x; Q[4 * j + 1] = v.y; Q[4 * j + 2] = v.z; Q[4 * j + 3] = v.w; }
        }
        TA(10);
        if (i == 3) { lp0 = z.l0; lp1 = z.l1; row_rcp(lp0, lp1); softmax_start(z); }
        TA(7);
        so ^= 16; dB ^= dBx; dA ^= dAx;
        ready = mbar_test(sb + BAR_FULL1 + 8 + so, ph);
        softmax_half(SL, PL, O, z, i == 3, tag);
        TA(8);
        wg_wait<0>();
        TA(9);
        reg_fence<32>(SH); reg_fence<16>(PH); reg_fence<64>(O); reg_fence<32>(Q);
        if ((tid & 127) < 2) mbar_arrive_cl(rel + BAR_EMPTY1 + so);
      }
      TAFLUSH();
      TR(9);
      {
        if (!ready) mbar_wait(sb + BAR_FULL1 + 8 * 3, ph);
        ph ^= 1;
        const uint64_t dv = d0 + 3 * (ST1 >> 4);
        wg_fence();
        issue_pv(O, PL, dv, 1);
        wg_commit();
        bb_fence(tag);
        softmax_half(SH, PH, O, z, false, tag);
        wg_fence();
        issue_pv(O, PH, dv + 1024, 1);
        wg_commit();
        TR(10);
        row_rcp(z.l0, z.l1);
        mbar_wait(sb + (pair ? BAR_X : BAR_STASH) + 8 * wg, 0);
#pragma unroll
        for (int kk = 0; kk < 8; kk++) ldsm4((stsm_addr + (kk >> 2) * 8192) ^ ((kk & 3) * 32), X + 4 * kk);
        reg_fence<32>(X);
        __syncwarp();
        wg_wait<0>();
        reg_fence<64>(O);
        TR(11);
        if ((tid & 127) < 2) mbar_arrive_cl(rel + BAR_EMPTY1 + 8 * 3);
        stage_o(O, z.l0, z.l1, stsm_addr);
        nb_arrive(NB_OST + wg, 160);
      }
      TR(12);
      if (tid == 0) { TS(9 + pair * 2); TSC(62); }
      if (pair == 1) break;
      {
        mbar_wait(sb + BAR_FULL1, ph);
        const uint64_t da = mk_desc(sb + SM_RING + wg * 8192, 16), db = mk_desc(sb + SM_RING + 16384, 8192);
        wg_fence();
        wgmma_ss256_z<1>(acc, da, db);
#pragma unroll
        for (int kk = 1; kk < 4; kk++) wgmma_ss256<1>(acc, da + kk * 2, db + kk * 128, 1);
        wg_commit();
      }
#pragma unroll 1
      for (int kt = 1; kt < 16; kt++) {
        const uint32_t s = kt & 3;
        if (s == 0) ph ^= 1;
        mbar_wait(sb + BAR_FULL1 + 8 * s, ph);
        const uint32_t st = sb + SM_RING + s * ST1;
        const uint64_t da = mk_desc(st + wg * 8192, 16), db = mk_desc(st + 16384, 8192);
        wg_fence();
#pragma unroll
        for (int kk = 0; kk < 4; kk++) wgmma_ss256<1>(acc, da + kk * 2, db + kk * 128, 1);
        wg_commit();
        wg_wait<1>();
        if ((tid & 127) < 2) mbar_arrive_cl(rel + BAR_EMPTY1 + 8 * ((s + 3) & 3));
      }
      ph ^= 1;
      wg_wait<0>();
      reg_fence<128>(acc);
      TR(13);
    }

    uint4 WG[16], WU[16];
    const int fp = 64 * warp + 8 * g + t;
    uint32_t fsb0, fsb1, fcb0, fcb1, fgb0, fgb1;
    const uint32_t gu_base = sb + SM_RING + (warp >> 1) * ST1 + 32768 + (warp & 1) * 8192;
    const uint32_t gu_addr = gu_base + t * 128 + (g & 1) * 64 + ((g >> 1) ^ t) * 16;
    {
      const uint64_t da0 = mk_desc(sb + SM_RING + __shfl_sync(0xffffffffu, wg, 0) * 8192, 16), db0 = mk_desc(sb + SM_RING + 16384, 8192);
#pragma unroll
      for (int n = 0; n < 4 + 5 * PEEL; n++) {
        const int s = n < 4 ? n : (n - 4) % 5;
        mbar_wait(sb + BAR_FULL1 + 8 * s, n < 4 ? 0 : ((n - 4) / 5 + (s < 4)) & 1);
        if (n < 4) TSX(40 + wg * 6 + n);
        const uint64_t da = da0 + s * (ST1 >> 4), db = db0 + s * (ST1 >> 4);
        wg_fence();
        if (n == 0) wgmma_ss128_z<1>(acc, da, db); else wgmma_ss128<1>(acc, da, db, 1);
#pragma unroll
        for (int kk = 1; kk < 4; kk++) wgmma_ss128<1>(acc, da + kk * 2, db + kk * 128, 1);
        wg_commit();
        if (n == 0 && b < NFFN) mbar_wait(sb + BAR_FFN, 0);
        {
          constexpr int NT = 4 + 5 * PEEL, F0 = NT > 16 ? NT - 16 : 0;
#pragma unroll
          for (int i = 0; i < 16; i++) if (F0 + i * (NT - F0) / 16 == n) WG[i] = lds128(gu_addr + i * 512);
        }
        if (n > 0) {
          wg_wait<1>();
          if ((tid & 127) < 2) mbar_arrive_cl(rel + BAR_EMPTY1 + 8 * (n == 4 ? 3 : s ? s - 1 : 4));
        }
      }
      TSX(44 + wg * 6);
      {
        uint32_t dep = 0;
#pragma unroll
        for (int i = 0; i < 16; i++) dep ^= WG[i].x;
        if (__shfl_sync(0xffffffffu, tag, dep & 31) == tag && lane == 2) mbar_arrive(sb + BAR_TFREE);
      }
      {
        uint32_t so = 0, sp = 4 * 8, par = PEEL + 1;
#pragma unroll 1
        for (int n = 4 + 5 * PEEL; n < 64; n++) {
          mbar_wait(sb + BAR_FULL1 + so, (par + (so >> 5)) & 1);
          const uint64_t da = da0 + so * (ST1 >> 7), db = db0 + so * (ST1 >> 7);
          wg_fence();
#pragma unroll
          for (int kk = 0; kk < 4; kk++) wgmma_ss128<1>(acc, da + kk * 2, db + kk * 128, 1);
          wg_commit();
          wg_wait<1>();
          if ((tid & 127) < 2) mbar_arrive_cl(rel + BAR_EMPTY1 + sp);
          sp = so; so += 8;
          if (so == 40) { so = 0; par++; }
        }
      }
    }
    mbar_wait(sb + BAR_VEC, 0);
    const int lrow = warp * 16 + g;
    uint2 ga[8], b1[8];
#pragma unroll
    for (int kk = 0; kk < 8; kk++) { ga[kk] = lds64(sb + SM_GA + kk * 32 + t * 8); b1[kk] = lds64(sb + SM_B1 + min(g, 3) * 32 + t * 8 + kk * 128); }
    uint4* const stp = &g_stats[b * 128 + lrow + 8 * t];
    bb_fence(tag);
    wg_wait<0>();
    reg_fence<64>(acc);
    if (tid == 0) { TS(12); TSC(63); }

    TT(0);
    {
      float d1[4] = {0.f, 0.f, 0.f, 0.f}, d2[4] = {0.f, 0.f, 0.f, 0.f}, d3[4] = {0.f, 0.f, 0.f, 0.f};
      float d4[4] = {0.f, 0.f, 0.f, 0.f}, d5[4] = {0.f, 0.f, 0.f, 0.f};
#pragma unroll
      for (int kk = 0; kk < 8; kk++) {
        uint32_t* x = X + 4 * kk;
        x[0] = hfma2(ga[kk].x, pack2(acc[8 * kk + 0], acc[8 * kk + 1]), x[0]);
        x[1] = hfma2(ga[kk].x, pack2(acc[8 * kk + 2], acc[8 * kk + 3]), x[1]);
        x[2] = hfma2(ga[kk].y, pack2(acc[8 * kk + 4], acc[8 * kk + 5]), x[2]);
        x[3] = hfma2(ga[kk].y, pack2(acc[8 * kk + 6], acc[8 * kk + 7]), x[3]);
        mma16816(d1, x, b1[kk].x, b1[kk].y);
        mma1688(d2, x[0], x[1], x[0]); mma1688(d3, x[0], x[1], x[1]);
        mma1688(d4, x[2], x[3], x[2]); mma1688(d5, x[2], x[3], x[3]);
      }
      const int qb = lane & 28;
      const float q0 = __shfl_sync(0xffffffffu, (g & 1) ? d2[1] + d4[1] : d2[0] + d4[0], qb | (g >> 1));
      const float q1 = __shfl_sync(0xffffffffu, (g & 1) ? d3[3] + d5[3] : d3[2] + d5[2], qb | (g >> 1));
      const float e0 = __shfl_xor_sync(0xffffffffu, t ? d1[0] : d1[3], 1);
      const float e1 = __shfl_sync(0xffffffffu, d1[2], qb);
      if (t < 2) st_pkt16(stp, __float_as_uint(t ? e1 : d1[0]), __float_as_uint(t ? q1 : q0),
                          __float_as_uint((t ? d1[2] : d1[1]) + e0), tag);
    }
    {
      const uint2* mp = &g_mod[3 * 512 + fp];
      fsb0 = ld_pkt8(mp).x; fsb1 = ld_pkt8(mp + 4).x; fcb0 = ld_pkt8(mp + 512).x; fcb1 = ld_pkt8(mp + 516).x;
      fgb0 = ld_pkt8(mp + 1024).x; fgb1 = ld_pkt8(mp + 1028).x;
    }
    TSY(13);
    TT(1);
    float mb, rd, den, br;
    {
      const uint4* sp = &g_stats[(rt * 8 + 4 * (t & 1)) * 128 + lrow + 4 * (t & 2)];
      mbar_wait(sb + BAR_EMPTY1 + 8 * 3, 0);
#pragma unroll
      for (int kk = 0; kk < 8; kk++) stsm4((stsm_addr - SM_STASH + SM_X2 + (kk >> 2) * 8192) ^ ((kk & 3) * 32), X[4 * kk], X[4 * kk + 1], X[4 * kk + 2], X[4 * kk + 3]);
      if (b < NFFN) mbar_wait(sb + BAR_FFN, 1);
#pragma unroll
      for (int i = 0; i < WU1; i++) WU[i] = lds128(gu_addr + i * 512);
      bb_fence(tag);
      TT(2);
      uint4 v0, v1, v2, v3;
      int it = 0;
      do { v0 = ld_pkt16(sp); v1 = ld_pkt16(sp + 128); v2 = ld_pkt16(sp + 256); v3 = ld_pkt16(sp + 384); spin_guard(it); }
        while (!(__all_sync(0xffffffffu, v0.w == tag && v1.w == tag && v2.w == tag && v3.w == tag)));
      TT(3);
      float sm = (__uint_as_float(v0.x) + __uint_as_float(v1.x)) + (__uint_as_float(v2.x) + __uint_as_float(v3.x));
      float sq = (__uint_as_float(v0.y) + __uint_as_float(v1.y)) + (__uint_as_float(v2.y) + __uint_as_float(v3.y));
      float dt = (__uint_as_float(v0.z) + __uint_as_float(v1.z)) + (__uint_as_float(v2.z) + __uint_as_float(v3.z));
      sm += __shfl_xor_sync(0xffffffffu, sm, 1); sq += __shfl_xor_sync(0xffffffffu, sq, 1); dt += __shfl_xor_sync(0xffffffffu, dt, 1);
      const uint2 scal = lds64(sb + SM_SCAL);
      const float mu = sm * (1.f / 1024.f);
      mb = rbf(mu);
      den = rbf(sqrt_f(rbf(rbf(fmaxf(fmaf(-mu, mu, sq * (1.f / 1024.f)), 0.f)) + 1e-5f)));
      rd = rcp_f(den);
      br = fmaf(fmaf(-mb, __uint_as_float(scal.x), dt), rd, __uint_as_float(scal.y));
    }
    TSY(14);
    TT(4);
    {
      const int rb = __float_as_int(br);
      const int key = ((rb ^ ((rb >> 31) & 0x7fffffff)) | 127) - (lrow + 4 * (t & 2));
      if (key == __reduce_max_sync(0xffffffffu, key)) sts64(sb + SM_AMAX + warp * 8, (uint32_t)key, pack2(mb, den));
      __syncwarp();
      nb_arrive(NB_AMAX, 288);
    }
    TT(5);
    const uint4* ep = &g_entry[(warp * 16 + (lane & 15)) * 8];
    const uint32_t slot = sb + SM_STASH + wg * 8192 + (tid & 127) * 16;
    cp_async16(slot, ep);
    {
      const float rh = rbf(rd);
      const uint32_t u = pack2(-mb * rh, rh);
      const int qb = lane & 28;
      const uint32_t u0 = __shfl_sync(0xffffffffu, u, qb), u1 = __shfl_sync(0xffffffffu, u, qb | 2);
      const uint32_t m0 = __byte_perm(u0, 0, 0x1010), h0 = __byte_perm(u0, 0, 0x3232);
      const uint32_t m1 = __byte_perm(u1, 0, 0x1010), h1 = __byte_perm(u1, 0, 0x3232);
#pragma unroll
      for (int j = 0; j < 16; j++) {
        const uint4 rec = lds128(sb + SM_REC + (4 * j + t) * 16);
        X[2 * j] = hfma2(rec.z, hfma2(hfma2(X[2 * j], h0, m0), rec.x, rec.y), X[2 * j]);
        X[2 * j + 1] = hfma2(rec.z, hfma2(hfma2(X[2 * j + 1], h1, m1), rec.x, rec.y), X[2 * j + 1]);
      }
#pragma unroll
      for (int kk = 0; kk < 8; kk++) stsm4((stsm_addr - SM_STASH + SM_OUT + (kk >> 2) * 8192) ^ ((kk & 3) * 32), X[4 * kk], X[4 * kk + 1], X[4 * kk + 2], X[4 * kk + 3]);
    }
    cp_async_wait();
    uint4 ent = lds128(slot);
    TSY(16);
    TT(6);
    int wrow;
    uint32_t xs0, xs1, hs0, hs1;
    uint32_t WD[64];
    const uint32_t wd_addr = sb + SM_RING + wg * ST1 + wq * 8192 + ((lane & 7) + ((lane >> 4) << 3)) * 128 + ((((lane >> 3) & 1) ^ (lane & 7)) * 16);
    {
      int gmax;
      auto leader = [&]() {
        gmax = __reduce_max_sync(0xffffffffu, ent.w == tag ? (int)ent.x : (int)0x8000000f);
        return ~gmax & 15;
      };
      int wt = leader(), it = 0;
      TT(7);
      nb_arrive(NB_OST + wg, 160);
      TT(8);
      cp_async16(slot + 2048, &g_cand[(wt * 8 + warp) * 32 + lane]);
      if (ent.w != tag) cp_async16(slot, ep);
#pragma unroll
      for (int i = WU1; i < 16; i++) WU[i] = lds128(gu_addr + i * 512);
      if (b < NFFN) mbar_wait(sb + BAR_FFN + 8, 0);
#pragma unroll
      for (int mt = 0; mt < 8; mt++)
#pragma unroll
        for (int s = 0; s < 2; s++) ldsm4t((wd_addr + (mt >> 2) * 4096 + s * 2048) ^ ((mt & 3) * 32), WD + (mt * 2 + s) * 4);
      cp_async_wait();
      uint4 v = lds128(slot + 2048);
      ent = lds128(slot);
      TT(9);
      while (true) {
        const int have = wt;
        wt = leader();
        if (__all_sync(0xffffffffu, ent.w == tag && have == wt && v.z == tag)) break;
        v = ld_pkt16(&g_cand[(wt * 8 + warp) * 32 + lane]);
        if (ent.w != tag) ent = ld_pkt16(ep);
        spin_guard(it);
      }
      TT(10);
      ent.x = gmax ^ ((gmax >> 31) & 0x7fffffff);
      wrow = __shfl_sync(0xffffffffu, ent.y, wt); ent.z = __shfl_sync(0xffffffffu, ent.z, wt);
      xs0 = v.x; xs1 = v.y;
      const uint32_t mm = __byte_perm(ent.z, 0, 0x1010);
      const float rs = rcp_f(hi2f(ent.z));
      const uint32_t e0 = hsub2(xs0, mm), e1 = hsub2(xs1, mm);
      hs0 = hfma2(pack2(lo2f(e0) * rs, hi2f(e0) * rs), hadd2(fcb0, ONE2), fsb0);
      hs1 = hfma2(pack2(lo2f(e1) * rs, hi2f(e1) * rs), hadd2(fcb1, ONE2), fsb1);
    }
    if ((tid & 127) == 0) sts32(sb + SM_WROW + 4 * wg, wrow);
    nb_arrive(NB_WIN + wg, 160);
    TSY(17);
    TT(11);
    if (b < NFFN) {
      float da[4][4];
#pragma unroll
      for (int i = 0; i < 4; i++) { da[i][0] = da[i][1] = da[i][2] = da[i][3] = 0.f; }
      const uint32_t selv = ((g & 1) ? 0x1044 : 0x4410) + ((g & 4) ? ((g & 1) ? 0x2200 : 0x0022) : 0);
      const uint32_t sel0 = (g & 2) ? 0x4444 : selv, sel1 = (g & 2) ? selv : 0x4444;
#pragma unroll
      for (int s = 0; s < 16; s++) {
        const uint32_t v = __shfl_sync(0xffffffffu, (s & 1) ? hs1 : hs0, 4 * (s >> 1) + t);
        const uint32_t b0 = __byte_perm(v, 0, sel0), b1 = __byte_perm(v, 0, sel1);
        const uint32_t a0[4] = {WG[s].x, WG[s].y, WG[s].z, WG[s].w};
        const uint32_t a1[4] = {WU[s].x, WU[s].y, WU[s].z, WU[s].w};
        mma16816(da[(s & 1) * 2], a0, b0, b1);
        mma16816(da[(s & 1) * 2 + 1], a1, b0, b1);
      }
      {
        float v[4];
#pragma unroll
        for (int i = 0; i < 4; i++) {
          const float vg = da[0][i] + da[2][i], vu = da[1][i] + da[3][i];
          v[i] = ((g & 1) ? vu : vg) + __shfl_xor_sync(0xffffffffu, (g & 1) ? vg : vu, 6);
        }
        if ((t >> 1) == (g & 1))
          sts128(gu_base + (g & 1) * 128 + (g >> 1) * 32 + (t & 1) * 16, __float_as_uint(v[0]), __float_as_uint(v[1]), __float_as_uint(v[2]), __float_as_uint(v[3]));
      }
      TT(12);
      nb_sync(NB_CONS, 256);
      float gp[8], up[8];
#pragma unroll
      for (int w = 0; w < 8; w++) {
        const uint32_t a = sb + SM_RING + (w >> 1) * ST1 + 32768 + (w & 1) * 8192 + lane * 4;
        gp[w] = lds_f32(a); up[w] = lds_f32(a + 128);
      }
      const float gsum = ((gp[0] + gp[1]) + (gp[2] + gp[3])) + ((gp[4] + gp[5]) + (gp[6] + gp[7]));
      const float usum = ((up[0] + up[1]) + (up[2] + up[3])) + ((up[4] + up[5]) + (up[6] + up[7]));
      const float act = rbf(silu_f(rbf(gsum))) * rbf(usum);
      TT(13);
      const uint32_t ap = pack2(act, __shfl_down_sync(0xffffffffu, act, 1));
      const uint32_t b00 = __shfl_sync(0xffffffffu, ap, 2 * t), b01 = __shfl_sync(0xffffffffu, ap, 2 * t + 8);
      const uint32_t b10 = __shfl_sync(0xffffffffu, ap, 2 * t + 16), b11 = __shfl_sync(0xffffffffu, ap, 2 * t + 24);
      float y[8][4];
#pragma unroll
      for (int mt = 0; mt < 8; mt++) {
        y[mt][0] = y[mt][1] = y[mt][2] = y[mt][3] = 0.f;
        mma16816(y[mt], WD + (mt * 2) * 4, b00, b01);
        mma16816(y[mt], WD + (mt * 2 + 1) * 4, b10, b11);
      }
#pragma unroll
      for (int e = 0; e < 2; e++) {
        const float v0 = t == 0 ? y[e][0] : t == 1 ? y[2 + e][0] : t == 2 ? y[4 + e][0] : y[6 + e][0];
        const float v1 = t == 0 ? y[e][2] : t == 1 ? y[2 + e][2] : t == 2 ? y[4 + e][2] : y[6 + e][2];
        st_pkt8(reinterpret_cast<uint2*>(g_ypart) + (((tag & 1) * 64 + 8 * warp + 2 * t + e) * NFFN + b) * 8 + g, ~__float_as_uint(v0), __float_as_uint(v1));
      }
    }
    TSY(18);
    TT(14);
    if (b & 1) return;
    {
      const int pw = warp - (warp > (b >> 4));
      if (warp != (b >> 4)) {
        const uint4* yp = &g_ypart[((tag & 1) * 64 + (b >> 1)) * NFFN * 4 + pw * 64 + lane];
        uint4 v0, v1;
        int it = 0;
        { const uint32_t c1 = clock(); while ((uint32_t)clock() - c1 < (b < NFFN ? YD : YD + 1500)) {} }
        do { v0 = ld_pkt8x2(yp); v1 = ld_pkt8x2(yp + 32); spin_guard(it); }
        while (!(__all_sync(0xffffffffu, v0.x != 0 && v0.z != 0 && v1.x != 0 && v1.z != 0)));
        float y[4] = {__uint_as_float(~v0.x) + __uint_as_float(~v1.x), __uint_as_float(~v0.z) + __uint_as_float(~v1.z),
                      __uint_as_float(v0.y) + __uint_as_float(v1.y), __uint_as_float(v0.w) + __uint_as_float(v1.w)};
#pragma unroll
        for (int o = 4; o <= 16; o <<= 1)
#pragma unroll
          for (int i = 0; i < 4; i++) y[i] += __shfl_xor_sync(0xffffffffu, y[i], o);
        if (lane < 4) sts128(sb + SM_B1 + pw * 64 + lane * 16, __float_as_uint(y[0]), __float_as_uint(y[1]), __float_as_uint(y[2]), __float_as_uint(y[3]));
      }
    }
    TT(15);
    if (warp != (b >> 4)) {
      nb_arrive(NB_CONS, 256);
    } else {
      nb_sync(NB_CONS, 256);
      float y[4] = {0.f, 0.f, 0.f, 0.f};
      if (lane < 28) { const uint4 e = lds128(sb + SM_B1 + lane * 16); y[0] = __uint_as_float(e.x); y[1] = __uint_as_float(e.y); y[2] = __uint_as_float(e.z); y[3] = __uint_as_float(e.w); }
#pragma unroll
      for (int o = 4; o <= 16; o <<= 1)
#pragma unroll
        for (int i = 0; i < 4; i++) y[i] += __shfl_xor_sync(0xffffffffu, y[i], o);
      const float ya = y[0], yb = y[1], yc = y[2], yd = y[3];
      if (g == ((b >> 1) & 7)) {
        const float rs = rbf(__uint_as_float(ent.x));
        const float sg = sigmoid_f(rs);
        const uint32_t sg2 = pack2(sg, sg);
        const uint32_t o0 = hadd2(xs0, hmul2(fgb0, hadd2(hs0, hmul2(pack2(ya, yb), sg2))));
        const uint32_t o1 = hadd2(xs1, hmul2(fgb1, hadd2(hs1, hmul2(pack2(yc, yd), sg2))));
        uint32_t* op = reinterpret_cast<uint32_t*>(p.out + (size_t)wrow * 1024) + fp;
        op[0] = o0; op[4] = o1;
      }
      if (b == 0) {
        if (lane < 8) st_relaxed(&p.sc->ticket[lane * 32], 0);
        st_relaxed(&p.sc->epoch[lane], tag);
      }
      if (lane == 0) TS(19);
    }
  }
}

typedef CUresult (*EncodeFn)(CUtensorMap*, CUtensorMapDataType, cuuint32_t, void*, const cuuint64_t*, const cuuint64_t*,
                             const cuuint32_t*, const cuuint32_t*, CUtensorMapInterleave, CUtensorMapSwizzle,
                             CUtensorMapL2promotion, CUtensorMapFloatOOBfill);

CUtensorMap make_map(EncodeFn enc, const void* ptr, uint64_t rows, uint64_t cols, uint32_t box_rows, uint32_t box_cols, CUtensorMapSwizzle sw) {
  CUtensorMap m;
  cuuint64_t dims[2] = {cols, rows};
  cuuint64_t strides[1] = {cols * 2};
  cuuint32_t box[2] = {box_cols, box_rows};
  cuuint32_t es[2] = {1, 1};
  enc(&m, CU_TENSOR_MAP_DATA_TYPE_BFLOAT16, 2, const_cast<void*>(ptr), dims, strides, box, es, CU_TENSOR_MAP_INTERLEAVE_NONE, sw,
      CU_TENSOR_MAP_L2_PROMOTION_L2_128B, CU_TENSOR_MAP_FLOAT_OOB_FILL_NONE);
  return m;
}

CUtensorMap make_map3(EncodeFn enc, const void* ptr, uint64_t rows, uint64_t cols, uint32_t box_rows, uint32_t box_blks) {
  CUtensorMap m;
  cuuint64_t dims[3] = {64, rows, cols / 64};
  cuuint64_t strides[2] = {cols * 2, 128};
  cuuint32_t box[3] = {64, box_rows, box_blks};
  cuuint32_t es[3] = {1, 1, 1};
  enc(&m, CU_TENSOR_MAP_DATA_TYPE_BFLOAT16, 3, const_cast<void*>(ptr), dims, strides, box, es, CU_TENSOR_MAP_INTERLEAVE_NONE,
      CU_TENSOR_MAP_SWIZZLE_128B, CU_TENSOR_MAP_L2_PROMOTION_L2_128B, CU_TENSOR_MAP_FLOAT_OOB_FILL_NONE);
  return m;
}

}

extern "C" void kernel_launch(void* const* d_in, const int* in_sizes, int n_in, void* d_out, int out_size) {
  (void)in_sizes; (void)n_in; (void)out_size;
  Params p;
  p.x = (const bf16*)d_in[0]; p.kc = (const bf16*)d_in[1]; p.vc = (const bf16*)d_in[2];
  p.wq = (const bf16*)d_in[3]; p.wo = (const bf16*)d_in[4]; p.w_r = (const bf16*)d_in[6];
  p.wg = (const bf16*)d_in[7]; p.wu = (const bf16*)d_in[8]; p.wd = (const bf16*)d_in[9];
  p.c = (const bf16*)d_in[10]; p.w_mod = (const bf16*)d_in[11]; p.out = (bf16*)d_out;

  void* fn = nullptr;
  cudaDriverEntryPointQueryResult st;
  cudaGetDriverEntryPoint("cuTensorMapEncodeTiled", &fn, cudaEnableDefault, &st);
  EncodeFn enc = (EncodeFn)fn;
  void* scp = nullptr;
  cudaGetSymbolAddress(&scp, g_scratch);
  p.sc = (Scratch*)scp;
  void *hp = p.sc->h, *op = p.sc->o;
  const CUtensorMapSwizzle S128 = CU_TENSOR_MAP_SWIZZLE_128B;
  CUtensorMap mH = make_map(enc, hp, 2048, 1024, 64, 64, S128);
  CUtensorMap mWq = make_map3(enc, p.wq, 1024, 4096, 64, 4);
  CUtensorMap mK = make_map(enc, p.kc, 8192, 128, 64, 64, S128);
  CUtensorMap mV = make_map(enc, p.vc, 8192, 128, 64, 64, S128);
  CUtensorMap mO = make_map(enc, op, 2048, 4096, 64, 64, S128);
  CUtensorMap mOs = make_map(enc, op, 2048, 4096, 16, 64, S128);
  CUtensorMap mWo = make_map3(enc, p.wo, 4096, 1024, 64, 2);
  CUtensorMap mX = make_map(enc, p.x, 2048, 1024, 64, 64, S128);
  CUtensorMap mOut = make_map(enc, p.out, 2048, 1024, 64, 64, S128);
  CUtensorMap mWg = make_map(enc, p.wg, 1024, 3584, 256, 32, CU_TENSOR_MAP_SWIZZLE_64B);
  CUtensorMap mWu = make_map(enc, p.wu, 1024, 3584, 256, 32, CU_TENSOR_MAP_SWIZZLE_64B);
  CUtensorMap mWd = make_map3(enc, p.wd, 3584, 1024, 32, 8);
  CUtensorMap mWm = make_map(enc, p.w_mod, 1024, 6144, 16, 256, CU_TENSOR_MAP_SWIZZLE_NONE);
  CUtensorMap mWh = make_map(enc, p.w_mod, 1024, 6144, 256, 32, CU_TENSOR_MAP_SWIZZLE_64B);
  CUtensorMap mWs = make_map(enc, p.w_mod, 1024, 6144, 128, 128, CU_TENSOR_MAP_SWIZZLE_NONE);
  cudaFuncSetAttribute(fused_kernel, cudaFuncAttributeMaxDynamicSharedMemorySize, SMEM_BYTES);
  fused_kernel<<<NCTA, NTHREADS, SMEM_BYTES>>>(p, mH, mWq, mK, mV, mO, mWo, mX, mOut, mWg, mWu, mWd, mWm, mWs, mWh, mOs);
}
```

```cpp
#include <cuda_runtime.h>
#include <cuda_bf16.h>
#include <cuda.h>
#include <stdint.h>
#include <stddef.h>

#define UPD 200
#define GATED 700
#define PFW 100
#define OP0 200
#define OP3 90
#define PLD 200
#define WL 3500
#define SPT 5000
#define HD 6000
#define YD 300
#define PEEL 1
#define WU1 12

namespace {

typedef __nv_bfloat16 bf16;

constexpr int NTHREADS = 384;
constexpr int NMAIN = 128;
constexpr int NCTA = 132;
constexpr int RS = 8, RV = 16 * RS + 64;
constexpr int NREP = 4;
constexpr int NFFN = 112;

constexpr uint32_t SM_RING = 0;
constexpr uint32_t ST1 = 49152;
constexpr uint32_t ST2 = 32768;
constexpr int NST2 = 6;
constexpr uint32_t SM_STASH = 196608;
constexpr uint32_t SM_MISC = 229376;
constexpr uint32_t BAR_FULL1 = SM_MISC + 0;
constexpr uint32_t BAR_EMPTY1 = SM_MISC + 40;
constexpr uint32_t BAR_FULL2 = SM_MISC + 0;
constexpr uint32_t BAR_EMPTY2 = SM_MISC + 48;
constexpr uint32_t BAR_STASH = SM_MISC + 160;
constexpr uint32_t BAR_SFREE = SM_MISC + 176;
constexpr uint32_t BAR_TFREE = SM_MISC + 184;
constexpr uint32_t BAR_FFN = SM_MISC + 192;
constexpr uint32_t BAR_VEC = SM_MISC + 208;
constexpr uint32_t BAR_RED = SM_MISC + 216;
constexpr uint32_t BAR_XH = SM_MISC + 968;
constexpr uint32_t BAR_HS = SM_MISC + 80;
constexpr uint32_t BAR_G = SM_MISC + 112;
constexpr uint32_t BAR_T1 = SM_MISC + 120;
constexpr uint32_t BAR_HF = SM_MISC + 128;
constexpr uint32_t BAR_X = SM_MISC + 136;
constexpr uint32_t BAR_OF = SM_MISC + 224;
constexpr uint32_t BAR_ROLE = SM_MISC + 240;
constexpr uint32_t SM_ROLE = SM_MISC + 248;
constexpr uint32_t SM_GA = SM_MISC + 256;
constexpr uint32_t SM_SCAL = SM_MISC + 512;
constexpr uint32_t SM_WROW = SM_MISC + 520;
constexpr uint32_t SM_AMAX = SM_MISC + 528;
constexpr uint32_t SM_X2 = 2 * ST1, SM_OUT = 3 * ST1;
constexpr uint32_t SM_REC = SM_MISC + 1024;
constexpr uint32_t BAR_TAB = SM_MISC + 1000;
constexpr uint32_t BAR_CAND = SM_MISC + 880;
constexpr uint32_t SM_CAND = SM_MISC + 888;
constexpr uint32_t BAR_WH = SM_MISC + 960;
constexpr uint32_t SM_WSLAB = 2 * 49152 + 16384;
constexpr uint32_t SM_XROW = 2 * 49152;
constexpr uint32_t SM_RED = SM_MISC + 2048;
constexpr uint32_t SM_B1 = SM_MISC + 2048;
constexpr uint32_t SMEM_BYTES = 232448;

constexpr int NB_CONS = 1, NB_WIN = 2  , NB_OST = 4  , NB_AMAX = 6;

struct __align__(1024) Scratch {
  uint32_t epoch[32];
  uint32_t hflag[16 * 32];
  uint32_t oflag[64 * 32];
  uint2 vdone[4 * 16];
  uint32_t pad[96 + 512];
  uint32_t ticket[8 * 32];
  uint2 mod[3072];
  uint4 rec[2][NREP][2 * RV];
  uint4 lnst[1024];
  uint4 entry[8 * 16 * 8];
  uint4 cand[16 * 8 * 32];
  uint4 stats[16 * 8 * 128];
  uint4 ypart[2 * 64 * NFFN * 4];
  unsigned long long ts[NCTA * 64];
  uint16_t h[2048 * 1024];
  uint16_t o[2048 * 4096];
};
__device__ Scratch g_scratch;
#define g_epoch (p.sc->epoch[0])
#define g_hflag (p.sc->hflag)
#define g_oflag (p.sc->oflag)
#define g_mod (p.sc->mod)
#define g_entry (p.sc->entry)
#define g_cand (p.sc->cand)
#define g_stats (p.sc->stats)
#define g_ypart (p.sc->ypart)
#define g_vdone (p.sc->vdone)
#define g_lnst (p.sc->lnst)
#define g_rec (p.sc->rec)
#define g_ts (p.sc->ts)
#define g_h (p.sc->h)

struct Params {
  const bf16* w_mod; const bf16* c; Scratch* sc; const bf16* x; const bf16* w_r; bf16* out;
  const bf16* wq; const bf16* wo; const bf16* wg; const bf16* wu; const bf16* wd; const bf16* kc; const bf16* vc;
};

__device__ __forceinline__ uint32_t smem_u32(const void* p) { return (uint32_t)__cvta_generic_to_shared(p); }
__device__ __forceinline__ void mbar_init(uint32_t bar, uint32_t cnt) { asm volatile("mbarrier.init.shared::cta.b64 [%0], %1;" :: "r"(bar), "r"(cnt) : "memory"); }
__device__ __forceinline__ void mbar_expect_tx(uint32_t bar, uint32_t bytes) { asm volatile("mbarrier.arrive.expect_tx.shared::cta.b64 _, [%0], %1;" :: "r"(bar), "r"(bytes) : "memory"); }
__device__ __forceinline__ void mbar_arrive(uint32_t bar) { asm volatile("mbarrier.arrive.shared::cta.b64 _, [%0];" :: "r"(bar) : "memory"); }
__device__ __forceinline__ void mbar_arrive_cl(uint32_t cluster_addr) { asm volatile("mbarrier.arrive.shared::cluster.b64 _, [%0];" :: "r"(cluster_addr) : "memory"); }
__device__ __forceinline__ uint32_t mapa(uint32_t addr, uint32_t cta) { uint32_t r; asm("mapa.shared::cluster.u32 %0, %1, %2;" : "=r"(r) : "r"(addr), "r"(cta)); return r; }
__device__ __forceinline__ bool mbar_test(uint32_t bar, uint32_t parity) {
  uint32_t ok;
  asm volatile("{\n.reg .pred p;\nmbarrier.test_wait.parity.shared::cta.b64 p, [%1], %2;\nselp.u32 %0, 1, 0, p;\n}" : "=r"(ok) : "r"(bar), "r"(parity) : "memory");
  return ok;
}
constexpr int SPIN_LIMIT = 300000;
__device__ __forceinline__ void spin_guard(int& it) {
  asm volatile("{\n.reg .pred p;\n.reg .b64 z;\nadd.s32 %0, %0, 1;\nsetp.gt.s32 p, %0, %1;\nmov.b64 z, 0;\n@p st.volatile.global.u32 [z], %0;\n}" : "+r"(it) : "n"(SPIN_LIMIT));
}
__device__ __forceinline__ void mbar_wait_g(uint32_t bar, uint32_t parity) {
  asm volatile("{\n.reg .pred p, q;\n.reg .b32 c;\n.reg .b64 z;\nmov.b32 c, 0;\nmov.b64 z, 0;\nMW_LOOP:\n"
               "mbarrier.try_wait.parity.shared::cta.b64 p, [%0], %1;\nadd.s32 c, c, 1;\nsetp.gt.s32 q, c, %2;\n"
               "@q st.volatile.global.u32 [z], c;\n@!p bra MW_LOOP;\n}" :: "r"(bar), "r"(parity), "n"(SPIN_LIMIT) : "memory");
}
__device__ __forceinline__ void mbar_wait(uint32_t bar, uint32_t parity) {
  asm volatile("{\n.reg .pred p;\nMW_LOOP:\nmbarrier.try_wait.parity.shared::cta.b64 p, [%0], %1;\n@!p bra MW_LOOP;\n}" :: "r"(bar), "r"(parity) : "memory");
}
__device__ __forceinline__ void bb_fence(uint32_t v) {
  asm volatile("{\n.reg .pred p;\n.reg .u32 c;\nsetp.ne.u32 p, %0, 0;\n@p bra.uni BF_DONE;\nBF_LOOP:\nnanosleep.u32 1;\nmov.u32 c, %%clock;\nsetp.eq.u32 p, c, 0;\n@p bra.uni BF_LOOP;\nBF_DONE:\n}" :: "r"(v) : "memory");
}
__device__ __forceinline__ bool elect_one() {
  uint32_t pred;
  asm volatile("{\n.reg .pred P;\nelect.sync _|P, 0xffffffff;\nselp.u32 %0, 1, 0, P;\n}" : "=r"(pred));
  return pred;
}
__device__ __forceinline__ void tma_ld_hint(uint32_t dst, const CUtensorMap* m, int c0, int c1, uint32_t bar, uint64_t pol) {
  asm volatile("cp.async.bulk.tensor.2d.shared::cluster.global.mbarrier::complete_tx::bytes.L2::cache_hint [%0], [%1, {%3, %4}], [%2], %5;"
    :: "r"(dst), "l"(m), "r"(bar), "r"(c0), "r"(c1), "l"(pol) : "memory");
}
__device__ __forceinline__ void tma_ld_mc(uint32_t dst, const CUtensorMap* m, int c0, int c1, uint32_t bar) {
  asm volatile("cp.async.bulk.tensor.2d.shared::cluster.global.mbarrier::complete_tx::bytes.multicast::cluster [%0], [%1, {%3, %4}], [%2], %5;"
    :: "r"(dst), "l"(m), "r"(bar), "r"(c0), "r"(c1), "h"((uint16_t)3) : "memory");
}
__device__ __forceinline__ void tma_ld_mc_hint(uint32_t dst, const CUtensorMap* m, int c0, int c1, uint32_t bar, uint64_t pol) {
  asm volatile("cp.async.bulk.tensor.2d.shared::cluster.global.mbarrier::complete_tx::bytes.multicast::cluster.L2::cache_hint [%0], [%1, {%3, %4}], [%2], %5, %6;"
    :: "r"(dst), "l"(m), "r"(bar), "r"(c0), "r"(c1), "h"((uint16_t)3), "l"(pol) : "memory");
}
__device__ __forceinline__ void tma_ld3_hint(uint32_t dst, const CUtensorMap* m, int row, int blk, uint32_t bar, uint64_t pol) {
  asm volatile("cp.async.bulk.tensor.3d.shared::cluster.global.mbarrier::complete_tx::bytes.L2::cache_hint [%0], [%1, {0, %3, %4}], [%2], %5;"
    :: "r"(dst), "l"(m), "r"(bar), "r"(row), "r"(blk), "l"(pol) : "memory");
}
__device__ __forceinline__ void tma_st(const CUtensorMap* m, int c0, int c1, uint32_t src) {
  asm volatile("cp.async.bulk.tensor.2d.global.shared::cta.bulk_group [%0, {%2, %3}], [%1];" :: "l"(m), "r"(src), "r"(c0), "r"(c1) : "memory");
}
__device__ __forceinline__ void tma_prefetch_desc(const CUtensorMap* m) { asm volatile("prefetch.tensormap [%0];" :: "l"(m) : "memory"); }
__device__ __forceinline__ void l2_prefetch(const void* p, uint32_t bytes) { asm volatile("cp.async.bulk.prefetch.L2.global [%0], %1;" :: "l"(p), "r"(bytes) : "memory"); }
__device__ __forceinline__ void bulk_commit() { asm volatile("cp.async.bulk.commit_group;" ::: "memory"); }
__device__ __forceinline__ void bulk_wait_read() { asm volatile("cp.async.bulk.wait_group.read 0;" ::: "memory"); }
__device__ __forceinline__ void bulk_wait_all() { asm volatile("cp.async.bulk.wait_group 0;" ::: "memory"); }
__device__ __forceinline__ void fence_async_smem() { asm volatile("fence.proxy.async.shared::cta;" ::: "memory"); }
__device__ __forceinline__ void fence_async_global() { asm volatile("fence.proxy.async.global;" ::: "memory"); }
__device__ __forceinline__ void fence_acquire_gpu() { asm volatile("fence.acquire.gpu;" ::: "memory"); }
__device__ __forceinline__ void fence_release_gpu() { asm volatile("fence.release.gpu;" ::: "memory"); }
__device__ __forceinline__ void st_async_f32x4(uint32_t cluster_addr, const float* v, uint32_t cluster_bar) {
  asm volatile("st.async.weak.shared::cluster.mbarrier::complete_tx::bytes.v4.f32 [%0], {%1,%2,%3,%4}, [%5];"
    :: "r"(cluster_addr), "f"(v[0]), "f"(v[1]), "f"(v[2]), "f"(v[3]), "r"(cluster_bar) : "memory");
}
__device__ __forceinline__ void nb_sync(int id, int n) { asm volatile("bar.sync %0, %1;" :: "r"(id), "r"(n) : "memory"); }
__device__ __forceinline__ void nb_arrive(int id, int n) { asm volatile("bar.arrive %0, %1;" :: "r"(id), "r"(n) : "memory"); }
__device__ __forceinline__ void wg_fence() { asm volatile("wgmma.fence.sync.aligned;" ::: "memory"); }
__device__ __forceinline__ void wg_commit() { asm volatile("wgmma.commit_group.sync.aligned;" ::: "memory"); }
template <int N> __device__ __forceinline__ void wg_wait() { asm volatile("wgmma.wait_group.sync.aligned %0;" :: "n"(N) : "memory"); }
template <int N> __device__ __forceinline__ void reg_fence(float* a) {
#pragma unroll
  for (int i = 0; i < N; i++) asm volatile("" : "+f"(a[i]) :: "memory");
}
template <int N> __device__ __forceinline__ void reg_fence(uint32_t* a) {
#pragma unroll
  for (int i = 0; i < N; i++) asm volatile("" : "+r"(a[i]) :: "memory");
}
__device__ __forceinline__ uint64_t mk_desc(uint32_t addr, uint32_t lbo) {
  return (uint64_t)((addr & 0x3FFFF) >> 4) | ((uint64_t)(lbo >> 4) << 16) | ((uint64_t)(1024 >> 4) << 32) | (1ull << 62);
}

__device__ __forceinline__ uint64_t policy_evict_first() { uint64_t pol; asm("createpolicy.fractional.L2::evict_first.b64 %0, 1.0;" : "=l"(pol)); return pol; }
__device__ __forceinline__ uint32_t ld_relaxed(const uint32_t* p) { uint32_t v; asm volatile("ld.relaxed.gpu.global.u32 %0, [%1];" : "=r"(v) : "l"(p) : "memory"); return v; }
__device__ __forceinline__ void st_relaxed(uint32_t* p, uint32_t v) { asm volatile("st.relaxed.gpu.global.u32 [%0], %1;" :: "l"(p), "r"(v) : "memory"); }
__device__ __forceinline__ void red_add_relaxed(uint32_t* p, uint32_t v) { asm volatile("red.relaxed.gpu.global.add.u32 [%0], %1;" :: "l"(p), "r"(v) : "memory"); }
__device__ __forceinline__ uint2 ld_pkt8(const uint2* p) {
  uint2 v; asm volatile("{\n.reg .b64 t;\nld.relaxed.gpu.global.b64 t, [%2];\nmov.b64 {%0,%1}, t;\n}" : "=r"(v.x), "=r"(v.y) : "l"(p) : "memory"); return v;
}
__device__ __forceinline__ uint4 ld_pkt8x2(const uint4* p) {
  uint4 v; asm volatile("{\n.reg .b64 a, b;\nld.relaxed.gpu.global.v2.b64 {a, b}, [%4];\nmov.b64 {%0,%1}, a;\nmov.b64 {%2,%3}, b;\n}"
    : "=r"(v.x), "=r"(v.y), "=r"(v.z), "=r"(v.w) : "l"(p) : "memory"); return v;
}
__device__ __forceinline__ void st_pkt8(uint2* p, uint32_t a, uint32_t b) {
  asm volatile("{\n.reg .b64 t;\nmov.b64 t, {%1,%2};\nst.relaxed.gpu.global.b64 [%0], t;\n}" :: "l"(p), "r"(a), "r"(b) : "memory");
}
__device__ __forceinline__ uint4 ld_pkt16(const uint4* p) {
  uint4 v; asm volatile("{\n.reg .b128 t;\n.reg .b64 a, b;\nld.relaxed.gpu.global.b128 t, [%4];\nmov.b128 {a, b}, t;\nmov.b64 {%0,%1}, a;\nmov.b64 {%2,%3}, b;\n}"
    : "=r"(v.x), "=r"(v.y), "=r"(v.z), "=r"(v.w) : "l"(p) : "memory"); return v;
}
__device__ __forceinline__ void st_pkt16(uint4* p, uint32_t x, uint32_t y, uint32_t z, uint32_t w) {
  asm volatile("{\n.reg .b128 t;\n.reg .b64 a, b;\nmov.b64 a, {%1,%2};\nmov.b64 b, {%3,%4};\nmov.b128 t, {a, b};\nst.relaxed.gpu.global.b128 [%0], t;\n}"
    :: "l"(p), "r"(x), "r"(y), "r"(z), "r"(w) : "memory");
}
__device__ __forceinline__ void cp_async16(uint32_t dst, const void* src) { asm volatile("cp.async.cg.shared.global [%0], [%1], 16;" :: "r"(dst), "l"(src) : "memory"); }
__device__ __forceinline__ void cp_async_wait() { asm volatile("cp.async.wait_all;" ::: "memory"); }
__device__ __forceinline__ uint32_t lds32(uint32_t a) { uint32_t v; asm volatile("ld.shared.u32 %0, [%1];" : "=r"(v) : "r"(a) : "memory"); return v; }
__device__ __forceinline__ float lds_f32(uint32_t a) { float v; asm volatile("ld.shared.f32 %0, [%1];" : "=f"(v) : "r"(a) : "memory"); return v; }
__device__ __forceinline__ uint2 lds64(uint32_t a) { uint2 v; asm volatile("ld.shared.v2.u32 {%0,%1}, [%2];" : "=r"(v.x), "=r"(v.y) : "r"(a) : "memory"); return v; }
__device__ __forceinline__ uint4 lds128(uint32_t a) { uint4 v; asm volatile("ld.shared.v4.u32 {%0,%1,%2,%3}, [%4];" : "=r"(v.x), "=r"(v.y), "=r"(v.z), "=r"(v.w) : "r"(a) : "memory"); return v; }
__device__ __forceinline__ void sts32(uint32_t a, uint32_t v) { asm volatile("st.shared.u32 [%0], %1;" :: "r"(a), "r"(v) : "memory"); }
__device__ __forceinline__ void sts64(uint32_t a, uint32_t x, uint32_t y) { asm volatile("st.shared.v2.u32 [%0], {%1,%2};" :: "r"(a), "r"(x), "r"(y) : "memory"); }
__device__ __forceinline__ void sts128(uint32_t a, uint32_t x, uint32_t y, uint32_t z, uint32_t w) { asm volatile("st.shared.v4.u32 [%0], {%1,%2,%3,%4};" :: "r"(a), "r"(x), "r"(y), "r"(z), "r"(w) : "memory"); }
__device__ __forceinline__ void stsm4(uint32_t a, uint32_t x, uint32_t y, uint32_t z, uint32_t w) {
  asm volatile("stmatrix.sync.aligned.m8n8.x4.shared.b16 [%0], {%1,%2,%3,%4};" :: "r"(a), "r"(x), "r"(y), "r"(z), "r"(w) : "memory");
}
__device__ __forceinline__ void ldsm4(uint32_t a, uint32_t* r) {
  asm volatile("ldmatrix.sync.aligned.m8n8.x4.shared.b16 {%0,%1,%2,%3}, [%4];" : "=r"(r[0]), "=r"(r[1]), "=r"(r[2]), "=r"(r[3]) : "r"(a) : "memory");
}
__device__ __forceinline__ void ldsm4t(uint32_t a, uint32_t* r) {
  asm volatile("ldmatrix.sync.aligned.m8n8.x4.trans.shared.b16 {%0,%1,%2,%3}, [%4];" : "=r"(r[0]), "=r"(r[1]), "=r"(r[2]), "=r"(r[3]) : "r"(a) : "memory");
}
__device__ __forceinline__ void mma16816(float* d, const uint32_t* a, uint32_t b0, uint32_t b1) {
  asm volatile("mma.sync.aligned.m16n8k16.row.col.f32.bf16.bf16.f32 {%0,%1,%2,%3}, {%4,%5,%6,%7}, {%8,%9}, {%0,%1,%2,%3};"
    : "+f"(d[0]), "+f"(d[1]), "+f"(d[2]), "+f"(d[3]) : "r"(a[0]), "r"(a[1]), "r"(a[2]), "r"(a[3]), "r"(b0), "r"(b1));
}
__device__ __forceinline__ void mma1688(float* d, uint32_t a0, uint32_t a1, uint32_t b0) {
  asm volatile("mma.sync.aligned.m16n8k8.row.col.f32.bf16.bf16.f32 {%0,%1,%2,%3}, {%4,%5}, {%6}, {%0,%1,%2,%3};"
    : "+f"(d[0]), "+f"(d[1]), "+f"(d[2]), "+f"(d[3]) : "r"(a0), "r"(a1), "r"(b0));
}
__device__ __forceinline__ uint32_t pack2(float lo, float hi) { uint32_t r; asm("cvt.rn.bf16x2.f32 %0, %1, %2;" : "=r"(r) : "f"(hi), "f"(lo)); return r; }
__device__ __forceinline__ float lo2f(uint32_t v) { return __uint_as_float(v << 16); }
__device__ __forceinline__ float hi2f(uint32_t v) { return __uint_as_float(v & 0xffff0000u); }
__device__ __forceinline__ uint32_t hmul2(uint32_t a, uint32_t b) { uint32_t r; asm("mul.rn.bf16x2 %0, %1, %2;" : "=r"(r) : "r"(a), "r"(b)); return r; }
__device__ __forceinline__ uint32_t hadd2(uint32_t a, uint32_t b) { uint32_t r; asm("add.rn.bf16x2 %0, %1, %2;" : "=r"(r) : "r"(a), "r"(b)); return r; }
__device__ __forceinline__ uint32_t hsub2(uint32_t a, uint32_t b) { uint32_t r; asm("sub.rn.bf16x2 %0, %1, %2;" : "=r"(r) : "r"(a), "r"(b)); return r; }
__device__ __forceinline__ uint32_t hfma2(uint32_t a, uint32_t b, uint32_t c) { uint32_t r; asm("fma.rn.bf16x2 %0, %1, %2, %3;" : "=r"(r) : "r"(a), "r"(b), "r"(c)); return r; }
__device__ __forceinline__ float rbf(float v) { return lo2f(pack2(v, 0.f)); }
__device__ __forceinline__ float ex2(float v) { float r; asm("ex2.approx.ftz.f32 %0, %1;" : "=f"(r) : "f"(v)); return r; }
__device__ __forceinline__ float rcp_f(float v) { float r; asm("rcp.approx.ftz.f32 %0, %1;" : "=f"(r) : "f"(v)); return r; }
__device__ __forceinline__ float sqrt_f(float v) { float r; asm("sqrt.approx.ftz.f32 %0, %1;" : "=f"(r) : "f"(v)); return r; }
__device__ __forceinline__ float sigmoid_f(float v) { return rcp_f(1.f + ex2(-1.4426950408889634f * v)); }
__device__ __forceinline__ float silu_f(float v) { return v * sigmoid_f(v); }
constexpr uint32_t ONE2 = 0x3f803f80u;

#define R8(a,o) "+f"(a[o+0]), "+f"(a[o+1]), "+f"(a[o+2]), "+f"(a[o+3]), "+f"(a[o+4]), "+f"(a[o+5]), "+f"(a[o+6]), "+f"(a[o+7])
#define R64(a,o) R8(a,o), R8(a,o+8), R8(a,o+16), R8(a,o+24), R8(a,o+32), R8(a,o+40), R8(a,o+48), R8(a,o+56)
#define D64 "{%0,%1,%2,%3,%4,%5,%6,%7,%8,%9,%10,%11,%12,%13,%14,%15,%16,%17,%18,%19,%20,%21,%22,%23,%24,%25,%26,%27,%28,%29,%30,%31," \
            "%32,%33,%34,%35,%36,%37,%38,%39,%40,%41,%42,%43,%44,%45,%46,%47,%48,%49,%50,%51,%52,%53,%54,%55,%56,%57,%58,%59,%60,%61,%62,%63"
#define D128 D64 ",%64,%65,%66,%67,%68,%69,%70,%71,%72,%73,%74,%75,%76,%77,%78,%79,%80,%81,%82,%83,%84,%85,%86,%87,%88,%89,%90,%91,%92,%93,%94,%95," \
            "%96,%97,%98,%99,%100,%101,%102,%103,%104,%105,%106,%107,%108,%109,%110,%111,%112,%113,%114,%115,%116,%117,%118,%119,%120,%121,%122,%123,%124,%125,%126,%127"

template <int TB> __device__ __forceinline__ void wgmma_ss128(float* d, uint64_t da, uint64_t db, int acc) {
  asm volatile("{\n.reg .pred p;\nsetp.ne.b32 p, %66, 0;\nwgmma.mma_async.sync.aligned.m64n128k16.f32.bf16.bf16 " D64 "}, %64, %65, p, 1, 1, 0, %67;\n}"
    : R64(d, 0) : "l"(da), "l"(db), "r"(acc), "n"(TB));
}
template <int TB> __device__ __forceinline__ void wgmma_rs128(float* d, const uint32_t* a, uint64_t db, int acc) {
  asm volatile("{\n.reg .pred p;\nsetp.ne.b32 p, %69, 0;\nwgmma.mma_async.sync.aligned.m64n128k16.f32.bf16.bf16 " D64 "}, {%64,%65,%66,%67}, %68, p, 1, 1, %70;\n}"
    : R64(d, 0) : "r"(a[0]), "r"(a[1]), "r"(a[2]), "r"(a[3]), "l"(db), "r"(acc), "n"(TB));
}
template <int TB> __device__ __forceinline__ void wgmma_ss256(float* d, uint64_t da, uint64_t db, int acc) {
  asm volatile("{\n.reg .pred p;\nsetp.ne.b32 p, %130, 0;\nwgmma.mma_async.sync.aligned.m64n256k16.f32.bf16.bf16 " D128 "}, %128, %129, p, 1, 1, 0, %131;\n}"
    : R64(d, 0), R64(d, 64) : "l"(da), "l"(db), "r"(acc), "n"(TB));
}

#define W8(a,o) "=f"(a[o+0]), "=f"(a[o+1]), "=f"(a[o+2]), "=f"(a[o+3]), "=f"(a[o+4]), "=f"(a[o+5]), "=f"(a[o+6]), "=f"(a[o+7])
#define W64(a,o) W8(a,o), W8(a,o+8), W8(a,o+16), W8(a,o+24), W8(a,o+32), W8(a,o+40), W8(a,o+48), W8(a,o+56)
template <int TB> __device__ __forceinline__ void wgmma_ss128_z(float* d, uint64_t da, uint64_t db) {
  asm volatile("wgmma.mma_async.sync.aligned.m64n128k16.f32.bf16.bf16 " D64 "}, %64, %65, 0, 1, 1, 0, %66;"
    : W64(d, 0) : "l"(da), "l"(db), "n"(TB));
}
template <int TB> __device__ __forceinline__ void wgmma_rs128_z(float* d, const uint32_t* a, uint64_t db) {
  asm volatile("wgmma.mma_async.sync.aligned.m64n128k16.f32.bf16.bf16 " D64 "}, {%64,%65,%66,%67}, %68, 0, 1, 1, %69;"
    : W64(d, 0) : "r"(a[0]), "r"(a[1]), "r"(a[2]), "r"(a[3]), "l"(db), "n"(TB));
}
template <int TB> __device__ __forceinline__ void wgmma_ss256_z(float* d, uint64_t da, uint64_t db) {
  asm volatile("wgmma.mma_async.sync.aligned.m64n256k16.f32.bf16.bf16 " D128 "}, %128, %129, 0, 1, 1, 0, %130;"
    : W64(d, 0), W64(d, 64) : "l"(da), "l"(db), "n"(TB));
}

template <int TB> __device__ __forceinline__ void wgmma_rs256(float* d, const uint32_t* a, uint64_t db) {
  asm volatile("wgmma.mma_async.sync.aligned.m64n256k16.f32.bf16.bf16 " D128 "}, {%128,%129,%130,%131}, %132, 1, 1, 1, %133;"
    : R64(d, 0), R64(d, 64) : "r"(a[0]), "r"(a[1]), "r"(a[2]), "r"(a[3]), "l"(db), "n"(TB));
}
template <int TB> __device__ __forceinline__ void wgmma_rs256_z(float* d, const uint32_t* a, uint64_t db) {
  asm volatile("wgmma.mma_async.sync.aligned.m64n256k16.f32.bf16.bf16 " D128 "}, {%128,%129,%130,%131}, %132, 0, 1, 1, %133;"
    : W64(d, 0), W64(d, 64) : "r"(a[0]), "r"(a[1]), "r"(a[2]), "r"(a[3]), "l"(db), "n"(TB));
}
#define D32 "{%0,%1,%2,%3,%4,%5,%6,%7,%8,%9,%10,%11,%12,%13,%14,%15,%16,%17,%18,%19,%20,%21,%22,%23,%24,%25,%26,%27,%28,%29,%30,%31}"
__device__ __forceinline__ void wgmma_rs64(float* d, const uint32_t* a, uint64_t db) {
  asm volatile("wgmma.mma_async.sync.aligned.m64n64k16.f32.bf16.bf16 " D32 ", {%32,%33,%34,%35}, %36, 1, 1, 1, 0;"
    : R8(d, 0), R8(d, 8), R8(d, 16), R8(d, 24) : "r"(a[0]), "r"(a[1]), "r"(a[2]), "r"(a[3]), "l"(db));
}
__device__ __forceinline__ void wgmma_rs64_z(float* d, const uint32_t* a, uint64_t db) {
  asm volatile("wgmma.mma_async.sync.aligned.m64n64k16.f32.bf16.bf16 " D32 ", {%32,%33,%34,%35}, %36, 0, 1, 1, 0;"
    : W8(d, 0), W8(d, 8), W8(d, 16), W8(d, 24) : "r"(a[0]), "r"(a[1]), "r"(a[2]), "r"(a[3]), "l"(db));
}
__device__ __forceinline__ void issue_qk(float* S, const uint32_t* Q, uint64_t dk) {
  wgmma_rs64_z(S, Q, dk);
#pragma unroll
  for (int kk = 1; kk < 8; kk++) wgmma_rs64(S, Q + 4 * kk, dk + (kk >> 2) * 512 + (kk & 3) * 2);
}
__device__ __forceinline__ void issue_pv(float* O, const uint32_t* P, uint64_t dv, int acc) {
#pragma unroll
  for (int kk = 0; kk < 4; kk++) wgmma_rs128<1>(O, P + 4 * kk, dv + kk * 128, kk ? 1 : acc);
}

#define TS(i)
#define TSC(i)
#define TSX(i)
#define TSY(k) do { if ((tid & 127) == 0) TS((k) + 40 * wg); } while (0)
#define TT(k)
#define TV(k)
#define TR(k)
#define TQ(k)
#define TH(k)
#define TA(k)
#define TAFLUSH()

struct SoftmaxState { float c0, c1, l0, l1; bool shifted; };
constexpr float SM_SCALE = 0.08838834764831845f * 1.4426950408889634f;
__device__ __forceinline__ void softmax_start(SoftmaxState& z) { z.c0 = z.c1 = z.l0 = z.l1 = 0.f; z.shifted = false; }
__device__ __forceinline__ void softmax_half(float* S, uint32_t* P, float* O, SoftmaxState& z, bool first, uint32_t tag) {
  const float lo0 = z.l0, lo1 = z.l1;
  float lim = 1.2676506002282294e30f;
  const float low = first ? 8.673617379884035e-19f : 0.f;
  if (z.shifted) {
#pragma unroll
    for (int j = 0; j < 32; j++) S[j] += (j & 2) ? z.c1 : z.c0;
  }
#pragma unroll 1
  while (true) {
    bb_fence(tag);
#pragma unroll
    for (int j = 0; j < 8; j++) {
      const float p0 = ex2(S[4 * j]), p1 = ex2(S[4 * j + 1]), p2 = ex2(S[4 * j + 2]), p3 = ex2(S[4 * j + 3]);
      z.l0 += p0; z.l1 += p2; z.l0 += p1; z.l1 += p3;
      P[2 * j] = pack2(p0, p1); P[2 * j + 1] = pack2(p2, p3);
    }
    if (!__any_sync(0xffffffffu, !(z.l0 < lim && z.l1 < lim && fminf(z.l0, z.l1) >= low) && lim > 0.f)) break;
    float d0 = fmaxf(S[0], S[1]), d1 = fmaxf(S[2], S[3]);
#pragma unroll
    for (int j = 1; j < 8; j++) { d0 = fmaxf(d0, fmaxf(S[4 * j], S[4 * j + 1])); d1 = fmaxf(d1, fmaxf(S[4 * j + 2], S[4 * j + 3])); }
    d0 = fmaxf(d0, __shfl_xor_sync(0xffffffffu, d0, 1)); d1 = fmaxf(d1, __shfl_xor_sync(0xffffffffu, d1, 1));
    d0 = fmaxf(d0, __shfl_xor_sync(0xffffffffu, d0, 2)); d1 = fmaxf(d1, __shfl_xor_sync(0xffffffffu, d1, 2));
    if (!first) { d0 = fmaxf(d0, 0.f); d1 = fmaxf(d1, 0.f); }
    z.shifted = true;
    z.c0 -= d0; z.c1 -= d1;
#pragma unroll
    for (int j = 0; j < 32; j++) S[j] -= (j & 2) ? d1 : d0;
    const float a0 = first ? 1.f : ex2(-d0), a1 = first ? 1.f : ex2(-d1);
    z.l0 = lo0 * a0; z.l1 = lo1 * a1;
    lim = -1.f;
    wg_wait<0>();
    reg_fence<64>(O);
#pragma unroll
    for (int j = 0; j < 16; j++) { O[4 * j] *= a0; O[4 * j + 1] *= a0; O[4 * j + 2] *= a1; O[4 * j + 3] *= a1; }
  }
}

__device__ __forceinline__ void modulate_frags(uint32_t* A, const uint32_t* V, const uint4* R, const uint32_t* ln) {
#pragma unroll
  for (int kk = 0; kk < 4; kk++) {
    const uint4 sa = R[kk >> 1], c1 = R[2 + (kk >> 1)];
#pragma unroll
    for (int j = 0; j < 4; j++) {
      const uint32_t n = hfma2(V[4 * kk + j], ln[(j & 1) * 2 + 1], ln[(j & 1) * 2]);
      A[4 * kk + j] = (kk & 1) ? ((j & 2) ? hfma2(n, c1.w, sa.x) : hfma2(n, c1.z, sa.w)) : ((j & 2) ? hfma2(n, c1.y, sa.z) : hfma2(n, c1.x, sa.y));
    }
  }
}
__device__ __forceinline__ void publish_record(uint4* dst, uint32_t pk, int src, int vec, bool doit) {
  const int r = vec ? 0 : 12;
  const uint32_t x = __shfl_sync(0xffffffffu, pk, src + r), y = __shfl_sync(0xffffffffu, pk, src + ((r + 4) & 12));
  const uint32_t z = __shfl_sync(0xffffffffu, pk, src + ((r + 8) & 12)), w = __shfl_sync(0xffffffffu, pk, src + ((r + 12) & 12));
  if (doit) st_pkt16(dst, ~x, y, z, w);
}
__device__ __forceinline__ void put_record(uint32_t sb, int idx, const uint4& v) {
  sts128(sb + SM_STASH + idx * 16, ~v.x, v.y, v.z, v.w);
  sts128(sb + SM_STASH + 16384 + idx * 16, ~v.x, v.y, v.z, v.w);
}
__device__ __forceinline__ float mod_value(float v, int vec) {
  v = rbf(v);
  return (vec ? rbf(1.f + v) : v) * SM_SCALE;
}

__device__ __forceinline__ void row_rcp(float& l0, float& l1) {
  l0 += __shfl_xor_sync(0xffffffffu, l0, 1); l1 += __shfl_xor_sync(0xffffffffu, l1, 1);
  l0 += __shfl_xor_sync(0xffffffffu, l0, 2); l1 += __shfl_xor_sync(0xffffffffu, l1, 2);
  l0 = rcp_f(l0); l1 = rcp_f(l1);
}
__device__ __forceinline__ void stage_o(const float* O, float r0, float r1, uint32_t stsm_addr) {
#pragma unroll
  for (int kk = 0; kk < 8; kk++) {
    stsm4((stsm_addr + (kk >> 2) * 8192) ^ ((kk & 3) * 32),
          pack2(O[8 * kk + 0] * r0, O[8 * kk + 1] * r0), pack2(O[8 * kk + 2] * r1, O[8 * kk + 3] * r1),
          pack2(O[8 * kk + 4] * r0, O[8 * kk + 5] * r0), pack2(O[8 * kk + 6] * r1, O[8 * kk + 7] * r1));
  }
}

__global__ void __cluster_dims__(2, 1, 1) __launch_bounds__(NTHREADS, 1)
fused_kernel(const Params p, const __grid_constant__ CUtensorMap mH, const __grid_constant__ CUtensorMap mWq,
             const __grid_constant__ CUtensorMap mK, const __grid_constant__ CUtensorMap mV,
             const __grid_constant__ CUtensorMap mO, const __grid_constant__ CUtensorMap mWo,
             const __grid_constant__ CUtensorMap mX, const __grid_constant__ CUtensorMap mOut,
             const __grid_constant__ CUtensorMap mWg, const __grid_constant__ CUtensorMap mWu,
             const __grid_constant__ CUtensorMap mWd, const __grid_constant__ CUtensorMap mWm,
             const __grid_constant__ CUtensorMap mWs, const __grid_constant__ CUtensorMap mWh,
             const __grid_constant__ CUtensorMap mOs) {
  extern __shared__ __align__(1024) uint8_t smem_raw[];
  TH(0);
  const uint32_t sb = smem_u32(smem_raw);
  const int tid = threadIdx.x;
  const int b0 = blockIdx.x;
  const int lane = tid & 31;
  const int role = __shfl_sync(0xffffffffu, tid >> 8, 0);

  if (b0 >= NMAIN) {
    const uint32_t cs = clock();
    const uint32_t tag = ld_relaxed(&g_epoch) + 1;
    const int sp = b0 - NMAIN, vec = 2 + sp;
    const int warp = __shfl_sync(0xffffffffu, tid >> 5, 0);
    float* sc = reinterpret_cast<float*>(smem_raw + SM_STASH);
    float* red = reinterpret_cast<float*>(smem_raw + SM_STASH + 4096);
    const int ridx = (lane >> 3) * 2 * RV + (sp & 1) * RV + 16 * RS + (sp >> 1) * 16 + (warp & 1) * 8 + (lane & 7);
    if (warp < 8) st_pkt16(&g_rec[warp >> 2][0][ridx + (warp & 2) * 16], 0, 0, 0, 0);
#pragma unroll 1
    for (int i = tid; i < 1024; i += NTHREADS) sc[i] = rbf(silu_f(__bfloat162float(p.c[i])));
    if (tid == 0) {
      tma_prefetch_desc(&mWs);
      for (int s = 0; s < NST2; s++) { mbar_init(sb + BAR_FULL2 + 8 * s, 1); mbar_init(sb + BAR_EMPTY2 + 8 * s, 8); }
      fence_async_smem();
      while ((uint32_t)clock() - cs < SPT) {}
    }
    __syncthreads();
    int s = 0; uint32_t ph = 0;
    if (tid == 0) TS(0);
    if (warp == 8) {
      const uint64_t pol = policy_evict_first();
#pragma unroll 1
      for (int n = 0; n < 80; n++) {
        mbar_wait_g(sb + BAR_EMPTY2 + 8 * s, ph ^ 1);
        if (elect_one()) {
          mbar_expect_tx(sb + BAR_FULL2 + 8 * s, 32768);
          if (n < 16) {
            tma_ld_hint(sb + s * ST2, &mWs, (sp & 1) * 1024 + 512 + (n >> 3) * 256 + (sp >> 1) * 128, (n & 7) * 128, sb + BAR_FULL2 + 8 * s, pol);
          } else {
#pragma unroll
            for (int j = 0; j < 4; j++) tma_ld_hint(sb + s * ST2 + j * 8192, &mWm, vec * 1024 + j * 256, (n - 16) * 16, sb + BAR_FULL2 + 8 * s, pol);
          }
        }
        __syncwarp();
        if (++s == NST2) { s = 0; ph ^= 1; }
      }
    } else if (warp < 8) {
      float acc[8];
#pragma unroll
      for (int i = 0; i < 8; i++) acc[i] = 0.f;
      auto stage = [&](uint32_t a0, int da, const float* cp, int dc) {
        mbar_wait_g(sb + BAR_FULL2 + 8 * s, ph);
#pragma unroll
        for (int i = 0; i < 8; i++) {
          const uint4 v = lds128(a0 + s * ST2 + i * da);
          const float c = cp[i * dc];
          acc[0] = fmaf(lo2f(v.x), c, acc[0]); acc[1] = fmaf(hi2f(v.x), c, acc[1]);
          acc[2] = fmaf(lo2f(v.y), c, acc[2]); acc[3] = fmaf(hi2f(v.y), c, acc[3]);
          acc[4] = fmaf(lo2f(v.z), c, acc[4]); acc[5] = fmaf(hi2f(v.z), c, acc[5]);
          acc[6] = fmaf(lo2f(v.w), c, acc[6]); acc[7] = fmaf(hi2f(v.w), c, acc[7]);
        }
        if (__shfl_sync(0xffffffffu, lane, __float_as_uint(acc[7]) & 31) < 32 && lane == 0) mbar_arrive(sb + BAR_EMPTY2 + 8 * s);
        if (++s == NST2) { s = 0; ph ^= 1; }
      };
#pragma unroll 1
      for (int n = 0; n < 16; n++) {
        stage(sb + tid * 16, 4096, sc + (n & 7) * 128 + (tid >> 4), 16);
        if ((n & 7) == 7) {
          float* r2 = red + 2048 + (n & 8) * 256;
#pragma unroll
          for (int i = 0; i < 8; i++) { r2[tid * 8 + i] = acc[i]; acc[i] = 0.f; }
          nb_sync(NB_CONS, 256);
          if (warp < 2) {
            float v0 = 0.f, v1 = 0.f;
#pragma unroll 4
            for (int i = 0; i < 16; i++) { const float2 e = reinterpret_cast<const float2*>(r2)[i * 64 + tid]; v0 += e.x; v1 += e.y; }
            publish_record(&g_rec[tag & 1][0][ridx + (n >> 3) * 32], pack2(mod_value(v0, sp & 1), mod_value(v1, sp & 1)),
                           (lane & 4) * 4 + (lane & 3), sp & 1, true);
          }
          if (tid == 0) TS(1 + (n >> 3));
        }
      }
#pragma unroll 1
      for (int n = 0; n < 64; n++) {
        stage(sb + ((tid >> 5) & 3) * 8192 + (tid >> 7) * 4096 + (tid & 31) * 16, 512, sc + n * 16 + (tid >> 7) * 8, 1);
      }
#pragma unroll
      for (int i = 0; i < 8; i++) red[(tid >> 7) * 1024 + (tid & 127) * 8 + i] = acc[i];
    }
    __syncthreads();
    float dot = 0.f;
#pragma unroll 1
    for (int i = tid; i < 512; i += NTHREADS) {
      uint32_t v = pack2(red[2 * i] + red[1024 + 2 * i], red[2 * i + 1] + red[1024 + 2 * i + 1]);
      st_pkt8(&g_mod[vec * 512 + i], v, tag);
      if (vec == 4) v = hadd2(v, ONE2);
      const uint32_t wr = reinterpret_cast<const uint32_t*>(p.w_r)[i];
      dot = fmaf(lo2f(v), lo2f(wr), fmaf(hi2f(v), hi2f(wr), dot));
    }
#pragma unroll
    for (int o = 16; o; o >>= 1) dot += __shfl_xor_sync(0xffffffffu, dot, o);
    if (lane == 0) sc[warp] = dot;
    __syncthreads();
    if (tid == 0) {
      dot = 0.f;
      for (int w = 0; w < 12; w++) dot += sc[w];
      fence_release_gpu();
      st_pkt8(&g_vdone[(vec - 2) * 16], __float_as_uint(dot), tag);
      TS(11);
#pragma unroll 1
      for (int i = 0; i < 128; i++) {
        const int u = i * 4 + (b0 - NMAIN);
        l2_prefetch(p.wo + (size_t)((4 * ((u >> 4) & 7) + (u >> 7)) * 128 + (u & 15) * 8) * 1024, 16384);
        __nanosleep(PFW);
      }
    }
    return;
  }

  const uint32_t rank = b0 & 1;
  const bool slab = !(b0 & 32), late = b0 & 16;
  const uint32_t c0 = clock();
  if (tid == 352) TS(0);
  const uint32_t slab_addr = sb + SM_WSLAB + (tid >> 5) * 4096 + (lane & 3) * 128 + (lane & 4) * 16 + (((lane >> 3) ^ lane) & 3) * 16;
  auto load_slab = [&]() {
    const bf16* wp = p.w_mod + (size_t)(512 * rank + 2 * (tid & ~31) + 2 * (lane & 3) + ((lane >> 2) & 1)) * 6144 + 32 * (b0 >> 1) + 8 * (lane >> 3);
    const uint64_t pef = policy_evict_first();
#pragma unroll
    for (int i = 0; i < 8; i++)
      asm volatile("cp.async.cg.shared.global.L2::cache_hint [%0], [%1], 16, %2;"
        :: "r"(slab_addr + i * 512), "l"(wp + (size_t)i * 8 * 6144), "l"(pef) : "memory");
  };
  if (tid == 256) {
    mbar_init(sb + BAR_XH, 1); mbar_init(sb + BAR_XH + 8, 1);
    fence_async_smem();
#pragma unroll
    for (int i = 0; i < 2; i++) {
      mbar_expect_tx(sb + BAR_XH + 8 * i, 16384);
      asm volatile("cp.async.bulk.shared::cluster.global.mbarrier::complete_tx::bytes [%0], [%1], 16384, [%2];"
        :: "r"(sb + SM_XROW + i * ST1), "l"(p.x + (size_t)b0 * 16384 + i * 8192), "r"(sb + BAR_XH + 8 * i) : "memory");
    }
  }
  __syncwarp();
  uint32_t cw[8];
#pragma unroll
  for (int i = 0; i < 8; i++) cw[i] = 0;
  if (!role && slab) {
#pragma unroll
    for (int i = 0; i < 8; i++) cw[i] = ld_relaxed(reinterpret_cast<const uint32_t*>(p.c) + 256 * rank + (tid & ~28) + 4 * i);
  }
  uint32_t epoch = 0;
  if (!role) epoch = ld_relaxed(&p.sc->epoch[lane]);
  if (!role && slab && !late) load_slab();
#define TILE_ROLES() \
  mbar_wait(sb + BAR_ROLE, 0); \
  const int b = 2 * __shfl_sync(0xffffffffu, lds32(sb + SM_ROLE), 0) + rank; \
  const int rt = b >> 3;     \
  const int ct = b & 7;

  if (role) {
    asm volatile("setmaxnreg.dec.sync.aligned.u32 24;");
    const int warp = __shfl_sync(0xffffffffu, tid >> 5, 0);
    if (tid == 256) {
      mbar_init(sb + BAR_RED, 1); mbar_init(sb + BAR_WH, 1);
      for (int s = 0; s < 2; s++) mbar_init(sb + BAR_OF + 8 * s, 1);
      mbar_init(sb + BAR_ROLE, 1);
      for (int s = 0; s < 5; s++) { mbar_init(sb + BAR_FULL1 + 8 * s, 1); mbar_init(sb + BAR_EMPTY1 + 8 * s, 4); }
      for (int s = 0; s < 2; s++) { mbar_init(sb + BAR_STASH + 8 * s, 1); mbar_init(sb + BAR_X + 8 * s, 1); }
      for (int s = 0; s < 4; s++) mbar_init(sb + BAR_HS + 8 * s, 1);
      mbar_init(sb + BAR_G, 16); mbar_init(sb + BAR_T1, 1); mbar_init(sb + BAR_HF, 1);
      mbar_init(sb + BAR_SFREE, 4); mbar_init(sb + BAR_TFREE, 8);
      mbar_init(sb + BAR_FFN, 4); mbar_init(sb + BAR_FFN + 8, 2);
      mbar_init(sb + BAR_CAND, 1); mbar_init(sb + BAR_VEC, 32); for (int s = 0; s < 3; s++) mbar_init(sb + BAR_TAB + 8 * s, 32);
      mbar_expect_tx(sb + BAR_RED, 1024);
      mbar_expect_tx(sb + BAR_ROLE, 4);
      asm volatile("fence.mbarrier_init.release.cluster;" ::: "memory");
    }
    __syncwarp();
    asm volatile("barrier.cluster.arrive.relaxed.aligned;" ::: "memory");
    const int ridx = ((lane >> 1) & 3) * 2 * RV + (b0 >> 6) * RV + ((b0 >> 1) & 31) * RS + 2 * rank + (lane & 1) + (lane >> 3) * 4;
    if (warp == 11 && slab && lane < 2 * RS) { st_pkt16(&g_rec[0][0][ridx], 0, 0, 0, 0); st_pkt16(&g_rec[1][0][ridx], 0, 0, 0, 0); }
    if (tid == 256) {
      tma_prefetch_desc(&mWq); tma_prefetch_desc(&mX); tma_prefetch_desc(&mH); tma_prefetch_desc(&mK); tma_prefetch_desc(&mV); tma_prefetch_desc(&mOs);
    }
    uint32_t pairid = 0;
    if (tid == 320 && rank == 0) {
      uint32_t t;
      asm("mov.u32 %0, %%smid;" : "=r"(t));
      t >>= 1;
      uint32_t grp = ((0x73216540u >> (4 * ((t < 32 ? t : t < 60 ? 1 + (t - 32) % 7 : t < 62 ? t - 54 : 0) & 7))) & 7) - 1, slot;
      int it = 0;
      do {
        grp = (grp + 1) & 7;
        asm volatile("atom.relaxed.gpu.global.add.u32 %0, [%1], 1;" : "=r"(slot) : "l"(&p.sc->ticket[grp * 32]) : "memory");
        spin_guard(it);
      } while (slot >= 8);
      pairid = slot * 8 + grp;
    }
    __syncwarp();
    asm volatile("barrier.cluster.wait.aligned;" ::: "memory");
    if (tid == 320 && rank == 0) {
#pragma unroll
      for (int r = 0; r < 2; r++)
        asm volatile("st.async.weak.shared::cluster.mbarrier::complete_tx::bytes.b32 [%0], %1, [%2];"
          :: "r"(mapa(sb + SM_ROLE, r)), "r"(pairid), "r"(mapa(sb + BAR_ROLE, r)) : "memory");
    }
    __syncwarp();
    const uint32_t tag = ld_relaxed(&g_epoch) + 1;
    if (warp == 8) {
      TILE_ROLES();
      const int kvrow = (ct >> 1) * 2048 + 1536, arow = rt * 128 + rank * 64;
      const uint64_t pef = policy_evict_first();
#pragma unroll 1
      for (int pair = 0; pair < 2; pair++) {
        const int wblk = (4 * ct + 2 * pair) * 2;
        if (pair) { mbar_wait_g(sb + BAR_HF, 0); fence_async_global(); }
#pragma unroll 1
        for (int n = 0; n < 16; n++) {
          const uint32_t s = n & 3, st = sb + SM_RING + s * ST1, fb = sb + BAR_FULL1 + 8 * s;
          if (n == 2 && pair == 0) mbar_wait_g(sb + BAR_G, 0);
          mbar_wait_g(fb + (BAR_EMPTY1 - BAR_FULL1), ((n >> 2) & 1) ^ 1);
          if (elect_one()) {
            mbar_expect_tx(fb, 49152);
            if (pair) tma_ld_mc_hint(st + rank * 8192, &mH, n * 64, arow, fb, pef); else
            tma_ld_mc(st + rank * 8192, pair ? &mH : &mX, n * 64, arow, fb);
            tma_ld3_hint(st + 16384, &mWq, n * 64, wblk, fb, pef);
          }
          __syncwarp();
        }
#pragma unroll 1
        for (int n = 0; n < 16; n++) {
          const uint32_t s = n & 3, st = sb + SM_RING + s * ST1 + rank * 8192, fb = sb + BAR_FULL1 + 8 * s;
          const int h0 = n == 0 ? 0 : n == 15 ? 14 : n + 1, h1 = n == 0 ? 1 : n == 15 ? 15 : n - 1;
          mbar_wait_g(fb + (BAR_EMPTY1 - BAR_FULL1), ((n >> 2) & 1) ^ 1);
          if (elect_one()) {
            mbar_expect_tx(fb, 32768);
            tma_ld_mc(st, n == 15 ? &mV : &mK, rank * 64, kvrow + (h0 & 7) * 64, fb);
            tma_ld_mc(st + 16384, n == 0 ? &mK : &mV, rank * 64, kvrow + (h1 & 7) * 64, fb);
            if (n == 3 && pair == 1) mbar_arrive(sb + BAR_T1);
          }
          __syncwarp();
        }
      }
      {
        uint32_t s = 0, ph = 1;
#pragma unroll 1
        for (int half = 0; half < 2; half++) {
          mbar_wait_g(sb + BAR_OF + 8 * half, 0);
          fence_async_global();
#pragma unroll 1
          for (int n = 32 * half; n < 32 * half + 32; n++) {
            const uint32_t st = sb + SM_RING + s * ST1, fb = sb + BAR_FULL1 + 8 * s;
            const int k0 = ((n & 14) * 2 + (n >> 4)) * 128 + (n & 1) * 64;
            mbar_wait_g(n == 8 ? sb + BAR_SFREE : fb + (BAR_EMPTY1 - BAR_FULL1), n == 8 ? 0 : ph ^ (s >> 2));
            if (elect_one()) {
              mbar_expect_tx(fb, 32768);
              tma_ld_mc_hint(st + rank * 8192, &mO, k0, arow, fb, pef);
              tma_ld3_hint(st + 16384, &mWo, k0, 2 * ct, fb, pef);
            }
            __syncwarp();
            if (++s == 5 || n == 3) { s = 0; ph ^= 1; }
          }
        }
        if (b < NFFN) {
#pragma unroll 1
          for (s = 0; s < 2; s++) {
            mbar_wait_g(sb + BAR_EMPTY1 + 8 * s, 0);
            if (elect_one()) {
              mbar_expect_tx(sb + BAR_FFN + 8, 32768);
              tma_ld3_hint(sb + SM_RING + s * ST1, &mWd, b * 32, s * 8, sb + BAR_FFN + 8, pef);
            }
            __syncwarp();
          }
        }
      }
    } else if (warp <= 10) {
      const int w = warp - 9;
      if (slab && late && w == 0 && lane == 0) {
        tma_prefetch_desc(&mWh);
        mbar_expect_tx(sb + BAR_WH, 32768);
        while ((uint32_t)clock() - c0 < WL) {}
        const uint64_t pef = policy_evict_first();
#pragma unroll
        for (int i = 0; i < 2; i++) tma_ld_hint(sb + SM_WSLAB + i * 16384, &mWh, 32 * (b0 >> 1), 512 * rank + 256 * i, sb + BAR_WH, pef);
      }
      __syncwarp();
      TILE_ROLES();
      const uint32_t st = sb + SM_STASH + w * 16384;
#pragma unroll 1
      for (int j = 0; j < 2; j++) {
        nb_sync(NB_OST + w, 160);
        if (elect_one()) {
          fence_async_smem();
          tma_st(&mH, (2 * ct + j) * 64, rt * 128 + w * 64, st + 4096);
          bulk_commit();
          bulk_wait_read();
          mbar_arrive(sb + BAR_HS + 16 * w + 8 * j);
          if (j) {
            bulk_wait_all();
            fence_async_global();
            fence_release_gpu();
            red_add_relaxed(&g_hflag[rt * 32], 1);
          }
        }
        __syncwarp();
      }
#pragma unroll 1
      for (int r = 0; r < 4; r++) {
        nb_sync(NB_OST + w, 160);
        if (elect_one()) {
          fence_async_smem();
          const int hcol = (4 * ct + r) * 128;
#pragma unroll 1
          for (int i = 0; i < 8; i++) {
            tma_st(&mOs, hcol + (i & 4) * 16, rt * 128 + w * 64 + (i & 3) * 16, st + i * 2048);
            __nanosleep(r == 3 ? OP3 : OP0);
          }
          bulk_commit();
          bulk_wait_read();
          if (r < 2) {
            mbar_arrive(sb + BAR_STASH + 8 * w);
          } else if (r == 2) {
            mbar_expect_tx(sb + BAR_X + 8 * w, 16384);
            tma_ld_hint(st, &mX, ct * 128, rt * 128 + w * 64, sb + BAR_X + 8 * w, policy_evict_first());
            tma_ld_hint(st + 8192, &mX, ct * 128 + 64, rt * 128 + w * 64, sb + BAR_X + 8 * w, policy_evict_first());
          } else {
            mbar_arrive_cl(mapa(sb + BAR_SFREE, 0)); mbar_arrive_cl(mapa(sb + BAR_SFREE, 1));
          }
          bulk_wait_all();
          fence_async_global();
          fence_release_gpu();
          red_add_relaxed(&g_oflag[(rt * 4 + r) * 32], 1);
        }
        __syncwarp();
      }
      nb_sync(NB_OST + w, 160);
      int skip = -1;
      mbar_wait_g(sb + BAR_CAND, 0);
      const bool has_cand = (lds32(sb + SM_CAND) >> 6) == w;
      if (has_cand) {
        nb_sync(NB_WIN + w, 160);
        skip = (int)lds32(sb + SM_WROW + 4 * w) - (rt * 128 + w * 64);
      }
      if ((unsigned)skip >= 64u) {
        if (elect_one()) {
          fence_async_smem();
          tma_st(&mOut, ct * 128, rt * 128 + w * 64, sb + SM_OUT + w * 16384);
          tma_st(&mOut, ct * 128 + 64, rt * 128 + w * 64, sb + SM_OUT + w * 16384 + 8192);
          bulk_commit();
          bulk_wait_read();
        }
        __syncwarp();
      } else {
        uint4* dst = reinterpret_cast<uint4*>(p.out + (size_t)(rt * 128 + w * 64 + (lane >> 4)) * 1024 + ct * 128) + (lane & 15);
#pragma unroll 2
        for (int r = lane >> 4; r < 64; r += 2) {
          const uint4 v = lds128(sb + SM_OUT + w * 16384 + ((lane >> 3) & 1) * 8192 + r * 128 + (((lane ^ r) & 7) * 16));
          if (r != skip) *dst = v;
          dst += 256;
        }
      }
      if (!has_cand) nb_sync(NB_WIN + w, 160);
    } else {
      if (slab) {
        mbar_wait_g(sb + BAR_RED, 0);
        float v = 0.f;
#pragma unroll
        for (int w = 0; w < 8; w++) v += lds_f32(sb + SM_RED + w * 128 + lane * 4);
        v += __shfl_xor_sync(0xffffffffu, v, 16);
        v = mod_value(v, b0 >> 6);
        publish_record(&g_rec[tag & 1][0][ridx], pack2(v, __shfl_down_sync(0xffffffffu, v, 1)), 2 * (lane & 1), b0 >> 6, lane < 8);
        if (lane == 0) TS(1);
      }
      mbar_wait_g(sb + BAR_G, 0);
#pragma unroll 1
      for (int i = 1; i < 4; i++) {
        const uint4* mp = &g_rec[tag & 1][(b0 >> 1) & (NREP - 1)][i == 1 ? (8 + (lane >> 2)) * RS + (lane & 3) : 16 * RS - 64 + 32 * i + lane];
        uint4 v0, v1; int it = 0;
        while (true) {
          v0 = ld_pkt16(mp); v1 = ld_pkt16(mp + RV);
          if (v0.x != 0 && v1.x != 0) break;
          spin_guard(it); __nanosleep(PLD);
        }
        put_record(sb, 32 * i + lane, v0);
        put_record(sb, 128 + 32 * i + lane, v1);
        mbar_arrive(sb + BAR_TAB - 8 + 8 * i);
        if (lane == 0) {
          TS(3 + i + (i > 2));
          if (i == 1) l2_prefetch(((b0 & 64) ? p.vc : p.kc) + (size_t)(((b0 >> 4) & 3) * 2048 + 1536) * 128 + (b0 & 15) * 4096, 8192);
        }
        __syncwarp();
      }
      TILE_ROLES();
      if (lane == 0) {
        int it = 0;
        do { __nanosleep(500); spin_guard(it); } while (ld_relaxed(&g_hflag[rt * 32]) != tag * 16u);
        fence_acquire_gpu();
        mbar_arrive(sb + BAR_HF);
        if (b < NFFN) for (int i = 0; i < 8; i++) { __nanosleep(800); l2_prefetch(p.wd + (size_t)(b * 32 + i * 4) * 1024, 8192); }
      }
      __syncwarp();
      {
        uint2 v; int it = 0;
        do { __nanosleep(1000); v = ld_pkt8(&g_vdone[(lane & 3) * 16]); spin_guard(it); }
        while (!(v.y == tag));
        __syncwarp();
        fence_acquire_gpu();
        if (lane == 1 || lane == 2) sts32(sb + SM_SCAL + (2 - lane) * 4, v.x);
      }
#pragma unroll 1
      for (int i = 0; i < 2; i++) {
        const int q = i * 32 + lane, pi = ct * 64 + q;
        const uint32_t vga = g_mod[2 * 512 + pi].x, vsb = g_mod[3 * 512 + pi].x, vcb = g_mod[4 * 512 + pi].x, vgb = g_mod[5 * 512 + pi].x;
        const uint32_t wr = reinterpret_cast<const uint32_t*>(p.w_r)[pi];
        const uint32_t c1 = hadd2(vcb, ONE2);
        const float al = lo2f(c1) * lo2f(wr), ah = hi2f(c1) * hi2f(wr);
        const uint32_t o8 = (q & 3) * 8 + ((q >> 2) & 1) * 4;
        sts32(sb + SM_GA + (q >> 3) * 32 + o8, vga);
        sts128(sb + SM_REC + q * 16, c1, vsb, vgb, 0);
        const uint32_t ahi = pack2(al, ah), alo = pack2(al - lo2f(ahi), ah - hi2f(ahi));
        const uint32_t ba = sb + SM_B1 + (q >> 3) * 128 + o8;
        sts32(ba, ONE2); sts32(ba + 32, ahi); sts32(ba + 64, alo); sts32(ba + 96, 0);
      }
      if (lane == 0) TS(28);
      if (lane == 0) {
        tma_prefetch_desc(&mWo); tma_prefetch_desc(&mO); tma_prefetch_desc(&mOut); tma_prefetch_desc(&mWd); tma_prefetch_desc(&mWg); tma_prefetch_desc(&mWu);
#pragma unroll 1
        for (int r = 0; r < 4; r++) {
          int it = 0;
          do { __nanosleep(200); spin_guard(it); } while (ld_relaxed(&g_oflag[(rt * 4 + r) * 32]) != tag * 16u);
          if (r & 1) { fence_acquire_gpu(); mbar_arrive(sb + BAR_OF + 8 * (r >> 1)); }
          if (r == 1 && b < NFFN) {
            const uint64_t pef = policy_evict_first();
            mbar_wait_g(sb + BAR_T1, 0);
#pragma unroll 1
            for (int i = 0; i < 4; i++) {
              mbar_expect_tx(sb + BAR_FFN, 16384);
              tma_ld_hint(sb + SM_RING + i * ST1 + 32768, &mWg, b * 32, i * 256, sb + BAR_FFN, pef);
              __nanosleep(GATED);
            }
          }
        }
      }
      __syncwarp();
      if (b < NFFN) {
        mbar_wait_g(sb + BAR_TFREE, 0);
        const uint64_t pef = policy_evict_first();
#pragma unroll 1
        for (int i = 0; i < 5; i++) {
          if (i > 0 && lane == 0) {
            mbar_expect_tx(sb + BAR_FFN, 16384);
            tma_ld_hint(sb + SM_RING + (i - 1) * ST1 + 32768, &mWu, b * 32, (i - 1) * 256, sb + BAR_FFN, pef);
          }
          if (i < 4) {
#pragma unroll 1
            for (int j = 0; j < 8; j++) {
              asm volatile("prefetch.global.L2 [%0];" :: "l"(p.wu + (size_t)(i * 256 + j * 32 + lane) * 3584 + b * 32) : "memory");
              __nanosleep(UPD);
            }
            __nanosleep(500);
          }
        }
      }
      if (lane == 0) TS(29);
#pragma unroll 1
      for (int i = lane; i < 128; i += 32) st_pkt16(&g_stats[b * 128 + i], 0, 0, 0, 0);
      st_pkt16(&g_cand[b * 32 + lane], 0, 0, 0, 0);
      if (lane < 8) st_pkt16(&g_entry[(ct * 16 + rt) * 8 + lane], 0, 0, 0, 0);
#pragma unroll 1
      for (int i = lane; i < (b < NFFN ? 512 : 0); i += 32) st_pkt16(&g_ypart[((i >> 2) * NFFN + b) * 4 + (i & 3)], 0, 0, 0, 0);
      mbar_arrive(sb + BAR_VEC);
      uint4* const cp = &g_cand[b * 32 + lane];
      uint4* const ep = &g_entry[(ct * 16 + rt) * 8];
      nb_sync(NB_AMAX, 288);
      TV(0);
      const uint2 e = lds64(sb + SM_AMAX + (lane & 7) * 8);
      const int tmax = __reduce_max_sync(0xffffffffu, (int)e.x);
      const uint32_t row = ~tmax & 127;
      const int wl = row >> 4;
      const uint32_t xa = sb + SM_X2 + (row >> 6) * 16384 + (lane >> 4) * 8192 + (row & 63) * 128 + (lane & 3) * 4
                        + ((((lane >> 1) & 6) ^ (row & 7)) * 16);
      const uint32_t v0 = lds32(xa), v1 = lds32(xa ^ 16);
      if (lane == wl) st_pkt16(ep, (tmax | 127) - rt, rt * 128 + row, e.y, tag);
      st_pkt16(cp, v0, v1, tag, 0);
      if (lane == 0) { sts32(sb + SM_CAND, row); mbar_arrive(sb + BAR_CAND); }
      TV(1);
      if (lane == 0) TS(15);
    }
  } else {
    const int warp = tid >> 5;
    const int wg = warp >> 2, wq = warp & 3;
    const int g = lane >> 2, t = lane & 3;
    uint32_t tag;
    uint32_t ln[4];
    float acc[128];
    uint32_t bf[16];
    auto gemv = [&]() {
          if (late) mbar_wait(sb + BAR_WH, 0); else
          asm volatile("cp.async.wait_all;" ::: "memory");
          float d0[4] = {0.f, 0.f, 0.f, 0.f}, d1[4] = {0.f, 0.f, 0.f, 0.f};
#pragma unroll
          for (int i = 0; i < 8; i++) {
            const uint4 wv = lds128(slab_addr + i * 512);
            const uint32_t a[4] = {wv.x, wv.y, wv.z, wv.w};
            mma16816((i & 1) ? d1 : d0, a, bf[2 * i], bf[2 * i + 1]);
          }
#pragma unroll
          for (int i = 0; i < 4; i++) { d0[i] += d1[i]; d0[i] += __shfl_xor_sync(0xffffffffu, d0[i], 6); }
          const uint32_t dst = mapa(sb + SM_MISC, t & 1) - SM_MISC;
          if (!(lane & 6)) st_async_f32x4(dst + SM_RED + warp * 128 + rank * 64 + g * 8, d0, dst + BAR_RED);
          TH(4);
    };
    {
      asm volatile("barrier.cluster.arrive.relaxed.aligned;" ::: "memory");
      if (lane == 0) st_pkt16(&g_lnst[8 * b0 + warp], 0, 0, 0, 0);
      TH(1);
      asm volatile("setmaxnreg.inc.sync.aligned.u32 240;");
      TH(2);
#pragma unroll
      for (int i = 0; i < 8; i++) {
        const float sv = silu_f((g & 4) ? hi2f(cw[i]) : lo2f(cw[i]));
        const uint32_t sp = (g & 1) ? pack2(0.f, sv) : pack2(sv, 0.f);
        bf[2 * i] = (g & 2) ? 0 : sp; bf[2 * i + 1] = (g & 2) ? sp : 0;
      }
      asm volatile("barrier.cluster.wait.aligned;" ::: "memory");
#pragma unroll
      for (int i = 0; i < 128; i++) acc[i] = 0.f;
      reg_fence<128>(acc);
      tag = __shfl_sync(0xffffffffu, epoch, 0) + 1;
      TH(3);
      if (slab && !late) gemv();
      {
        {
          mbar_wait(sb + BAR_XH + 8 * wg, 0);
          TH(5);
          float ds[4] = {0.f, 0.f, 0.f, 0.f}, dq[4][4];
#pragma unroll
          for (int i = 0; i < 4; i++) { dq[i][0] = dq[i][1] = dq[i][2] = dq[i][3] = 0.f; }
#pragma unroll
          for (int i = 0; i < 8; i++) {
            uint32_t a[4];
            ldsm4(sb + SM_XROW + wg * ST1 + wq * 4096 + ((lane >> 3) & 1) * 2048 + i * 256 + (lane >> 4) * 128 + (lane & 7) * 16, a);
            mma16816(ds, a, ONE2, ONE2);
            mma16816(dq[2 * (i & 1)], a, a[0], a[2]); mma16816(dq[1 + 2 * (i & 1)], a, a[1], a[3]);
          }
          float q0 = (g & 1) ? dq[0][1] + dq[2][1] : dq[0][0] + dq[2][0], q1 = (g & 1) ? dq[1][3] + dq[3][3] : dq[1][2] + dq[3][2];
          float s0 = ds[0], s1 = ds[2];
#pragma unroll
          for (int o = 0; o < 3; o++) {
            const int m = o == 0 ? 4 : o == 1 ? 9 : 18;
            q0 += __shfl_xor_sync(0xffffffffu, q0, m); q1 += __shfl_xor_sync(0xffffffffu, q1, m);
            s0 += __shfl_xor_sync(0xffffffffu, s0, m); s1 += __shfl_xor_sync(0xffffffffu, s1, m);
          }
          s0 *= 1.f / 1024.f; s1 *= 1.f / 1024.f;
          const uint32_t rh = pack2(rcp_f(rbf(sqrt_f(rbf(rbf(fmaxf(fmaf(-s0, s0, q0 * (1.f / 1024.f)), 0.f)) + 1e-5f)))),
                                    rcp_f(rbf(sqrt_f(rbf(rbf(fmaxf(fmaf(-s1, s1, q1 * (1.f / 1024.f)), 0.f)) + 1e-5f)))));
          if (lane == 0) st_pkt16(&g_lnst[8 * b0 + warp], pack2(-rbf(s0) * lo2f(rh), -rbf(s1) * hi2f(rh)), rh, 0, tag);
          TH(6);
          if (tid == 0) TS(2);
        }
      }
    }
    if (slab && late) gemv();
    TILE_ROLES();
    const uint32_t xa0 = sb + SM_RING + (warp * 16 + (lane & 15)) * 128 + (((lane >> 4) ^ (lane & 7)) * 16);
    uint32_t V[16];
    {
      const uint4* mp = &g_rec[tag & 1][(b0 >> 1) & (NREP - 1)][RV * wg + (lane >> 2) * RS + (lane & 3)];
      const uint4* lp = &g_lnst[(8 * rt + warp) * 8 + (g >> 1)];
      mbar_wait(sb + BAR_FULL1, 0);
#pragma unroll
      for (int kk = 0; kk < 4; kk++) ldsm4(xa0 ^ (kk * 32), V + 4 * kk);
      uint4 v0 = make_uint4(1, 0, 0, 0), l0, l1;
      int it = 0;
      while ((uint32_t)clock() - c0 < HD) {}
      do { if (wq == 0) v0 = ld_pkt16(mp);
           l0 = ld_pkt16(lp); l1 = ld_pkt16(lp + 4); spin_guard(it); }
        while (!(__all_sync(0xffffffffu, v0.x != 0 && l0.w == tag && l1.w == tag)));
      TH(7);
      if (wq == 0) put_record(sb, 128 * wg + lane, v0);
      const uint32_t sel = (g & 1) ? 0x3232 : 0x1010;
      ln[0] = __byte_perm(l0.x, 0, sel); ln[1] = __byte_perm(l0.y, 0, sel);
      ln[2] = __byte_perm(l1.x, 0, sel); ln[3] = __byte_perm(l1.y, 0, sel);
      __syncwarp();
      if (lane < 2) mbar_arrive_cl(mapa(sb + BAR_G, lane));
      nb_sync(NB_CONS, 256);
      if (tid == 0) TS(3);
      TH(13);
    }

    const uint32_t rel = mapa(sb + SM_MISC, lane & 1) - SM_MISC;
    const uint32_t stsm_addr = sb + SM_STASH + wg * 16384 + (wq * 16 + (lane & 15)) * 128 + (((lane >> 4) ^ (lane & 7)) * 16);

    uint32_t ph = 0;
    uint32_t X[32];
    {
      const uint32_t tab0 = sb + SM_STASH + wg * 16384 + t * 16;
      const uint64_t db0 = mk_desc(sb + SM_RING + 16384, 8192);
      uint32_t A[2][16];
      uint32_t xa[4];
#pragma unroll
      for (int kk = 0; kk < 4; kk++) xa[kk] = xa0 ^ (kk * 32);
      uint32_t tab = tab0;
      reg_fence<4>(xa);
      asm volatile("{\n.reg .pred p;\nsetp.eq.u32 p, %4, 0;\n@p ld.shared.v4.u32 {%0,%1,%2,%3}, [%5];\n}"
        : "+r"(ln[2]), "+r"(ln[0]), "+r"(ln[3]), "+r"(ln[1]) : "r"(tag), "r"(sb));
      int hs = 2 * ct;
      uint4 R[4];
#pragma unroll
      for (int kk = 0; kk < 4; kk++) R[kk] = lds128(tab + (kk >> 1) * 2048 + (kk & 1) * 64);
#pragma unroll 1
      for (int k4 = 0; k4 < 4; k4++) {
#pragma unroll
        for (int s = 0; s < 4; s++) {
          uint32_t* a = A[s & 1];
          const int sn = (s + 1) & 3;
          const uint32_t pn = (k4 + (s == 3)) & 1;
          modulate_frags(a, V, R, ln);
          if (hs == (s & 2)) {
            if (s & 1) mbar_wait(sb + BAR_HS + 16 * wg, 0);
#pragma unroll
            for (int kk = 0; kk < 4; kk++) stsm4((stsm_addr + 4096) ^ (kk * 32), a[4 * kk], a[4 * kk + 1], a[4 * kk + 2], a[4 * kk + 3]);
            nb_arrive(NB_OST + wg, 160);
          }
          if (s == 0 && k4 == 0) TH(8);
          TQ(3 * s);
          if (s == 0 && k4 == 0 && tid == 0) { TS(6); TSC(61); }
          wg_fence();
#pragma unroll
          for (int kk = 0; kk < 4; kk++) wgmma_rs256<1>(acc, a + 4 * kk, db0 + s * (ST1 >> 4) + kk * 128);
          wg_commit();
          if (s == 3) TQ(12);
          if (s == 3 && k4 < 3) mbar_wait(sb + BAR_TAB + 8 * k4, 0);
          if (s == 3) TQ(13);
#pragma unroll
          for (int kk = 0; kk < 4; kk++) R[kk] = lds128(tab + (s + 1) * 128 + (kk >> 1) * 2048 + (kk & 1) * 64);
          wg_wait<1>();
          if (k4 == 0) TH(9 + s);
          TQ(3 * s + 1);
          reg_fence<16>(A[(s & 1) ^ 1]);
          if ((tid & 127) < 2 && (s | k4)) mbar_arrive_cl(rel + BAR_EMPTY1 + 8 * ((s + 3) & 3));
          if (s < 3 || k4 < 3) {
            mbar_wait(sb + BAR_FULL1 + 8 * sn, pn);
            TQ(3 * s + 2);
#pragma unroll
            for (int kk = 0; kk < 4; kk++) ldsm4(xa[kk] + sn * ST1, V + 4 * kk);
          }
        }
        tab += 512; hs -= 4;
      }
      mbar_wait(sb + BAR_HS + 16 * wg + 8, 0);
      wg_wait<0>();
      reg_fence<128>(acc);
    }
#pragma unroll 1
    for (int pair = 0; pair < 2; pair++) {
      uint32_t Q[32];
      TR(0);
      {
        if ((tid & 127) < 2) mbar_arrive_cl(rel + BAR_EMPTY1 + 8 * 3);
        if (pair == 1) mbar_wait(sb + BAR_STASH + 8 * wg, 1);
#pragma unroll
        for (int i = 0; i < 32; i++) Q[i] = pack2(acc[2 * i], acc[2 * i + 1]);
        const uint32_t qs = sb + SM_STASH + wg * 16384 + wq * 2048 + lane * 16;
#pragma unroll
        for (int i = 0; i < 8; i++)
          sts128(qs + (i & 3) * 512 + (i >> 2) * 8192, pack2(acc[64 + 8 * i], acc[65 + 8 * i]), pack2(acc[66 + 8 * i], acc[67 + 8 * i]),
                 pack2(acc[68 + 8 * i], acc[69 + 8 * i]), pack2(acc[70 + 8 * i], acc[71 + 8 * i]));
      }
      if (tid == 0) TS(8 + pair * 2);
      TR(1);
      float O[64], SL[32], SH[32];
      uint32_t PL[16], PH[16];
      SoftmaxState z;
      const uint64_t d0 = mk_desc(sb + SM_RING, 8192);
      {
        mbar_wait(sb + BAR_FULL1, ph);
        wg_fence();
        issue_qk(SL, Q, d0);
        wg_commit();
        issue_qk(SH, Q, d0 + 1024);
        wg_commit();
#pragma unroll
        for (int i = 0; i < 64; i++) O[i] = 0.f;
        reg_fence<64>(O);
        wg_wait<1>();
        reg_fence<32>(SL);
        softmax_start(z);
        softmax_half(SL, PL, O, z, true, tag);
        wg_wait<0>();
        reg_fence<32>(SH);
        if ((tid & 127) < 2) mbar_arrive_cl(rel + BAR_EMPTY1);
      }
      float lp0 = 0.f, lp1 = 0.f;
      uint32_t dB = (uint32_t)d0 + 1 * (ST1 >> 4), dA = (uint32_t)d0 + 2 * (ST1 >> 4);
      const uint32_t dBx = dB ^ ((uint32_t)d0 + 3 * (ST1 >> 4)), dAx = dA ^ (uint32_t)d0;
      uint32_t so = 0;
      bool ready = false;
#pragma unroll 1
      for (int i = 0; i < 7; i++) {
        TA(0);
        TR(2 + i);
        if (!ready) mbar_wait(sb + BAR_FULL1 + 8 + so, ph);
        TA(1);
        TA(2);
        wg_fence();
        issue_qk(SL, Q, (d0 & 0xffffffff00000000ull) | dB);
        if (i == 4) {
          __syncwarp();
          stage_o(O, lp0, lp1, stsm_addr);
        }
        wg_fence();
        issue_pv(O, PL, ((d0 & 0xffffffff00000000ull) | dB) + 1024, i != 4);
        wg_commit();
        if (i == 4) {
          nb_arrive(NB_OST + wg, 160);
        }
        TA(3);
        ph ^= i & 1;
        ready = mbar_test(sb + BAR_FULL1 + 16 - so, ph);
        softmax_half(SH, PH, O, z, false, tag);
        TA(4);
        wg_wait<0>();
        TA(5);
        reg_fence<32>(SL); reg_fence<16>(PL);
        if ((tid & 127) < 2) mbar_arrive_cl(rel + BAR_EMPTY1 + 8 + so);
        if (!ready) mbar_wait(sb + BAR_FULL1 + 16 - so, ph);
        TA(6);
        wg_fence();
        issue_qk(SH, Q, (d0 & 0xffffffff00000000ull) | dA);
        wg_commit();
        issue_pv(O, PH, ((d0 & 0xffffffff00000000ull) | dA) + 1024, 1);
        wg_commit();
        if (i == 2) {
          wg_wait<1>();
          reg_fence<32>(Q);
          const uint32_t qs = sb + SM_STASH + wg * 16384 + wq * 2048 + lane * 16;
#pragma unroll
          for (int j = 0; j < 8; j++) { const uint4 v = lds128(qs + (j & 3) * 512 + (j >> 2) * 8192); Q[4 * j] = v.x; Q[4 * j + 1] = v.y; Q[4 * j + 2] = v.z; Q[4 * j + 3] = v.w; }
        }
        TA(10);
        if (i == 3) { lp0 = z.l0; lp1 = z.l1; row_rcp(lp0, lp1); softmax_start(z); }
        TA(7);
        so ^= 16; dB ^= dBx; dA ^= dAx;
        ready = mbar_test(sb + BAR_FULL1 + 8 + so, ph);
        softmax_half(SL, PL, O, z, i == 3, tag);
        TA(8);
        wg_wait<0>();
        TA(9);
        reg_fence<32>(SH); reg_fence<16>(PH); reg_fence<64>(O); reg_fence<32>(Q);
        if ((tid & 127) < 2) mbar_arrive_cl(rel + BAR_EMPTY1 + so);
      }
      TAFLUSH();
      TR(9);
      {
        if (!ready) mbar_wait(sb + BAR_FULL1 + 8 * 3, ph);
        ph ^= 1;
        const uint64_t dv = d0 + 3 * (ST1 >> 4);
        wg_fence();
        issue_pv(O, PL, dv, 1);
        wg_commit();
        bb_fence(tag);
        softmax_half(SH, PH, O, z, false, tag);
        wg_fence();
        issue_pv(O, PH, dv + 1024, 1);
        wg_commit();
        TR(10);
        row_rcp(z.l0, z.l1);
        mbar_wait(sb + (pair ? BAR_X : BAR_STASH) + 8 * wg, 0);
#pragma unroll
        for (int kk = 0; kk < 8; kk++) ldsm4((stsm_addr + (kk >> 2) * 8192) ^ ((kk & 3) * 32), X + 4 * kk);
        reg_fence<32>(X);
        __syncwarp();
        wg_wait<0>();
        reg_fence<64>(O);
        TR(11);
        if ((tid & 127) < 2) mbar_arrive_cl(rel + BAR_EMPTY1 + 8 * 3);
        stage_o(O, z.l0, z.l1, stsm_addr);
        nb_arrive(NB_OST + wg, 160);
      }
      TR(12);
      if (tid == 0) { TS(9 + pair * 2); TSC(62); }
      if (pair == 1) break;
      {
        mbar_wait(sb + BAR_FULL1, ph);
        const uint64_t da = mk_desc(sb + SM_RING + wg * 8192, 16), db = mk_desc(sb + SM_RING + 16384, 8192);
        wg_fence();
        wgmma_ss256_z<1>(acc, da, db);
#pragma unroll
        for (int kk = 1; kk < 4; kk++) wgmma_ss256<1>(acc, da + kk * 2, db + kk * 128, 1);
        wg_commit();
      }
#pragma unroll 1
      for (int kt = 1; kt < 16; kt++) {
        const uint32_t s = kt & 3;
        if (s == 0) ph ^= 1;
        mbar_wait(sb + BAR_FULL1 + 8 * s, ph);
        const uint32_t st = sb + SM_RING + s * ST1;
        const uint64_t da = mk_desc(st + wg * 8192, 16), db = mk_desc(st + 16384, 8192);
        wg_fence();
#pragma unroll
        for (int kk = 0; kk < 4; kk++) wgmma_ss256<1>(acc, da + kk * 2, db + kk * 128, 1);
        wg_commit();
        wg_wait<1>();
        if ((tid & 127) < 2) mbar_arrive_cl(rel + BAR_EMPTY1 + 8 * ((s + 3) & 3));
      }
      ph ^= 1;
      wg_wait<0>();
      reg_fence<128>(acc);
      TR(13);
    }

    uint4 WG[16], WU[16];
    const int fp = 64 * warp + 8 * g + t;
    uint32_t fsb0, fsb1, fcb0, fcb1, fgb0, fgb1;
    const uint32_t gu_base = sb + SM_RING + (warp >> 1) * ST1 + 32768 + (warp & 1) * 8192;
    const uint32_t gu_addr = gu_base + t * 128 + (g & 1) * 64 + ((g >> 1) ^ t) * 16;
    {
      const uint64_t da0 = mk_desc(sb + SM_RING + __shfl_sync(0xffffffffu, wg, 0) * 8192, 16), db0 = mk_desc(sb + SM_RING + 16384, 8192);
#pragma unroll
      for (int n = 0; n < 4 + 5 * PEEL; n++) {
        const int s = n < 4 ? n : (n - 4) % 5;
        mbar_wait(sb + BAR_FULL1 + 8 * s, n < 4 ? 0 : ((n - 4) / 5 + (s < 4)) & 1);
        if (n < 4) TSX(40 + wg * 6 + n);
        const uint64_t da = da0 + s * (ST1 >> 4), db = db0 + s * (ST1 >> 4);
        wg_fence();
        if (n == 0) wgmma_ss128_z<1>(acc, da, db); else wgmma_ss128<1>(acc, da, db, 1);
#pragma unroll
        for (int kk = 1; kk < 4; kk++) wgmma_ss128<1>(acc, da + kk * 2, db + kk * 128, 1);
        wg_commit();
        if (n == 0 && b < NFFN) mbar_wait(sb + BAR_FFN, 0);
        {
          constexpr int NT = 4 + 5 * PEEL, F0 = NT > 16 ? NT - 16 : 0;
#pragma unroll
          for (int i = 0; i < 16; i++) if (F0 + i * (NT - F0) / 16 == n) WG[i] = lds128(gu_addr + i * 512);
        }
        if (n > 0) {
          wg_wait<1>();
          if ((tid & 127) < 2) mbar_arrive_cl(rel + BAR_EMPTY1 + 8 * (n == 4 ? 3 : s ? s - 1 : 4));
        }
      }
      TSX(44 + wg * 6);
      {
        uint32_t dep = 0;
#pragma unroll
        for (int i = 0; i < 16; i++) dep ^= WG[i].x;
        if (__shfl_sync(0xffffffffu, tag, dep & 31) == tag && lane == 2) mbar_arrive(sb + BAR_TFREE);
      }
      {
        uint32_t so = 0, sp = 4 * 8, par = PEEL + 1;
#pragma unroll 1
        for (int n = 4 + 5 * PEEL; n < 64; n++) {
          mbar_wait(sb + BAR_FULL1 + so, (par + (so >> 5)) & 1);
          const uint64_t da = da0 + so * (ST1 >> 7), db = db0 + so * (ST1 >> 7);
          wg_fence();
#pragma unroll
          for (int kk = 0; kk < 4; kk++) wgmma_ss128<1>(acc, da + kk * 2, db + kk * 128, 1);
          wg_commit();
          wg_wait<1>();
          if ((tid & 127) < 2) mbar_arrive_cl(rel + BAR_EMPTY1 + sp);
          sp = so; so += 8;
          if (so == 40) { so = 0; par++; }
        }
      }
    }
    mbar_wait(sb + BAR_VEC, 0);
    const int lrow = warp * 16 + g;
    uint2 ga[8], b1[8];
#pragma unroll
    for (int kk = 0; kk < 8; kk++) { ga[kk] = lds64(sb + SM_GA + kk * 32 + t * 8); b1[kk] = lds64(sb + SM_B1 + min(g, 3) * 32 + t * 8 + kk * 128); }
    uint4* const stp = &g_stats[b * 128 + lrow + 8 * t];
    bb_fence(tag);
    wg_wait<0>();
    reg_fence<64>(acc);
    if (tid == 0) { TS(12); TSC(63); }

    TT(0);
    {
      float d1[4] = {0.f, 0.f, 0.f, 0.f}, d2[4] = {0.f, 0.f, 0.f, 0.f}, d3[4] = {0.f, 0.f, 0.f, 0.f};
      float d4[4] = {0.f, 0.f, 0.f, 0.f}, d5[4] = {0.f, 0.f, 0.f, 0.f};
#pragma unroll
      for (int kk = 0; kk < 8; kk++) {
        uint32_t* x = X + 4 * kk;
        x[0] = hfma2(ga[kk].x, pack2(acc[8 * kk + 0], acc[8 * kk + 1]), x[0]);
        x[1] = hfma2(ga[kk].x, pack2(acc[8 * kk + 2], acc[8 * kk + 3]), x[1]);
        x[2] = hfma2(ga[kk].y, pack2(acc[8 * kk + 4], acc[8 * kk + 5]), x[2]);
        x[3] = hfma2(ga[kk].y, pack2(acc[8 * kk + 6], acc[8 * kk + 7]), x[3]);
        mma16816(d1, x, b1[kk].x, b1[kk].y);
        mma1688(d2, x[0], x[1], x[0]); mma1688(d3, x[0], x[1], x[1]);
        mma1688(d4, x[2], x[3], x[2]); mma1688(d5, x[2], x[3], x[3]);
      }
      const int qb = lane & 28;
      const float q0 = __shfl_sync(0xffffffffu, (g & 1) ? d2[1] + d4[1] : d2[0] + d4[0], qb | (g >> 1));
      const float q1 = __shfl_sync(0xffffffffu, (g & 1) ? d3[3] + d5[3] : d3[2] + d5[2], qb | (g >> 1));
      const float e0 = __shfl_xor_sync(0xffffffffu, t ? d1[0] : d1[3], 1);
      const float e1 = __shfl_sync(0xffffffffu, d1[2], qb);
      if (t < 2) st_pkt16(stp, __float_as_uint(t ? e1 : d1[0]), __float_as_uint(t ? q1 : q0),
                          __float_as_uint((t ? d1[2] : d1[1]) + e0), tag);
    }
    {
      const uint2* mp = &g_mod[3 * 512 + fp];
      fsb0 = ld_pkt8(mp).x; fsb1 = ld_pkt8(mp + 4).x; fcb0 = ld_pkt8(mp + 512).x; fcb1 = ld_pkt8(mp + 516).x;
      fgb0 = ld_pkt8(mp + 1024).x; fgb1 = ld_pkt8(mp + 1028).x;
    }
    TSY(13);
    TT(1);
    float mb, rd, den, br;
    {
      const uint4* sp = &g_stats[(rt * 8 + 4 * (t & 1)) * 128 + lrow + 4 * (t & 2)];
      mbar_wait(sb + BAR_EMPTY1 + 8 * 3, 0);
#pragma unroll
      for (int kk = 0; kk < 8; kk++) stsm4((stsm_addr - SM_STASH + SM_X2 + (kk >> 2) * 8192) ^ ((kk & 3) * 32), X[4 * kk], X[4 * kk + 1], X[4 * kk + 2], X[4 * kk + 3]);
      if (b < NFFN) mbar_wait(sb + BAR_FFN, 1);
#pragma unroll
      for (int i = 0; i < WU1; i++) WU[i] = lds128(gu_addr + i * 512);
      bb_fence(tag);
      TT(2);
      uint4 v0, v1, v2, v3;
      int it = 0;
      do { v0 = ld_pkt16(sp); v1 = ld_pkt16(sp + 128); v2 = ld_pkt16(sp + 256); v3 = ld_pkt16(sp + 384); spin_guard(it); }
        while (!(__all_sync(0xffffffffu, v0.w == tag && v1.w == tag && v2.w == tag && v3.w == tag)));
      TT(3);
      float sm = (__uint_as_float(v0.x) + __uint_as_float(v1.x)) + (__uint_as_float(v2.x) + __uint_as_float(v3.x));
      float sq = (__uint_as_float(v0.y) + __uint_as_float(v1.y)) + (__uint_as_float(v2.y) + __uint_as_float(v3.y));
      float dt = (__uint_as_float(v0.z) + __uint_as_float(v1.z)) + (__uint_as_float(v2.z) + __uint_as_float(v3.z));
      sm += __shfl_xor_sync(0xffffffffu, sm, 1); sq += __shfl_xor_sync(0xffffffffu, sq, 1); dt += __shfl_xor_sync(0xffffffffu, dt, 1);
      const uint2 scal = lds64(sb + SM_SCAL);
      const float mu = sm * (1.f / 1024.f);
      mb = rbf(mu);
      den = rbf(sqrt_f(rbf(rbf(fmaxf(fmaf(-mu, mu, sq * (1.f / 1024.f)), 0.f)) + 1e-5f)));
      rd = rcp_f(den);
      br = fmaf(fmaf(-mb, __uint_as_float(scal.x), dt), rd, __uint_as_float(scal.y));
    }
    TSY(14);
    TT(4);
    {
      const int rb = __float_as_int(br);
      const int key = ((rb ^ ((rb >> 31) & 0x7fffffff)) | 127) - (lrow + 4 * (t & 2));
      if (key == __reduce_max_sync(0xffffffffu, key)) sts64(sb + SM_AMAX + warp * 8, (uint32_t)key, pack2(mb, den));
      __syncwarp();
      nb_arrive(NB_AMAX, 288);
    }
    TT(5);
    const uint4* ep = &g_entry[(warp * 16 + (lane & 15)) * 8];
    const uint32_t slot = sb + SM_STASH + wg * 8192 + (tid & 127) * 16;
    cp_async16(slot, ep);
    {
      const float rh = rbf(rd);
      const uint32_t u = pack2(-mb * rh, rh);
      const int qb = lane & 28;
      const uint32_t u0 = __shfl_sync(0xffffffffu, u, qb), u1 = __shfl_sync(0xffffffffu, u, qb | 2);
      const uint32_t m0 = __byte_perm(u0, 0, 0x1010), h0 = __byte_perm(u0, 0, 0x3232);
      const uint32_t m1 = __byte_perm(u1, 0, 0x1010), h1 = __byte_perm(u1, 0, 0x3232);
#pragma unroll
      for (int j = 0; j < 16; j++) {
        const uint4 rec = lds128(sb + SM_REC + (4 * j + t) * 16);
        X[2 * j] = hfma2(rec.z, hfma2(hfma2(X[2 * j], h0, m0), rec.x, rec.y), X[2 * j]);
        X[2 * j + 1] = hfma2(rec.z, hfma2(hfma2(X[2 * j + 1], h1, m1), rec.x, rec.y), X[2 * j + 1]);
      }
#pragma unroll
      for (int kk = 0; kk < 8; kk++) stsm4((stsm_addr - SM_STASH + SM_OUT + (kk >> 2) * 8192) ^ ((kk & 3) * 32), X[4 * kk], X[4 * kk + 1], X[4 * kk + 2], X[4 * kk + 3]);
    }
    cp_async_wait();
    uint4 ent = lds128(slot);
    TSY(16);
    TT(6);
    int wrow;
    uint32_t xs0, xs1, hs0, hs1;
    uint32_t WD[64];
    const uint32_t wd_addr = sb + SM_RING + wg * ST1 + wq * 8192 + ((lane & 7) + ((lane >> 4) << 3)) * 128 + ((((lane >> 3) & 1) ^ (lane & 7)) * 16);
    {
      int gmax;
      auto leader = [&]() {
        gmax = __reduce_max_sync(0xffffffffu, ent.w == tag ? (int)ent.x : (int)0x8000000f);
        return ~gmax & 15;
      };
      int wt = leader(), it = 0;
      TT(7);
      nb_arrive(NB_OST + wg, 160);
      TT(8);
      cp_async16(slot + 2048, &g_cand[(wt * 8 + warp) * 32 + lane]);
      if (ent.w != tag) cp_async16(slot, ep);
#pragma unroll
      for (int i = WU1; i < 16; i++) WU[i] = lds128(gu_addr + i * 512);
      if (b < NFFN) mbar_wait(sb + BAR_FFN + 8, 0);
#pragma unroll
      for (int mt = 0; mt < 8; mt++)
#pragma unroll
        for (int s = 0; s < 2; s++) ldsm4t((wd_addr + (mt >> 2) * 4096 + s * 2048) ^ ((mt & 3) * 32), WD + (mt * 2 + s) * 4);
      cp_async_wait();
      uint4 v = lds128(slot + 2048);
      ent = lds128(slot);
      TT(9);
      while (true) {
        const int have = wt;
        wt = leader();
        if (__all_sync(0xffffffffu, ent.w == tag && have == wt && v.z == tag)) break;
        v = ld_pkt16(&g_cand[(wt * 8 + warp) * 32 + lane]);
        if (ent.w != tag) ent = ld_pkt16(ep);
        spin_guard(it);
      }
      TT(10);
      ent.x = gmax ^ ((gmax >> 31) & 0x7fffffff);
      wrow = __shfl_sync(0xffffffffu, ent.y, wt); ent.z = __shfl_sync(0xffffffffu, ent.z, wt);
      xs0 = v.x; xs1 = v.y;
      const uint32_t mm = __byte_perm(ent.z, 0, 0x1010);
      const float rs = rcp_f(hi2f(ent.z));
      const uint32_t e0 = hsub2(xs0, mm), e1 = hsub2(xs1, mm);
      hs0 = hfma2(pack2(lo2f(e0) * rs, hi2f(e0) * rs), hadd2(fcb0, ONE2), fsb0);
      hs1 = hfma2(pack2(lo2f(e1) * rs, hi2f(e1) * rs), hadd2(fcb1, ONE2), fsb1);
    }
    if ((tid & 127) == 0) sts32(sb + SM_WROW + 4 * wg, wrow);
    nb_arrive(NB_WIN + wg, 160);
    TSY(17);
    TT(11);
    if (b < NFFN) {
      float da[4][4];
#pragma unroll
      for (int i = 0; i < 4; i++) { da[i][0] = da[i][1] = da[i][2] = da[i][3] = 0.f; }
      const uint32_t selv = ((g & 1) ? 0x1044 : 0x4410) + ((g & 4) ? ((g & 1) ? 0x2200 : 0x0022) : 0);
      const uint32_t sel0 = (g & 2) ? 0x4444 : selv, sel1 = (g & 2) ? selv : 0x4444;
#pragma unroll
      for (int s = 0; s < 16; s++) {
        const uint32_t v = __shfl_sync(0xffffffffu, (s & 1) ? hs1 : hs0, 4 * (s >> 1) + t);
        const uint32_t b0 = __byte_perm(v, 0, sel0), b1 = __byte_perm(v, 0, sel1);
        const uint32_t a0[4] = {WG[s].x, WG[s].y, WG[s].z, WG[s].w};
        const uint32_t a1[4] = {WU[s].x, WU[s].y, WU[s].z, WU[s].w};
        mma16816(da[(s & 1) * 2], a0, b0, b1);
        mma16816(da[(s & 1) * 2 + 1], a1, b0, b1);
      }
      {
        float v[4];
#pragma unroll
        for (int i = 0; i < 4; i++) {
          const float vg = da[0][i] + da[2][i], vu = da[1][i] + da[3][i];
          v[i] = ((g & 1) ? vu : vg) + __shfl_xor_sync(0xffffffffu, (g & 1) ? vg : vu, 6);
        }
        if ((t >> 1) == (g & 1))
          sts128(gu_base + (g & 1) * 128 + (g >> 1) * 32 + (t & 1) * 16, __float_as_uint(v[0]), __float_as_uint(v[1]), __float_as_uint(v[2]), __float_as_uint(v[3]));
      }
      TT(12);
      nb_sync(NB_CONS, 256);
      float gp[8], up[8];
#pragma unroll
      for (int w = 0; w < 8; w++) {
        const uint32_t a = sb + SM_RING + (w >> 1) * ST1 + 32768 + (w & 1) * 8192 + lane * 4;
        gp[w] = lds_f32(a); up[w] = lds_f32(a + 128);
      }
      const float gsum = ((gp[0] + gp[1]) + (gp[2] + gp[3])) + ((gp[4] + gp[5]) + (gp[6] + gp[7]));
      const float usum = ((up[0] + up[1]) + (up[2] + up[3])) + ((up[4] + up[5]) + (up[6] + up[7]));
      const float act = rbf(silu_f(rbf(gsum))) * rbf(usum);
      TT(13);
      const uint32_t ap = pack2(act, __shfl_down_sync(0xffffffffu, act, 1));
      const uint32_t b00 = __shfl_sync(0xffffffffu, ap, 2 * t), b01 = __shfl_sync(0xffffffffu, ap, 2 * t + 8);
      const uint32_t b10 = __shfl_sync(0xffffffffu, ap, 2 * t + 16), b11 = __shfl_sync(0xffffffffu, ap, 2 * t + 24);
      float y[8][4];
#pragma unroll
      for (int mt = 0; mt < 8; mt++) {
        y[mt][0] = y[mt][1] = y[mt][2] = y[mt][3] = 0.f;
        mma16816(y[mt], WD + (mt * 2) * 4, b00, b01);
        mma16816(y[mt], WD + (mt * 2 + 1) * 4, b10, b11);
      }
#pragma unroll
      for (int e = 0; e < 2; e++) {
        const float v0 = t == 0 ? y[e][0] : t == 1 ? y[2 + e][0] : t == 2 ? y[4 + e][0] : y[6 + e][0];
        const float v1 = t == 0 ? y[e][2] : t == 1 ? y[2 + e][2] : t == 2 ? y[4 + e][2] : y[6 + e][2];
        st_pkt8(reinterpret_cast<uint2*>(g_ypart) + (((tag & 1) * 64 + 8 * warp + 2 * t + e) * NFFN + b) * 8 + g, ~__float_as_uint(v0), __float_as_uint(v1));
      }
    }
    TSY(18);
    TT(14);
    if (b & 1) return;
    {
      const int pw = warp - (warp > (b >> 4));
      if (warp != (b >> 4)) {
        const uint4* yp = &g_ypart[((tag & 1) * 64 + (b >> 1)) * NFFN * 4 + pw * 64 + lane];
        uint4 v0, v1;
        int it = 0;
        { const uint32_t c1 = clock(); while ((uint32_t)clock() - c1 < (b < NFFN ? YD : YD + 1500)) {} }
        do { v0 = ld_pkt8x2(yp); v1 = ld_pkt8x2(yp + 32); spin_guard(it); }
        while (!(__all_sync(0xffffffffu, v0.x != 0 && v0.z != 0 && v1.x != 0 && v1.z != 0)));
        float y[4] = {__uint_as_float(~v0.x) + __uint_as_float(~v1.x), __uint_as_float(~v0.z) + __uint_as_float(~v1.z),
                      __uint_as_float(v0.y) + __uint_as_float(v1.y), __uint_as_float(v0.w) + __uint_as_float(v1.w)};
#pragma unroll
        for (int o = 4; o <= 16; o <<= 1)
#pragma unroll
          for (int i = 0; i < 4; i++) y[i] += __shfl_xor_sync(0xffffffffu, y[i], o);
        if (lane < 4) sts128(sb + SM_B1 + pw * 64 + lane * 16, __float_as_uint(y[0]), __float_as_uint(y[1]), __float_as_uint(y[2]), __float_as_uint(y[3]));
      }
    }
    TT(15);
    if (warp != (b >> 4)) {
      nb_arrive(NB_CONS, 256);
    } else {
      nb_sync(NB_CONS, 256);
      float y[4] = {0.f, 0.f, 0.f, 0.f};
      if (lane < 28) { const uint4 e = lds128(sb + SM_B1 + lane * 16); y[0] = __uint_as_float(e.x); y[1] = __uint_as_float(e.y); y[2] = __uint_as_float(e.z); y[3] = __uint_as_float(e.w); }
#pragma unroll
      for (int o = 4; o <= 16; o <<= 1)
#pragma unroll
        for (int i = 0; i < 4; i++) y[i] += __shfl_xor_sync(0xffffffffu, y[i], o);
      const float ya = y[0], yb = y[1], yc = y[2], yd = y[3];
      if (g == ((b >> 1) & 7)) {
        const float rs = rbf(__uint_as_float(ent.x));
        const float sg = sigmoid_f(rs);
        const uint32_t sg2 = pack2(sg, sg);
        const uint32_t o0 = hadd2(xs0, hmul2(fgb0, hadd2(hs0, hmul2(pack2(ya, yb), sg2))));
        const uint32_t o1 = hadd2(xs1, hmul2(fgb1, hadd2(hs1, hmul2(pack2(yc, yd), sg2))));
        uint32_t* op = reinterpret_cast<uint32_t*>(p.out + (size_t)wrow * 1024) + fp;
        op[0] = o0; op[4] = o1;
      }
      if (b == 0) {
        if (lane < 8) st_relaxed(&p.sc->ticket[lane * 32], 0);
        st_relaxed(&p.sc->epoch[lane], tag);
      }
      if (lane == 0) TS(19);
    }
  }
}

typedef CUresult (*EncodeFn)(CUtensorMap*, CUtensorMapDataType, cuuint32_t, void*, const cuuint64_t*, const cuuint64_t*,
                             const cuuint32_t*, const cuuint32_t*, CUtensorMapInterleave, CUtensorMapSwizzle,
                             CUtensorMapL2promotion, CUtensorMapFloatOOBfill);

CUtensorMap make_map(EncodeFn enc, const void* ptr, uint64_t rows, uint64_t cols, uint32_t box_rows, uint32_t box_cols, CUtensorMapSwizzle sw) {
  CUtensorMap m;
  cuuint64_t dims[2] = {cols, rows};
  cuuint64_t strides[1] = {cols * 2};
  cuuint32_t box[2] = {box_cols, box_rows};
  cuuint32_t es[2] = {1, 1};
  enc(&m, CU_TENSOR_MAP_DATA_TYPE_BFLOAT16, 2, const_cast<void*>(ptr), dims, strides, box, es, CU_TENSOR_MAP_INTERLEAVE_NONE, sw,
      CU_TENSOR_MAP_L2_PROMOTION_L2_128B, CU_TENSOR_MAP_FLOAT_OOB_FILL_NONE);
  return m;
}

CUtensorMap make_map3(EncodeFn enc, const void* ptr, uint64_t rows, uint64_t cols, uint32_t box_rows, uint32_t box_blks) {
  CUtensorMap m;
  cuuint64_t dims[3] = {64, rows, cols / 64};
  cuuint64_t strides[2] = {cols * 2, 128};
  cuuint32_t box[3] = {64, box_rows, box_blks};
  cuuint32_t es[3] = {1, 1, 1};
  enc(&m, CU_TENSOR_MAP_DATA_TYPE_BFLOAT16, 3, const_cast<void*>(ptr), dims, strides, box, es, CU_TENSOR_MAP_INTERLEAVE_NONE,
      CU_TENSOR_MAP_SWIZZLE_128B, CU_TENSOR_MAP_L2_PROMOTION_L2_128B, CU_TENSOR_MAP_FLOAT_OOB_FILL_NONE);
  return m;
}

}

extern "C" void kernel_launch(void* const* d_in, const int* in_sizes, int n_in, void* d_out, int out_size) {
  (void)in_sizes; (void)n_in; (void)out_size;
  Params p;
  p.x = (const bf16*)d_in[0]; p.kc = (const bf16*)d_in[1]; p.vc = (const bf16*)d_in[2];
  p.wq = (const bf16*)d_in[3]; p.wo = (const bf16*)d_in[4]; p.w_r = (const bf16*)d_in[6];
  p.wg = (const bf16*)d_in[7]; p.wu = (const bf16*)d_in[8]; p.wd = (const bf16*)d_in[9];
  p.c = (const bf16*)d_in[10]; p.w_mod = (const bf16*)d_in[11]; p.out = (bf16*)d_out;

  void* fn = nullptr;
  cudaDriverEntryPointQueryResult st;
  cudaGetDriverEntryPoint("cuTensorMapEncodeTiled", &fn, cudaEnableDefault, &st);
  EncodeFn enc = (EncodeFn)fn;
  void* scp = nullptr;
  cudaGetSymbolAddress(&scp, g_scratch);
  p.sc = (Scratch*)scp;
  void *hp = p.sc->h, *op = p.sc->o;
  const CUtensorMapSwizzle S128 = CU_TENSOR_MAP_SWIZZLE_128B;
  CUtensorMap mH = make_map(enc, hp, 2048, 1024, 64, 64, S128);
  CUtensorMap mWq = make_map3(enc, p.wq, 1024, 4096, 64, 4);
  CUtensorMap mK = make_map(enc, p.kc, 8192, 128, 64, 64, S128);
  CUtensorMap mV = make_map(enc, p.vc, 8192, 128, 64, 64, S128);
  CUtensorMap mO = make_map(enc, op, 2048, 4096, 64, 64, S128);
  CUtensorMap mOs = make_map(enc, op, 2048, 4096, 16, 64, S128);
  CUtensorMap mWo = make_map3(enc, p.wo, 4096, 1024, 64, 2);
  CUtensorMap mX = make_map(enc, p.x, 2048, 1024, 64, 64, S128);
  CUtensorMap mOut = make_map(enc, p.out, 2048, 1024, 64, 64, S128);
  CUtensorMap mWg = make_map(enc, p.wg, 1024, 3584, 256, 32, CU_TENSOR_MAP_SWIZZLE_64B);
  CUtensorMap mWu = make_map(enc, p.wu, 1024, 3584, 256, 32, CU_TENSOR_MAP_SWIZZLE_64B);
  CUtensorMap mWd = make_map3(enc, p.wd, 3584, 1024, 32, 8);
  CUtensorMap mWm = make_map(enc, p.w_mod, 1024, 6144, 16, 256, CU_TENSOR_MAP_SWIZZLE_NONE);
  CUtensorMap mWh = make_map(enc, p.w_mod, 1024, 6144, 256, 32, CU_TENSOR_MAP_SWIZZLE_64B);
  CUtensorMap mWs = make_map(enc, p.w_mod, 1024, 6144, 128, 128, CU_TENSOR_MAP_SWIZZLE_NONE);
  cudaFuncSetAttribute(fused_kernel, cudaFuncAttributeMaxDynamicSharedMemorySize, SMEM_BYTES);
  fused_kernel<<<NCTA, NTHREADS, SMEM_BYTES>>>(p, mH, mWq, mK, mV, mO, mWo, mX, mOut, mWg, mWu, mWd, mWm, mWs, mWh, mOs);
}
```

```cpp
#include <cuda_runtime.h>
#include <cuda_bf16.h>
#include <cuda.h>
#include <stdint.h>
#include <stddef.h>

#define UPD 200
#define GATED 700
#define PFW 100
#define OP0 200
#define OP3 90
#define PLD 200
#define WL 3500
#define SPT 5000
#define HD 6000
#define YD 300
#define PEEL 1
#define WU1 12

namespace {

typedef __nv_bfloat16 bf16;

constexpr int NTHREADS = 384;
constexpr int NMAIN = 128;
constexpr int NCTA = 132;
constexpr int RS = 8, RV = 16 * RS + 64;
constexpr int NREP = 4;
constexpr int NFFN = 112;

constexpr uint32_t SM_RING = 0;
constexpr uint32_t ST1 = 49152;
constexpr uint32_t ST2 = 32768;
constexpr int NST2 = 6;
constexpr uint32_t SM_STASH = 196608;
constexpr uint32_t SM_MISC = 229376;
constexpr uint32_t BAR_FULL1 = SM_MISC + 0;
constexpr uint32_t BAR_EMPTY1 = SM_MISC + 40;
constexpr uint32_t BAR_FULL2 = SM_MISC + 0;
constexpr uint32_t BAR_EMPTY2 = SM_MISC + 48;
constexpr uint32_t BAR_STASH = SM_MISC + 160;
constexpr uint32_t BAR_SFREE = SM_MISC + 176;
constexpr uint32_t BAR_TFREE = SM_MISC + 184;
constexpr uint32_t BAR_FFN = SM_MISC + 192;
constexpr uint32_t BAR_VEC = SM_MISC + 208;
constexpr uint32_t BAR_RED = SM_MISC + 216;
constexpr uint32_t BAR_XH = SM_MISC + 968;
constexpr uint32_t BAR_HS = SM_MISC + 80;
constexpr uint32_t BAR_G = SM_MISC + 112;
constexpr uint32_t BAR_T1 = SM_MISC + 120;
constexpr uint32_t BAR_HF = SM_MISC + 128;
constexpr uint32_t BAR_X = SM_MISC + 136;
constexpr uint32_t BAR_OF = SM_MISC + 224;
constexpr uint32_t BAR_ROLE = SM_MISC + 240;
constexpr uint32_t SM_ROLE = SM_MISC + 248;
constexpr uint32_t SM_GA = SM_MISC + 256;
constexpr uint32_t SM_SCAL = SM_MISC + 512;
constexpr uint32_t SM_WROW = SM_MISC + 520;
constexpr uint32_t SM_AMAX = SM_MISC + 528;
constexpr uint32_t SM_X2 = 2 * ST1, SM_OUT = 3 * ST1;
constexpr uint32_t SM_REC = SM_MISC + 1024;
constexpr uint32_t BAR_TAB = SM_MISC + 1000;
constexpr uint32_t BAR_CAND = SM_MISC + 880;
constexpr uint32_t SM_CAND = SM_MISC + 888;
constexpr uint32_t BAR_WH = SM_MISC + 960;
constexpr uint32_t SM_WSLAB = 2 * 49152 + 16384;
constexpr uint32_t SM_XROW = 2 * 49152;
constexpr uint32_t SM_RED = SM_MISC + 2048;
constexpr uint32_t SM_B1 = SM_MISC + 2048;
constexpr uint32_t SMEM_BYTES = 232448;

constexpr int NB_CONS = 1, NB_WIN = 2  , NB_OST = 4  , NB_AMAX = 6;

struct __align__(1024) Scratch {
  uint32_t epoch[32];
  uint32_t hflag[16 * 32];
  uint32_t oflag[64 * 32];
  uint2 vdone[4 * 16];
  uint32_t pad[96 + 512];
  uint32_t ticket[8 * 32];
  uint2 mod[3072];
  uint4 rec[2][NREP][2 * RV];
  uint4 lnst[1024];
  uint4 entry[8 * 16 * 8];
  uint4 cand[16 * 8 * 32];
  uint4 stats[16 * 8 * 128];
  uint4 ypart[2 * 64 * NFFN * 4];
  unsigned long long ts[NCTA * 64];
  uint16_t h[2048 * 1024];
  uint16_t o[2048 * 4096];
};
__device__ Scratch g_scratch;
#define g_epoch (p.sc->epoch[0])
#define g_hflag (p.sc->hflag)
#define g_oflag (p.sc->oflag)
#define g_mod (p.sc->mod)
#define g_entry (p.sc->entry)
#define g_cand (p.sc->cand)
#define g_stats (p.sc->stats)
#define g_ypart (p.sc->ypart)
#define g_vdone (p.sc->vdone)
#define g_lnst (p.sc->lnst)
#define g_rec (p.sc->rec)
#define g_ts (p.sc->ts)
#define g_h (p.sc->h)

struct Params {
  const bf16* w_mod; const bf16* c; Scratch* sc; const bf16* x; const bf16* w_r; bf16* out;
  const bf16* wq; const bf16* wo; const bf16* wg; const bf16* wu; const bf16* wd; const bf16* kc; const bf16* vc;
};

__device__ __forceinline__ uint32_t smem_u32(const void* p) { return (uint32_t)__cvta_generic_to_shared(p); }
__device__ __forceinline__ void mbar_init(uint32_t bar, uint32_t cnt) { asm volatile("mbarrier.init.shared::cta.b64 [%0], %1;" :: "r"(bar), "r"(cnt) : "memory"); }
__device__ __forceinline__ void mbar_expect_tx(uint32_t bar, uint32_t bytes) { asm volatile("mbarrier.arrive.expect_tx.shared::cta.b64 _, [%0], %1;" :: "r"(bar), "r"(bytes) : "memory"); }
__device__ __forceinline__ void mbar_arrive(uint32_t bar) { asm volatile("mbarrier.arrive.shared::cta.b64 _, [%0];" :: "r"(bar) : "memory"); }
__device__ __forceinline__ void mbar_arrive_cl(uint32_t cluster_addr) { asm volatile("mbarrier.arrive.shared::cluster.b64 _, [%0];" :: "r"(cluster_addr) : "memory"); }
__device__ __forceinline__ uint32_t mapa(uint32_t addr, uint32_t cta) { uint32_t r; asm("mapa.shared::cluster.u32 %0, %1, %2;" : "=r"(r) : "r"(addr), "r"(cta)); return r; }
__device__ __forceinline__ bool mbar_test(uint32_t bar, uint32_t parity) {
  uint32_t ok;
  asm volatile("{\n.reg .pred p;\nmbarrier.test_wait.parity.shared::cta.b64 p, [%1], %2;\nselp.u32 %0, 1, 0, p;\n}" : "=r"(ok) : "r"(bar), "r"(parity) : "memory");
  return ok;
}
constexpr int SPIN_LIMIT = 300000;
__device__ __forceinline__ void spin_guard(int& it) {
  asm volatile("{\n.reg .pred p;\n.reg .b64 z;\nadd.s32 %0, %0, 1;\nsetp.gt.s32 p, %0, %1;\nmov.b64 z, 0;\n@p st.volatile.global.u32 [z], %0;\n}" : "+r"(it) : "n"(SPIN_LIMIT));
}
__device__ __forceinline__ void mbar_wait_g(uint32_t bar, uint32_t parity) {
  asm volatile("{\n.reg .pred p, q;\n.reg .b32 c;\n.reg .b64 z;\nmov.b32 c, 0;\nmov.b64 z, 0;\nMW_LOOP:\n"
               "mbarrier.try_wait.parity.shared::cta.b64 p, [%0], %1;\nadd.s32 c, c, 1;\nsetp.gt.s32 q, c, %2;\n"
               "@q st.volatile.global.u32 [z], c;\n@!p bra MW_LOOP;\n}" :: "r"(bar), "r"(parity), "n"(SPIN_LIMIT) : "memory");
}
__device__ __forceinline__ void mbar_wait(uint32_t bar, uint32_t parity) {
  asm volatile("{\n.reg .pred p;\nMW_LOOP:\nmbarrier.try_wait.parity.shared::cta.b64 p, [%0], %1;\n@!p bra MW_LOOP;\n}" :: "r"(bar), "r"(parity) : "memory");
}
__device__ __forceinline__ void bb_fence(uint32_t v) {
  asm volatile("{\n.reg .pred p;\n.reg .u32 c;\nsetp.ne.u32 p, %0, 0;\n@p bra.uni BF_DONE;\nBF_LOOP:\nnanosleep.u32 1;\nmov.u32 c, %%clock;\nsetp.eq.u32 p, c, 0;\n@p bra.uni BF_LOOP;\nBF_DONE:\n}" :: "r"(v) : "memory");
}
__device__ __forceinline__ bool elect_one() {
  uint32_t pred;
  asm volatile("{\n.reg .pred P;\nelect.sync _|P, 0xffffffff;\nselp.u32 %0, 1, 0, P;\n}" : "=r"(pred));
  return pred;
}
__device__ __forceinline__ void tma_ld_hint(uint32_t dst, const CUtensorMap* m, int c0, int c1, uint32_t bar, uint64_t pol) {
  asm volatile("cp.async.bulk.tensor.2d.shared::cluster.global.mbarrier::complete_tx::bytes.L2::cache_hint [%0], [%1, {%3, %4}], [%2], %5;"
    :: "r"(dst), "l"(m), "r"(bar), "r"(c0), "r"(c1), "l"(pol) : "memory");
}
__device__ __forceinline__ void tma_ld_mc(uint32_t dst, const CUtensorMap* m, int c0, int c1, uint32_t bar) {
  asm volatile("cp.async.bulk.tensor.2d.shared::cluster.global.mbarrier::complete_tx::bytes.multicast::cluster [%0], [%1, {%3, %4}], [%2], %5;"
    :: "r"(dst), "l"(m), "r"(bar), "r"(c0), "r"(c1), "h"((uint16_t)3) : "memory");
}
__device__ __forceinline__ void tma_ld_mc_hint(uint32_t dst, const CUtensorMap* m, int c0, int c1, uint32_t bar, uint64_t pol) {
  asm volatile("cp.async.bulk.tensor.2d.shared::cluster.global.mbarrier::complete_tx::bytes.multicast::cluster.L2::cache_hint [%0], [%1, {%3, %4}], [%2], %5, %6;"
    :: "r"(dst), "l"(m), "r"(bar), "r"(c0), "r"(c1), "h"((uint16_t)3), "l"(pol) : "memory");
}
__device__ __forceinline__ void tma_ld3_hint(uint32_t dst, const CUtensorMap* m, int row, int blk, uint32_t bar, uint64_t pol) {
  asm volatile("cp.async.bulk.tensor.3d.shared::cluster.global.mbarrier::complete_tx::bytes.L2::cache_hint [%0], [%1, {0, %3, %4}], [%2], %5;"
    :: "r"(dst), "l"(m), "r"(bar), "r"(row), "r"(blk), "l"(pol) : "memory");
}
__device__ __forceinline__ void tma_st(const CUtensorMap* m, int c0, int c1, uint32_t src) {
  asm volatile("cp.async.bulk.tensor.2d.global.shared::cta.bulk_group [%0, {%2, %3}], [%1];" :: "l"(m), "r"(src), "r"(c0), "r"(c1) : "memory");
}
__device__ __forceinline__ void tma_prefetch_desc(const CUtensorMap* m) { asm volatile("prefetch.tensormap [%0];" :: "l"(m) : "memory"); }
__device__ __forceinline__ void l2_prefetch(const void* p, uint32_t bytes) { asm volatile("cp.async.bulk.prefetch.L2.global [%0], %1;" :: "l"(p), "r"(bytes) : "memory"); }
__device__ __forceinline__ void bulk_commit() { asm volatile("cp.async.bulk.commit_group;" ::: "memory"); }
__device__ __forceinline__ void bulk_wait_read() { asm volatile("cp.async.bulk.wait_group.read 0;" ::: "memory"); }
__device__ __forceinline__ void bulk_wait_all() { asm volatile("cp.async.bulk.wait_group 0;" ::: "memory"); }
__device__ __forceinline__ void fence_async_smem() { asm volatile("fence.proxy.async.shared::cta;" ::: "memory"); }
__device__ __forceinline__ void fence_async_global() { asm volatile("fence.proxy.async.global;" ::: "memory"); }
__device__ __forceinline__ void fence_acquire_gpu() { asm volatile("fence.acquire.gpu;" ::: "memory"); }
__device__ __forceinline__ void fence_release_gpu() { asm volatile("fence.release.gpu;" ::: "memory"); }
__device__ __forceinline__ void st_async_f32x4(uint32_t cluster_addr, const float* v, uint32_t cluster_bar) {
  asm volatile("st.async.weak.shared::cluster.mbarrier::complete_tx::bytes.v4.f32 [%0], {%1,%2,%3,%4}, [%5];"
    :: "r"(cluster_addr), "f"(v[0]), "f"(v[1]), "f"(v[2]), "f"(v[3]), "r"(cluster_bar) : "memory");
}
__device__ __forceinline__ void nb_sync(int id, int n) { asm volatile("bar.sync %0, %1;" :: "r"(id), "r"(n) : "memory"); }
__device__ __forceinline__ void nb_arrive(int id, int n) { asm volatile("bar.arrive %0, %1;" :: "r"(id), "r"(n) : "memory"); }
__device__ __forceinline__ void wg_fence() { asm volatile("wgmma.fence.sync.aligned;" ::: "memory"); }
__device__ __forceinline__ void wg_commit() { asm volatile("wgmma.commit_group.sync.aligned;" ::: "memory"); }
template <int N> __device__ __forceinline__ void wg_wait() { asm volatile("wgmma.wait_group.sync.aligned %0;" :: "n"(N) : "memory"); }
template <int N> __device__ __forceinline__ void reg_fence(float* a) {
#pragma unroll
  for (int i = 0; i < N; i++) asm volatile("" : "+f"(a[i]) :: "memory");
}
template <int N> __device__ __forceinline__ void reg_fence(uint32_t* a) {
#pragma unroll
  for (int i = 0; i < N; i++) asm volatile("" : "+r"(a[i]) :: "memory");
}
__device__ __forceinline__ uint64_t mk_desc(uint32_t addr, uint32_t lbo) {
  return (uint64_t)((addr & 0x3FFFF) >> 4) | ((uint64_t)(lbo >> 4) << 16) | ((uint64_t)(1024 >> 4) << 32) | (1ull << 62);
}

__device__ __forceinline__ uint64_t policy_evict_first() { uint64_t pol; asm("createpolicy.fractional.L2::evict_first.b64 %0, 1.0;" : "=l"(pol)); return pol; }
__device__ __forceinline__ uint32_t ld_relaxed(const uint32_t* p) { uint32_t v; asm volatile("ld.relaxed.gpu.global.u32 %0, [%1];" : "=r"(v) : "l"(p) : "memory"); return v; }
__device__ __forceinline__ void st_relaxed(uint32_t* p, uint32_t v) { asm volatile("st.relaxed.gpu.global.u32 [%0], %1;" :: "l"(p), "r"(v) : "memory"); }
__device__ __forceinline__ void red_add_relaxed(uint32_t* p, uint32_t v) { asm volatile("red.relaxed.gpu.global.add.u32 [%0], %1;" :: "l"(p), "r"(v) : "memory"); }
__device__ __forceinline__ uint2 ld_pkt8(const uint2* p) {
  uint2 v; asm volatile("{\n.reg .b64 t;\nld.relaxed.gpu.global.b64 t, [%2];\nmov.b64 {%0,%1}, t;\n}" : "=r"(v.x), "=r"(v.y) : "l"(p) : "memory"); return v;
}
__device__ __forceinline__ uint4 ld_pkt8x2(const uint4* p) {
  uint4 v; asm volatile("{\n.reg .b64 a, b;\nld.relaxed.gpu.global.v2.b64 {a, b}, [%4];\nmov.b64 {%0,%1}, a;\nmov.b64 {%2,%3}, b;\n}"
    : "=r"(v.x), "=r"(v.y), "=r"(v.z), "=r"(v.w) : "l"(p) : "memory"); return v;
}
__device__ __forceinline__ void st_pkt8(uint2* p, uint32_t a, uint32_t b) {
  asm volatile("{\n.reg .b64 t;\nmov.b64 t, {%1,%2};\nst.relaxed.gpu.global.b64 [%0], t;\n}" :: "l"(p), "r"(a), "r"(b) : "memory");
}
__device__ __forceinline__ uint4 ld_pkt16(const uint4* p) {
  uint4 v; asm volatile("{\n.reg .b128 t;\n.reg .b64 a, b;\nld.relaxed.gpu.global.b128 t, [%4];\nmov.b128 {a, b}, t;\nmov.b64 {%0,%1}, a;\nmov.b64 {%2,%3}, b;\n}"
    : "=r"(v.x), "=r"(v.y), "=r"(v.z), "=r"(v.w) : "l"(p) : "memory"); return v;
}
__device__ __forceinline__ void st_pkt16(uint4* p, uint32_t x, uint32_t y, uint32_t z, uint32_t w) {
  asm volatile("{\n.reg .b128 t;\n.reg .b64 a, b;\nmov.b64 a, {%1,%2};\nmov.b64 b, {%3,%4};\nmov.b128 t, {a, b};\nst.relaxed.gpu.global.b128 [%0], t;\n}"
    :: "l"(p), "r"(x), "r"(y), "r"(z), "r"(w) : "memory");
}
__device__ __forceinline__ void cp_async16(uint32_t dst, const void* src) { asm volatile("cp.async.cg.shared.global [%0], [%1], 16;" :: "r"(dst), "l"(src) : "memory"); }
__device__ __forceinline__ void cp_async_wait() { asm volatile("cp.async.wait_all;" ::: "memory"); }
__device__ __forceinline__ uint32_t lds32(uint32_t a) { uint32_t v; asm volatile("ld.shared.u32 %0, [%1];" : "=r"(v) : "r"(a) : "memory"); return v; }
__device__ __forceinline__ float lds_f32(uint32_t a) { float v; asm volatile("ld.shared.f32 %0, [%1];" : "=f"(v) : "r"(a) : "memory"); return v; }
__device__ __forceinline__ uint2 lds64(uint32_t a) { uint2 v; asm volatile("ld.shared.v2.u32 {%0,%1}, [%2];" : "=r"(v.x), "=r"(v.y) : "r"(a) : "memory"); return v; }
__device__ __forceinline__ uint4 lds128(uint32_t a) { uint4 v; asm volatile("ld.shared.v4.u32 {%0,%1,%2,%3}, [%4];" : "=r"(v.x), "=r"(v.y), "=r"(v.z), "=r"(v.w) : "r"(a) : "memory"); return v; }
__device__ __forceinline__ void sts32(uint32_t a, uint32_t v) { asm volatile("st.shared.u32 [%0], %1;" :: "r"(a), "r"(v) : "memory"); }
__device__ __forceinline__ void sts64(uint32_t a, uint32_t x, uint32_t y) { asm volatile("st.shared.v2.u32 [%0], {%1,%2};" :: "r"(a), "r"(x), "r"(y) : "memory"); }
__device__ __forceinline__ void sts128(uint32_t a, uint32_t x, uint32_t y, uint32_t z, uint32_t w) { asm volatile("st.shared.v4.u32 [%0], {%1,%2,%3,%4};" :: "r"(a), "r"(x), "r"(y), "r"(z), "r"(w) : "memory"); }
__device__ __forceinline__ void stsm4(uint32_t a, uint32_t x, uint32_t y, uint32_t z, uint32_t w) {
  asm volatile("stmatrix.sync.aligned.m8n8.x4.shared.b16 [%0], {%1,%2,%3,%4};" :: "r"(a), "r"(x), "r"(y), "r"(z), "r"(w) : "memory");
}
__device__ __forceinline__ void ldsm4(uint32_t a, uint32_t* r) {
  asm volatile("ldmatrix.sync.aligned.m8n8.x4.shared.b16 {%0,%1,%2,%3}, [%4];" : "=r"(r[0]), "=r"(r[1]), "=r"(r[2]), "=r"(r[3]) : "r"(a) : "memory");
}
__device__ __forceinline__ void ldsm4t(uint32_t a, uint32_t* r) {
  asm volatile("ldmatrix.sync.aligned.m8n8.x4.trans.shared.b16 {%0,%1,%2,%3}, [%4];" : "=r"(r[0]), "=r"(r[1]), "=r"(r[2]), "=r"(r[3]) : "r"(a) : "memory");
}
__device__ __forceinline__ void mma16816(float* d, const uint32_t* a, uint32_t b0, uint32_t b1) {
  asm volatile("mma.sync.aligned.m16n8k16.row.col.f32.bf16.bf16.f32 {%0,%1,%2,%3}, {%4,%5,%6,%7}, {%8,%9}, {%0,%1,%2,%3};"
    : "+f"(d[0]), "+f"(d[1]), "+f"(d[2]), "+f"(d[3]) : "r"(a[0]), "r"(a[1]), "r"(a[2]), "r"(a[3]), "r"(b0), "r"(b1));
}
__device__ __forceinline__ void mma1688(float* d, uint32_t a0, uint32_t a1, uint32_t b0) {
  asm volatile("mma.sync.aligned.m16n8k8.row.col.f32.bf16.bf16.f32 {%0,%1,%2,%3}, {%4,%5}, {%6}, {%0,%1,%2,%3};"
    : "+f"(d[0]), "+f"(d[1]), "+f"(d[2]), "+f"(d[3]) : "r"(a0), "r"(a1), "r"(b0));
}
__device__ __forceinline__ uint32_t pack2(float lo, float hi) { uint32_t r; asm("cvt.rn.bf16x2.f32 %0, %1, %2;" : "=r"(r) : "f"(hi), "f"(lo)); return r; }
__device__ __forceinline__ float lo2f(uint32_t v) { return __uint_as_float(v << 16); }
__device__ __forceinline__ float hi2f(uint32_t v) { return __uint_as_float(v & 0xffff0000u); }
__device__ __forceinline__ uint32_t hmul2(uint32_t a, uint32_t b) { uint32_t r; asm("mul.rn.bf16x2 %0, %1, %2;" : "=r"(r) : "r"(a), "r"(b)); return r; }
__device__ __forceinline__ uint32_t hadd2(uint32_t a, uint32_t b) { uint32_t r; asm("add.rn.bf16x2 %0, %1, %2;" : "=r"(r) : "r"(a), "r"(b)); return r; }
__device__ __forceinline__ uint32_t hsub2(uint32_t a, uint32_t b) { uint32_t r; asm("sub.rn.bf16x2 %0, %1, %2;" : "=r"(r) : "r"(a), "r"(b)); return r; }
__device__ __forceinline__ uint32_t hfma2(uint32_t a, uint32_t b, uint32_t c) { uint32_t r; asm("fma.rn.bf16x2 %0, %1, %2, %3;" : "=r"(r) : "r"(a), "r"(b), "r"(c)); return r; }
__device__ __forceinline__ float rbf(float v) { return lo2f(pack2(v, 0.f)); }
__device__ __forceinline__ float ex2(float v) { float r; asm("ex2.approx.ftz.f32 %0, %1;" : "=f"(r) : "f"(v)); return r; }
__device__ __forceinline__ float rcp_f(float v) { float r; asm("rcp.approx.ftz.f32 %0, %1;" : "=f"(r) : "f"(v)); return r; }
__device__ __forceinline__ float sqrt_f(float v) { float r; asm("sqrt.approx.ftz.f32 %0, %1;" : "=f"(r) : "f"(v)); return r; }
__device__ __forceinline__ float sigmoid_f(float v) { return rcp_f(1.f + ex2(-1.4426950408889634f * v)); }
__device__ __forceinline__ float silu_f(float v) { return v * sigmoid_f(v); }
constexpr uint32_t ONE2 = 0x3f803f80u;

#define R8(a,o) "+f"(a[o+0]), "+f"(a[o+1]), "+f"(a[o+2]), "+f"(a[o+3]), "+f"(a[o+4]), "+f"(a[o+5]), "+f"(a[o+6]), "+f"(a[o+7])
#define R64(a,o) R8(a,o), R8(a,o+8), R8(a,o+16), R8(a,o+24), R8(a,o+32), R8(a,o+40), R8(a,o+48), R8(a,o+56)
#define D64 "{%0,%1,%2,%3,%4,%5,%6,%7,%8,%9,%10,%11,%12,%13,%14,%15,%16,%17,%18,%19,%20,%21,%22,%23,%24,%25,%26,%27,%28,%29,%30,%31," \
            "%32,%33,%34,%35,%36,%37,%38,%39,%40,%41,%42,%43,%44,%45,%46,%47,%48,%49,%50,%51,%52,%53,%54,%55,%56,%57,%58,%59,%60,%61,%62,%63"
#define D128 D64 ",%64,%65,%66,%67,%68,%69,%70,%71,%72,%73,%74,%75,%76,%77,%78,%79,%80,%81,%82,%83,%84,%85,%86,%87,%88,%89,%90,%91,%92,%93,%94,%95," \
            "%96,%97,%98,%99,%100,%101,%102,%103,%104,%105,%106,%107,%108,%109,%110,%111,%112,%113,%114,%115,%116,%117,%118,%119,%120,%121,%122,%123,%124,%125,%126,%127"

template <int TB> __device__ __forceinline__ void wgmma_ss128(float* d, uint64_t da, uint64_t db, int acc) {
  asm volatile("{\n.reg .pred p;\nsetp.ne.b32 p, %66, 0;\nwgmma.mma_async.sync.aligned.m64n128k16.f32.bf16.bf16 " D64 "}, %64, %65, p, 1, 1, 0, %67;\n}"
    : R64(d, 0) : "l"(da), "l"(db), "r"(acc), "n"(TB));
}
template <int TB> __device__ __forceinline__ void wgmma_rs128(float* d, const uint32_t* a, uint64_t db, int acc) {
  asm volatile("{\n.reg .pred p;\nsetp.ne.b32 p, %69, 0;\nwgmma.mma_async.sync.aligned.m64n128k16.f32.bf16.bf16 " D64 "}, {%64,%65,%66,%67}, %68, p, 1, 1, %70;\n}"
    : R64(d, 0) : "r"(a[0]), "r"(a[1]), "r"(a[2]), "r"(a[3]), "l"(db), "r"(acc), "n"(TB));
}
template <int TB> __device__ __forceinline__ void wgmma_ss256(float* d, uint64_t da, uint64_t db, int acc) {
  asm volatile("{\n.reg .pred p;\nsetp.ne.b32 p, %130, 0;\nwgmma.mma_async.sync.aligned.m64n256k16.f32.bf16.bf16 " D128 "}, %128, %129, p, 1, 1, 0, %131;\n}"
    : R64(d, 0), R64(d, 64) : "l"(da), "l"(db), "r"(acc), "n"(TB));
}

#define W8(a,o) "=f"(a[o+0]), "=f"(a[o+1]), "=f"(a[o+2]), "=f"(a[o+3]), "=f"(a[o+4]), "=f"(a[o+5]), "=f"(a[o+6]), "=f"(a[o+7])
#define W64(a,o) W8(a,o), W8(a,o+8), W8(a,o+16), W8(a,o+24), W8(a,o+32), W8(a,o+40), W8(a,o+48), W8(a,o+56)
template <int TB> __device__ __forceinline__ void wgmma_ss128_z(float* d, uint64_t da, uint64_t db) {
  asm volatile("wgmma.mma_async.sync.aligned.m64n128k16.f32.bf16.bf16 " D64 "}, %64, %65, 0, 1, 1, 0, %66;"
    : W64(d, 0) : "l"(da), "l"(db), "n"(TB));
}
template <int TB> __device__ __forceinline__ void wgmma_rs128_z(float* d, const uint32_t* a, uint64_t db) {
  asm volatile("wgmma.mma_async.sync.aligned.m64n128k16.f32.bf16.bf16 " D64 "}, {%64,%65,%66,%67}, %68, 0, 1, 1, %69;"
    : W64(d, 0) : "r"(a[0]), "r"(a[1]), "r"(a[2]), "r"(a[3]), "l"(db), "n"(TB));
}
template <int TB> __device__ __forceinline__ void wgmma_ss256_z(float* d, uint64_t da, uint64_t db) {
  asm volatile("wgmma.mma_async.sync.aligned.m64n256k16.f32.bf16.bf16 " D128 "}, %128, %129, 0, 1, 1, 0, %130;"
    : W64(d, 0), W64(d, 64) : "l"(da), "l"(db), "n"(TB));
}

template <int TB> __device__ __forceinline__ void wgmma_rs256(float* d, const uint32_t* a, uint64_t db) {
  asm volatile("wgmma.mma_async.sync.aligned.m64n256k16.f32.bf16.bf16 " D128 "}, {%128,%129,%130,%131}, %132, 1, 1, 1, %133;"
    : R64(d, 0), R64(d, 64) : "r"(a[0]), "r"(a[1]), "r"(a[2]), "r"(a[3]), "l"(db), "n"(TB));
}
template <int TB> __device__ __forceinline__ void wgmma_rs256_z(float* d, const uint32_t* a, uint64_t db) {
  asm volatile("wgmma.mma_async.sync.aligned.m64n256k16.f32.bf16.bf16 " D128 "}, {%128,%129,%130,%131}, %132, 0, 1, 1, %133;"
    : W64(d, 0), W64(d, 64) : "r"(a[0]), "r"(a[1]), "r"(a[2]), "r"(a[3]), "l"(db), "n"(TB));
}
#define D32 "{%0,%1,%2,%3,%4,%5,%6,%7,%8,%9,%10,%11,%12,%13,%14,%15,%16,%17,%18,%19,%20,%21,%22,%23,%24,%25,%26,%27,%28,%29,%30,%31}"
__device__ __forceinline__ void wgmma_rs64(float* d, const uint32_t* a, uint64_t db) {
  asm volatile("wgmma.mma_async.sync.aligned.m64n64k16.f32.bf16.bf16 " D32 ", {%32,%33,%34,%35}, %36, 1, 1, 1, 0;"
    : R8(d, 0), R8(d, 8), R8(d, 16), R8(d, 24) : "r"(a[0]), "r"(a[1]), "r"(a[2]), "r"(a[3]), "l"(db));
}
__device__ __forceinline__ void wgmma_rs64_z(float* d, const uint32_t* a, uint64_t db) {
  asm volatile("wgmma.mma_async.sync.aligned.m64n64k16.f32.bf16.bf16 " D32 ", {%32,%33,%34,%35}, %36, 0, 1, 1, 0;"
    : W8(d, 0), W8(d, 8), W8(d, 16), W8(d, 24) : "r"(a[0]), "r"(a[1]), "r"(a[2]), "r"(a[3]), "l"(db));
}
__device__ __forceinline__ void issue_qk(float* S, const uint32_t* Q, uint64_t dk) {
  wgmma_rs64_z(S, Q, dk);
#pragma unroll
  for (int kk = 1; kk < 8; kk++) wgmma_rs64(S, Q + 4 * kk, dk + (kk >> 2) * 512 + (kk & 3) * 2);
}
__device__ __forceinline__ void issue_pv(float* O, const uint32_t* P, uint64_t dv, int acc) {
#pragma unroll
  for (int kk = 0; kk < 4; kk++) wgmma_rs128<1>(O, P + 4 * kk, dv + kk * 128, kk ? 1 : acc);
}

#define TS(i)
#define TSC(i)
#define TSX(i)
#define TSY(k) do { if ((tid & 127) == 0) TS((k) + 40 * wg); } while (0)
#define TT(k)
#define TV(k)
#define TR(k)
#define TQ(k)
#define TH(k)
#define TA(k)
#define TAFLUSH()

struct SoftmaxState { float c0, c1, l0, l1; bool shifted; };
constexpr float SM_SCALE = 0.08838834764831845f * 1.4426950408889634f;
__device__ __forceinline__ void softmax_start(SoftmaxState& z) { z.c0 = z.c1 = z.l0 = z.l1 = 0.f; z.shifted = false; }
__device__ __forceinline__ void softmax_half(float* S, uint32_t* P, float* O, SoftmaxState& z, bool first, uint32_t tag) {
  const float lo0 = z.l0, lo1 = z.l1;
  float lim = 1.2676506002282294e30f;
  const float low = first ? 8.673617379884035e-19f : 0.f;
  if (z.shifted) {
#pragma unroll
    for (int j = 0; j < 32; j++) S[j] += (j & 2) ? z.c1 : z.c0;
  }
#pragma unroll 1
  while (true) {
    bb_fence(tag);
#pragma unroll
    for (int j = 0; j < 8; j++) {
      const float p0 = ex2(S[4 * j]), p1 = ex2(S[4 * j + 1]), p2 = ex2(S[4 * j + 2]), p3 = ex2(S[4 * j + 3]);
      z.l0 += p0; z.l1 += p2; z.l0 += p1; z.l1 += p3;
      P[2 * j] = pack2(p0, p1); P[2 * j + 1] = pack2(p2, p3);
    }
    if (!__any_sync(0xffffffffu, !(z.l0 < lim && z.l1 < lim && fminf(z.l0, z.l1) >= low) && lim > 0.f)) break;
    float d0 = fmaxf(S[0], S[1]), d1 = fmaxf(S[2], S[3]);
#pragma unroll
    for (int j = 1; j < 8; j++) { d0 = fmaxf(d0, fmaxf(S[4 * j], S[4 * j + 1])); d1 = fmaxf(d1, fmaxf(S[4 * j + 2], S[4 * j + 3])); }
    d0 = fmaxf(d0, __shfl_xor_sync(0xffffffffu, d0, 1)); d1 = fmaxf(d1, __shfl_xor_sync(0xffffffffu, d1, 1));
    d0 = fmaxf(d0, __shfl_xor_sync(0xffffffffu, d0, 2)); d1 = fmaxf(d1, __shfl_xor_sync(0xffffffffu, d1, 2));
    if (!first) { d0 = fmaxf(d0, 0.f); d1 = fmaxf(d1, 0.f); }
    z.shifted = true;
    z.c0 -= d0; z.c1 -= d1;
#pragma unroll
    for (int j = 0; j < 32; j++) S[j] -= (j & 2) ? d1 : d0;
    const float a0 = first ? 1.f : ex2(-d0), a1 = first ? 1.f : ex2(-d1);
    z.l0 = lo0 * a0; z.l1 = lo1 * a1;
    lim = -1.f;
    wg_wait<0>();
    reg_fence<64>(O);
#pragma unroll
    for (int j = 0; j < 16; j++) { O[4 * j] *= a0; O[4 * j + 1] *= a0; O[4 * j + 2] *= a1; O[4 * j + 3] *= a1; }
  }
}

__device__ __forceinline__ void normalise_frags(uint32_t* V, const uint32_t* ln) {
#pragma unroll
  for (int i = 0; i < 16; i++) V[i] = hfma2(V[i], ln[(i & 1) * 2 + 1], ln[(i & 1) * 2]);
}
__device__ __forceinline__ void modulate_frags(uint32_t* A, const uint32_t* V, const uint4* R) {
#pragma unroll
  for (int kk = 0; kk < 4; kk++) {
    const uint4 sa = R[kk >> 1], c1 = R[2 + (kk >> 1)];
#pragma unroll
    for (int j = 0; j < 4; j++) {
      const uint32_t n = V[4 * kk + j];
      A[4 * kk + j] = (kk & 1) ? ((j & 2) ? hfma2(n, c1.w, sa.x) : hfma2(n, c1.z, sa.w)) : ((j & 2) ? hfma2(n, c1.y, sa.z) : hfma2(n, c1.x, sa.y));
    }
  }
}
__device__ __forceinline__ void publish_record(uint4* dst, uint32_t pk, int src, int vec, bool doit) {
  const int r = vec ? 0 : 12;
  const uint32_t x = __shfl_sync(0xffffffffu, pk, src + r), y = __shfl_sync(0xffffffffu, pk, src + ((r + 4) & 12));
  const uint32_t z = __shfl_sync(0xffffffffu, pk, src + ((r + 8) & 12)), w = __shfl_sync(0xffffffffu, pk, src + ((r + 12) & 12));
  if (doit) st_pkt16(dst, ~x, y, z, w);
}
__device__ __forceinline__ void put_record(uint32_t sb, int idx, const uint4& v) {
  sts128(sb + SM_STASH + idx * 16, ~v.x, v.y, v.z, v.w);
  sts128(sb + SM_STASH + 16384 + idx * 16, ~v.x, v.y, v.z, v.w);
}
__device__ __forceinline__ float mod_value(float v, int vec) {
  v = rbf(v);
  return (vec ? rbf(1.f + v) : v) * SM_SCALE;
}

__device__ __forceinline__ void row_rcp(float& l0, float& l1) {
  l0 += __shfl_xor_sync(0xffffffffu, l0, 1); l1 += __shfl_xor_sync(0xffffffffu, l1, 1);
  l0 += __shfl_xor_sync(0xffffffffu, l0, 2); l1 += __shfl_xor_sync(0xffffffffu, l1, 2);
  l0 = rcp_f(l0); l1 = rcp_f(l1);
}
__device__ __forceinline__ void stage_o(const float* O, float r0, float r1, uint32_t stsm_addr) {
#pragma unroll
  for (int kk = 0; kk < 8; kk++) {
    stsm4((stsm_addr + (kk >> 2) * 8192) ^ ((kk & 3) * 32),
          pack2(O[8 * kk + 0] * r0, O[8 * kk + 1] * r0), pack2(O[8 * kk + 2] * r1, O[8 * kk + 3] * r1),
          pack2(O[8 * kk + 4] * r0, O[8 * kk + 5] * r0), pack2(O[8 * kk + 6] * r1, O[8 * kk + 7] * r1));
  }
}

__global__ void __cluster_dims__(2, 1, 1) __launch_bounds__(NTHREADS, 1)
fused_kernel(const Params p, const __grid_constant__ CUtensorMap mH, const __grid_constant__ CUtensorMap mWq,
             const __grid_constant__ CUtensorMap mK, const __grid_constant__ CUtensorMap mV,
             const __grid_constant__ CUtensorMap mO, const __grid_constant__ CUtensorMap mWo,
             const __grid_constant__ CUtensorMap mX, const __grid_constant__ CUtensorMap mOut,
             const __grid_constant__ CUtensorMap mWg, const __grid_constant__ CUtensorMap mWu,
             const __grid_constant__ CUtensorMap mWd, const __grid_constant__ CUtensorMap mWm,
             const __grid_constant__ CUtensorMap mWs, const __grid_constant__ CUtensorMap mWh,
             const __grid_constant__ CUtensorMap mOs) {
  extern __shared__ __align__(1024) uint8_t smem_raw[];
  TH(0);
  const uint32_t sb = smem_u32(smem_raw);
  const int tid = threadIdx.x;
  const int b0 = blockIdx.x;
  const int lane = tid & 31;
  const int role = __shfl_sync(0xffffffffu, tid >> 8, 0);

  if (b0 >= NMAIN) {
    const uint32_t cs = clock();
    const uint32_t tag = ld_relaxed(&g_epoch) + 1;
    const int sp = b0 - NMAIN, vec = 2 + sp;
    const int warp = __shfl_sync(0xffffffffu, tid >> 5, 0);
    float* sc = reinterpret_cast<float*>(smem_raw + SM_STASH);
    float* red = reinterpret_cast<float*>(smem_raw + SM_STASH + 4096);
    const int ridx = (lane >> 3) * 2 * RV + (sp & 1) * RV + 16 * RS + (sp >> 1) * 16 + (warp & 1) * 8 + (lane & 7);
    if (warp < 8) st_pkt16(&g_rec[warp >> 2][0][ridx + (warp & 2) * 16], 0, 0, 0, 0);
#pragma unroll 1
    for (int i = tid; i < 1024; i += NTHREADS) sc[i] = rbf(silu_f(__bfloat162float(p.c[i])));
    if (tid == 0) {
      tma_prefetch_desc(&mWs);
      for (int s = 0; s < NST2; s++) { mbar_init(sb + BAR_FULL2 + 8 * s, 1); mbar_init(sb + BAR_EMPTY2 + 8 * s, 8); }
      fence_async_smem();
      while ((uint32_t)clock() - cs < SPT) {}
    }
    __syncthreads();
    int s = 0; uint32_t ph = 0;
    if (tid == 0) TS(0);
    if (warp == 8) {
      const uint64_t pol = policy_evict_first();
#pragma unroll 1
      for (int n = 0; n < 80; n++) {
        mbar_wait_g(sb + BAR_EMPTY2 + 8 * s, ph ^ 1);
        if (elect_one()) {
          mbar_expect_tx(sb + BAR_FULL2 + 8 * s, 32768);
          if (n < 16) {
            tma_ld_hint(sb + s * ST2, &mWs, (sp & 1) * 1024 + 512 + (n >> 3) * 256 + (sp >> 1) * 128, (n & 7) * 128, sb + BAR_FULL2 + 8 * s, pol);
          } else {
#pragma unroll
            for (int j = 0; j < 4; j++) tma_ld_hint(sb + s * ST2 + j * 8192, &mWm, vec * 1024 + j * 256, (n - 16) * 16, sb + BAR_FULL2 + 8 * s, pol);
          }
        }
        __syncwarp();
        if (++s == NST2) { s = 0; ph ^= 1; }
      }
    } else if (warp < 8) {
      float acc[8];
#pragma unroll
      for (int i = 0; i < 8; i++) acc[i] = 0.f;
      auto stage = [&](uint32_t a0, int da, const float* cp, int dc) {
        mbar_wait_g(sb + BAR_FULL2 + 8 * s, ph);
#pragma unroll
        for (int i = 0; i < 8; i++) {
          const uint4 v = lds128(a0 + s * ST2 + i * da);
          const float c = cp[i * dc];
          acc[0] = fmaf(lo2f(v.x), c, acc[0]); acc[1] = fmaf(hi2f(v.x), c, acc[1]);
          acc[2] = fmaf(lo2f(v.y), c, acc[2]); acc[3] = fmaf(hi2f(v.y), c, acc[3]);
          acc[4] = fmaf(lo2f(v.z), c, acc[4]); acc[5] = fmaf(hi2f(v.z), c, acc[5]);
          acc[6] = fmaf(lo2f(v.w), c, acc[6]); acc[7] = fmaf(hi2f(v.w), c, acc[7]);
        }
        if (__shfl_sync(0xffffffffu, lane, __float_as_uint(acc[7]) & 31) < 32 && lane == 0) mbar_arrive(sb + BAR_EMPTY2 + 8 * s);
        if (++s == NST2) { s = 0; ph ^= 1; }
      };
#pragma unroll 1
      for (int n = 0; n < 16; n++) {
        stage(sb + tid * 16, 4096, sc + (n & 7) * 128 + (tid >> 4), 16);
        if ((n & 7) == 7) {
          float* r2 = red + 2048 + (n & 8) * 256;
#pragma unroll
          for (int i = 0; i < 8; i++) { r2[tid * 8 + i] = acc[i]; acc[i] = 0.f; }
          nb_sync(NB_CONS, 256);
          if (warp < 2) {
            float v0 = 0.f, v1 = 0.f;
#pragma unroll 4
            for (int i = 0; i < 16; i++) { const float2 e = reinterpret_cast<const float2*>(r2)[i * 64 + tid]; v0 += e.x; v1 += e.y; }
            publish_record(&g_rec[tag & 1][0][ridx + (n >> 3) * 32], pack2(mod_value(v0, sp & 1), mod_value(v1, sp & 1)),
                           (lane & 4) * 4 + (lane & 3), sp & 1, true);
          }
          if (tid == 0) TS(1 + (n >> 3));
        }
      }
#pragma unroll 1
      for (int n = 0; n < 64; n++) {
        stage(sb + ((tid >> 5) & 3) * 8192 + (tid >> 7) * 4096 + (tid & 31) * 16, 512, sc + n * 16 + (tid >> 7) * 8, 1);
      }
#pragma unroll
      for (int i = 0; i < 8; i++) red[(tid >> 7) * 1024 + (tid & 127) * 8 + i] = acc[i];
    }
    __syncthreads();
    float dot = 0.f;
#pragma unroll 1
    for (int i = tid; i < 512; i += NTHREADS) {
      uint32_t v = pack2(red[2 * i] + red[1024 + 2 * i], red[2 * i + 1] + red[1024 + 2 * i + 1]);
      st_pkt8(&g_mod[vec * 512 + i], v, tag);
      if (vec == 4) v = hadd2(v, ONE2);
      const uint32_t wr = reinterpret_cast<const uint32_t*>(p.w_r)[i];
      dot = fmaf(lo2f(v), lo2f(wr), fmaf(hi2f(v), hi2f(wr), dot));
    }
#pragma unroll
    for (int o = 16; o; o >>= 1) dot += __shfl_xor_sync(0xffffffffu, dot, o);
    if (lane == 0) sc[warp] = dot;
    __syncthreads();
    if (tid == 0) {
      dot = 0.f;
      for (int w = 0; w < 12; w++) dot += sc[w];
      fence_release_gpu();
      st_pkt8(&g_vdone[(vec - 2) * 16], __float_as_uint(dot), tag);
      TS(11);
#pragma unroll 1
      for (int i = 0; i < 128; i++) {
        const int u = i * 4 + (b0 - NMAIN);
        l2_prefetch(p.wo + (size_t)((4 * ((u >> 4) & 7) + (u >> 7)) * 128 + (u & 15) * 8) * 1024, 16384);
        __nanosleep(PFW);
      }
    }
    return;
  }

  const uint32_t rank = b0 & 1;
  const bool slab = !(b0 & 32), late = b0 & 16;
  const uint32_t c0 = clock();
  if (tid == 352) TS(0);
  const uint32_t slab_addr = sb + SM_WSLAB + (tid >> 5) * 4096 + (lane & 3) * 128 + (lane & 4) * 16 + (((lane >> 3) ^ lane) & 3) * 16;
  auto load_slab = [&]() {
    const bf16* wp = p.w_mod + (size_t)(512 * rank + 2 * (tid & ~31) + 2 * (lane & 3) + ((lane >> 2) & 1)) * 6144 + 32 * (b0 >> 1) + 8 * (lane >> 3);
    const uint64_t pef = policy_evict_first();
#pragma unroll
    for (int i = 0; i < 8; i++)
      asm volatile("cp.async.cg.shared.global.L2::cache_hint [%0], [%1], 16, %2;"
        :: "r"(slab_addr + i * 512), "l"(wp + (size_t)i * 8 * 6144), "l"(pef) : "memory");
  };
  if (tid == 256) {
    mbar_init(sb + BAR_XH, 1); mbar_init(sb + BAR_XH + 8, 1);
    fence_async_smem();
#pragma unroll
    for (int i = 0; i < 2; i++) {
      mbar_expect_tx(sb + BAR_XH + 8 * i, 16384);
      asm volatile("cp.async.bulk.shared::cluster.global.mbarrier::complete_tx::bytes [%0], [%1], 16384, [%2];"
        :: "r"(sb + SM_XROW + i * ST1), "l"(p.x + (size_t)b0 * 16384 + i * 8192), "r"(sb + BAR_XH + 8 * i) : "memory");
    }
  }
  __syncwarp();
  uint32_t cw[8];
#pragma unroll
  for (int i = 0; i < 8; i++) cw[i] = 0;
  if (!role && slab) {
#pragma unroll
    for (int i = 0; i < 8; i++) cw[i] = ld_relaxed(reinterpret_cast<const uint32_t*>(p.c) + 256 * rank + (tid & ~28) + 4 * i);
  }
  uint32_t epoch = 0;
  if (!role) epoch = ld_relaxed(&p.sc->epoch[lane]);
  if (!role && slab && !late) load_slab();
#define TILE_ROLES() \
  mbar_wait(sb + BAR_ROLE, 0); \
  const int b = 2 * __shfl_sync(0xffffffffu, lds32(sb + SM_ROLE), 0) + rank; \
  const int rt = b >> 3;     \
  const int ct = b & 7;

  if (role) {
    asm volatile("setmaxnreg.dec.sync.aligned.u32 24;");
    const int warp = __shfl_sync(0xffffffffu, tid >> 5, 0);
    if (tid == 256) {
      mbar_init(sb + BAR_RED, 1); mbar_init(sb + BAR_WH, 1);
      for (int s = 0; s < 2; s++) mbar_init(sb + BAR_OF + 8 * s, 1);
      mbar_init(sb + BAR_ROLE, 1);
      for (int s = 0; s < 5; s++) { mbar_init(sb + BAR_FULL1 + 8 * s, 1); mbar_init(sb + BAR_EMPTY1 + 8 * s, 4); }
      for (int s = 0; s < 2; s++) { mbar_init(sb + BAR_STASH + 8 * s, 1); mbar_init(sb + BAR_X + 8 * s, 1); }
      for (int s = 0; s < 4; s++) mbar_init(sb + BAR_HS + 8 * s, 1);
      mbar_init(sb + BAR_G, 16); mbar_init(sb + BAR_T1, 1); mbar_init(sb + BAR_HF, 1);
      mbar_init(sb + BAR_SFREE, 4); mbar_init(sb + BAR_TFREE, 8);
      mbar_init(sb + BAR_FFN, 4); mbar_init(sb + BAR_FFN + 8, 2);
      mbar_init(sb + BAR_CAND, 1); mbar_init(sb + BAR_VEC, 32); for (int s = 0; s < 3; s++) mbar_init(sb + BAR_TAB + 8 * s, 32);
      mbar_expect_tx(sb + BAR_RED, 1024);
      mbar_expect_tx(sb + BAR_ROLE, 4);
      asm volatile("fence.mbarrier_init.release.cluster;" ::: "memory");
    }
    __syncwarp();
    asm volatile("barrier.cluster.arrive.relaxed.aligned;" ::: "memory");
    const int ridx = ((lane >> 1) & 3) * 2 * RV + (b0 >> 6) * RV + ((b0 >> 1) & 31) * RS + 2 * rank + (lane & 1) + (lane >> 3) * 4;
    if (warp == 11 && slab && lane < 2 * RS) { st_pkt16(&g_rec[0][0][ridx], 0, 0, 0, 0); st_pkt16(&g_rec[1][0][ridx], 0, 0, 0, 0); }
    if (tid == 256) {
      tma_prefetch_desc(&mWq); tma_prefetch_desc(&mX); tma_prefetch_desc(&mH); tma_prefetch_desc(&mK); tma_prefetch_desc(&mV); tma_prefetch_desc(&mOs);
    }
    uint32_t pairid = 0;
    if (tid == 320 && rank == 0) {
      uint32_t t;
      asm("mov.u32 %0, %%smid;" : "=r"(t));
      t >>= 1;
      uint32_t grp = ((0x73216540u >> (4 * ((t < 32 ? t : t < 60 ? 1 + (t - 32) % 7 : t < 62 ? t - 54 : 0) & 7))) & 7) - 1, slot;
      int it = 0;
      do {
        grp = (grp + 1) & 7;
        asm volatile("atom.relaxed.gpu.global.add.u32 %0, [%1], 1;" : "=r"(slot) : "l"(&p.sc->ticket[grp * 32]) : "memory");
        spin_guard(it);
      } while (slot >= 8);
      pairid = slot * 8 + grp;
    }
    __syncwarp();
    asm volatile("barrier.cluster.wait.aligned;" ::: "memory");
    if (tid == 320 && rank == 0) {
#pragma unroll
      for (int r = 0; r < 2; r++)
        asm volatile("st.async.weak.shared::cluster.mbarrier::complete_tx::bytes.b32 [%0], %1, [%2];"
          :: "r"(mapa(sb + SM_ROLE, r)), "r"(pairid), "r"(mapa(sb + BAR_ROLE, r)) : "memory");
    }
    __syncwarp();
    const uint32_t tag = ld_relaxed(&g_epoch) + 1;
    if (warp == 8) {
      TILE_ROLES();
      const int kvrow = (ct >> 1) * 2048 + 1536, arow = rt * 128 + rank * 64;
      const uint64_t pef = policy_evict_first();
#pragma unroll 1
      for (int pair = 0; pair < 2; pair++) {
        const int wblk = (4 * ct + 2 * pair) * 2;
        if (pair) { mbar_wait_g(sb + BAR_HF, 0); fence_async_global(); }
#pragma unroll 1
        for (int n = 0; n < 16; n++) {
          const uint32_t s = n & 3, st = sb + SM_RING + s * ST1, fb = sb + BAR_FULL1 + 8 * s;
          if (n == 2 && pair == 0) mbar_wait_g(sb + BAR_G, 0);
          mbar_wait_g(fb + (BAR_EMPTY1 - BAR_FULL1), ((n >> 2) & 1) ^ 1);
          if (elect_one()) {
            mbar_expect_tx(fb, 49152);
            if (pair) tma_ld_mc_hint(st + rank * 8192, &mH, n * 64, arow, fb, pef); else
            tma_ld_mc(st + rank * 8192, pair ? &mH : &mX, n * 64, arow, fb);
            tma_ld3_hint(st + 16384, &mWq, n * 64, wblk, fb, pef);
          }
          __syncwarp();
        }
#pragma unroll 1
        for (int n = 0; n < 16; n++) {
          const uint32_t s = n & 3, st = sb + SM_RING + s * ST1 + rank * 8192, fb = sb + BAR_FULL1 + 8 * s;
          const int h0 = n == 0 ? 0 : n == 15 ? 14 : n + 1, h1 = n == 0 ? 1 : n == 15 ? 15 : n - 1;
          mbar_wait_g(fb + (BAR_EMPTY1 - BAR_FULL1), ((n >> 2) & 1) ^ 1);
          if (elect_one()) {
            mbar_expect_tx(fb, 32768);
            tma_ld_mc(st, n == 15 ? &mV : &mK, rank * 64, kvrow + (h0 & 7) * 64, fb);
            tma_ld_mc(st + 16384, n == 0 ? &mK : &mV, rank * 64, kvrow + (h1 & 7) * 64, fb);
            if (n == 3 && pair == 1) mbar_arrive(sb + BAR_T1);
          }
          __syncwarp();
        }
      }
      {
        uint32_t s = 0, ph = 1;
#pragma unroll 1
        for (int half = 0; half < 2; half++) {
          mbar_wait_g(sb + BAR_OF + 8 * half, 0);
          fence_async_global();
#pragma unroll 1
          for (int n = 32 * half; n < 32 * half + 32; n++) {
            const uint32_t st = sb + SM_RING + s * ST1, fb = sb + BAR_FULL1 + 8 * s;
            const int k0 = ((n & 14) * 2 + (n >> 4)) * 128 + (n & 1) * 64;
            mbar_wait_g(n == 8 ? sb + BAR_SFREE : fb + (BAR_EMPTY1 - BAR_FULL1), n == 8 ? 0 : ph ^ (s >> 2));
            if (elect_one()) {
              mbar_expect_tx(fb, 32768);
              tma_ld_mc_hint(st + rank * 8192, &mO, k0, arow, fb, pef);
              tma_ld3_hint(st + 16384, &mWo, k0, 2 * ct, fb, pef);
            }
            __syncwarp();
            if (++s == 5 || n == 3) { s = 0; ph ^= 1; }
          }
        }
        if (b < NFFN) {
#pragma unroll 1
          for (s = 0; s < 2; s++) {
            mbar_wait_g(sb + BAR_EMPTY1 + 8 * s, 0);
            if (elect_one()) {
              mbar_expect_tx(sb + BAR_FFN + 8, 32768);
              tma_ld3_hint(sb + SM_RING + s * ST1, &mWd, b * 32, s * 8, sb + BAR_FFN + 8, pef);
            }
            __syncwarp();
          }
        }
      }
    } else if (warp <= 10) {
      const int w = warp - 9;
      if (slab && late && w == 0 && lane == 0) {
        tma_prefetch_desc(&mWh);
        mbar_expect_tx(sb + BAR_WH, 32768);
        while ((uint32_t)clock() - c0 < WL) {}
        const uint64_t pef = policy_evict_first();
#pragma unroll
        for (int i = 0; i < 2; i++) tma_ld_hint(sb + SM_WSLAB + i * 16384, &mWh, 32 * (b0 >> 1), 512 * rank + 256 * i, sb + BAR_WH, pef);
      }
      __syncwarp();
      TILE_ROLES();
      const uint32_t st = sb + SM_STASH + w * 16384;
#pragma unroll 1
      for (int j = 0; j < 2; j++) {
        nb_sync(NB_OST + w, 160);
        if (elect_one()) {
          fence_async_smem();
          tma_st(&mH, (2 * ct + j) * 64, rt * 128 + w * 64, st + 4096);
          bulk_commit();
          bulk_wait_read();
          mbar_arrive(sb + BAR_HS + 16 * w + 8 * j);
          if (j) {
            bulk_wait_all();
            fence_async_global();
            fence_release_gpu();
            red_add_relaxed(&g_hflag[rt * 32], 1);
          }
        }
        __syncwarp();
      }
#pragma unroll 1
      for (int r = 0; r < 4; r++) {
        nb_sync(NB_OST + w, 160);
        if (elect_one()) {
          fence_async_smem();
          const int hcol = (4 * ct + r) * 128;
#pragma unroll 1
          for (int i = 0; i < 8; i++) {
            tma_st(&mOs, hcol + (i & 4) * 16, rt * 128 + w * 64 + (i & 3) * 16, st + i * 2048);
            __nanosleep(r == 3 ? OP3 : OP0);
          }
          bulk_commit();
          bulk_wait_read();
          if (r < 2) {
            mbar_arrive(sb + BAR_STASH + 8 * w);
          } else if (r == 2) {
            mbar_expect_tx(sb + BAR_X + 8 * w, 16384);
            tma_ld_hint(st, &mX, ct * 128, rt * 128 + w * 64, sb + BAR_X + 8 * w, policy_evict_first());
            tma_ld_hint(st + 8192, &mX, ct * 128 + 64, rt * 128 + w * 64, sb + BAR_X + 8 * w, policy_evict_first());
          } else {
            mbar_arrive_cl(mapa(sb + BAR_SFREE, 0)); mbar_arrive_cl(mapa(sb + BAR_SFREE, 1));
          }
          bulk_wait_all();
          fence_async_global();
          fence_release_gpu();
          red_add_relaxed(&g_oflag[(rt * 4 + r) * 32], 1);
        }
        __syncwarp();
      }
      nb_sync(NB_OST + w, 160);
      int skip = -1;
      mbar_wait_g(sb + BAR_CAND, 0);
      const bool has_cand = (lds32(sb + SM_CAND) >> 6) == w;
      if (has_cand) {
        nb_sync(NB_WIN + w, 160);
        skip = (int)lds32(sb + SM_WROW + 4 * w) - (rt * 128 + w * 64);
      }
      if ((unsigned)skip >= 64u) {
        if (elect_one()) {
          fence_async_smem();
          tma_st(&mOut, ct * 128, rt * 128 + w * 64, sb + SM_OUT + w * 16384);
          tma_st(&mOut, ct * 128 + 64, rt * 128 + w * 64, sb + SM_OUT + w * 16384 + 8192);
          bulk_commit();
          bulk_wait_read();
        }
        __syncwarp();
      } else {
        uint4* dst = reinterpret_cast<uint4*>(p.out + (size_t)(rt * 128 + w * 64 + (lane >> 4)) * 1024 + ct * 128) + (lane & 15);
#pragma unroll 2
        for (int r = lane >> 4; r < 64; r += 2) {
          const uint4 v = lds128(sb + SM_OUT + w * 16384 + ((lane >> 3) & 1) * 8192 + r * 128 + (((lane ^ r) & 7) * 16));
          if (r != skip) *dst = v;
          dst += 256;
        }
      }
      if (!has_cand) nb_sync(NB_WIN + w, 160);
    } else {
      if (slab) {
        mbar_wait_g(sb + BAR_RED, 0);
        float v = 0.f;
#pragma unroll
        for (int w = 0; w < 8; w++) v += lds_f32(sb + SM_RED + w * 128 + lane * 4);
        v += __shfl_xor_sync(0xffffffffu, v, 16);
        v = mod_value(v, b0 >> 6);
        publish_record(&g_rec[tag & 1][0][ridx], pack2(v, __shfl_down_sync(0xffffffffu, v, 1)), 2 * (lane & 1), b0 >> 6, lane < 8);
        if (lane == 0) TS(1);
      }
      mbar_wait_g(sb + BAR_G, 0);
#pragma unroll 1
      for (int i = 1; i < 4; i++) {
        const uint4* mp = &g_rec[tag & 1][(b0 >> 1) & (NREP - 1)][i == 1 ? (8 + (lane >> 2)) * RS + (lane & 3) : 16 * RS - 64 + 32 * i + lane];
        uint4 v0, v1; int it = 0;
        while (true) {
          v0 = ld_pkt16(mp); v1 = ld_pkt16(mp + RV);
          if (v0.x != 0 && v1.x != 0) break;
          spin_guard(it); __nanosleep(PLD);
        }
        put_record(sb, 32 * i + lane, v0);
        put_record(sb, 128 + 32 * i + lane, v1);
        mbar_arrive(sb + BAR_TAB - 8 + 8 * i);
        if (lane == 0) {
          TS(3 + i + (i > 2));
          if (i == 1) l2_prefetch(((b0 & 64) ? p.vc : p.kc) + (size_t)(((b0 >> 4) & 3) * 2048 + 1536) * 128 + (b0 & 15) * 4096, 8192);
        }
        __syncwarp();
      }
      TILE_ROLES();
      if (lane == 0) {
        int it = 0;
        do { __nanosleep(500); spin_guard(it); } while (ld_relaxed(&g_hflag[rt * 32]) != tag * 16u);
        fence_acquire_gpu();
        mbar_arrive(sb + BAR_HF);
        if (b < NFFN) for (int i = 0; i < 8; i++) { __nanosleep(800); l2_prefetch(p.wd + (size_t)(b * 32 + i * 4) * 1024, 8192); }
      }
      __syncwarp();
      {
        uint2 v; int it = 0;
        do { __nanosleep(1000); v = ld_pkt8(&g_vdone[(lane & 3) * 16]); spin_guard(it); }
        while (!(v.y == tag));
        __syncwarp();
        fence_acquire_gpu();
        if (lane == 1 || lane == 2) sts32(sb + SM_SCAL + (2 - lane) * 4, v.x);
      }
#pragma unroll 1
      for (int i = 0; i < 2; i++) {
        const int q = i * 32 + lane, pi = ct * 64 + q;
        const uint32_t vga = g_mod[2 * 512 + pi].x, vsb = g_mod[3 * 512 + pi].x, vcb = g_mod[4 * 512 + pi].x, vgb = g_mod[5 * 512 + pi].x;
        const uint32_t wr = reinterpret_cast<const uint32_t*>(p.w_r)[pi];
        const uint32_t c1 = hadd2(vcb, ONE2);
        const float al = lo2f(c1) * lo2f(wr), ah = hi2f(c1) * hi2f(wr);
        const uint32_t o8 = (q & 3) * 8 + ((q >> 2) & 1) * 4;
        sts32(sb + SM_GA + (q >> 3) * 32 + o8, vga);
        sts128(sb + SM_REC + q * 16, c1, vsb, vgb, 0);
        const uint32_t ahi = pack2(al, ah), alo = pack2(al - lo2f(ahi), ah - hi2f(ahi));
        const uint32_t ba = sb + SM_B1 + (q >> 3) * 128 + o8;
        sts32(ba, ONE2); sts32(ba + 32, ahi); sts32(ba + 64, alo); sts32(ba + 96, 0);
      }
      if (lane == 0) TS(28);
      if (lane == 0) {
        tma_prefetch_desc(&mWo); tma_prefetch_desc(&mO); tma_prefetch_desc(&mOut); tma_prefetch_desc(&mWd); tma_prefetch_desc(&mWg); tma_prefetch_desc(&mWu);
#pragma unroll 1
        for (int r = 0; r < 4; r++) {
          int it = 0;
          do { __nanosleep(200); spin_guard(it); } while (ld_relaxed(&g_oflag[(rt * 4 + r) * 32]) != tag * 16u);
          if (r & 1) { fence_acquire_gpu(); mbar_arrive(sb + BAR_OF + 8 * (r >> 1)); }
          if (r == 1 && b < NFFN) {
            const uint64_t pef = policy_evict_first();
            mbar_wait_g(sb + BAR_T1, 0);
#pragma unroll 1
            for (int i = 0; i < 4; i++) {
              mbar_expect_tx(sb + BAR_FFN, 16384);
              tma_ld_hint(sb + SM_RING + i * ST1 + 32768, &mWg, b * 32, i * 256, sb + BAR_FFN, pef);
              __nanosleep(GATED);
            }
          }
        }
      }
      __syncwarp();
      if (b < NFFN) {
        mbar_wait_g(sb + BAR_TFREE, 0);
        const uint64_t pef = policy_evict_first();
#pragma unroll 1
        for (int i = 0; i < 5; i++) {
          if (i > 0 && lane == 0) {
            mbar_expect_tx(sb + BAR_FFN, 16384);
            tma_ld_hint(sb + SM_RING + (i - 1) * ST1 + 32768, &mWu, b * 32, (i - 1) * 256, sb + BAR_FFN, pef);
          }
          if (i < 4) {
#pragma unroll 1
            for (int j = 0; j < 8; j++) {
              asm volatile("prefetch.global.L2 [%0];" :: "l"(p.wu + (size_t)(i * 256 + j * 32 + lane) * 3584 + b * 32) : "memory");
              __nanosleep(UPD);
            }
            __nanosleep(500);
          }
        }
      }
      if (lane == 0) TS(29);
#pragma unroll 1
      for (int i = lane; i < 128; i += 32) st_pkt16(&g_stats[b * 128 + i], 0, 0, 0, 0);
      st_pkt16(&g_cand[b * 32 + lane], 0, 0, 0, 0);
      if (lane < 8) st_pkt16(&g_entry[(ct * 16 + rt) * 8 + lane], 0, 0, 0, 0);
#pragma unroll 1
      for (int i = lane; i < (b < NFFN ? 512 : 0); i += 32) st_pkt16(&g_ypart[((i >> 2) * NFFN + b) * 4 + (i & 3)], 0, 0, 0, 0);
      mbar_arrive(sb + BAR_VEC);
      uint4* const cp = &g_cand[b * 32 + lane];
      uint4* const ep = &g_entry[(ct * 16 + rt) * 8];
      nb_sync(NB_AMAX, 288);
      TV(0);
      const uint2 e = lds64(sb + SM_AMAX + (lane & 7) * 8);
      const int tmax = __reduce_max_sync(0xffffffffu, (int)e.x);
      const uint32_t row = ~tmax & 127;
      const int wl = row >> 4;
      const uint32_t xa = sb + SM_X2 + (row >> 6) * 16384 + (lane >> 4) * 8192 + (row & 63) * 128 + (lane & 3) * 4
                        + ((((lane >> 1) & 6) ^ (row & 7)) * 16);
      const uint32_t v0 = lds32(xa), v1 = lds32(xa ^ 16);
      if (lane == wl) st_pkt16(ep, (tmax | 127) - rt, rt * 128 + row, e.y, tag);
      st_pkt16(cp, v0, v1, tag, 0);
      if (lane == 0) { sts32(sb + SM_CAND, row); mbar_arrive(sb + BAR_CAND); }
      TV(1);
      if (lane == 0) TS(15);
    }
  } else {
    const int warp = tid >> 5;
    const int wg = warp >> 2, wq = warp & 3;
    const int g = lane >> 2, t = lane & 3;
    uint32_t tag;
    uint32_t ln[4];
    float acc[128];
    uint32_t bf[16];
    auto gemv = [&]() {
          if (late) mbar_wait(sb + BAR_WH, 0); else
          asm volatile("cp.async.wait_all;" ::: "memory");
          float d0[4] = {0.f, 0.f, 0.f, 0.f}, d1[4] = {0.f, 0.f, 0.f, 0.f};
#pragma unroll
          for (int i = 0; i < 8; i++) {
            const uint4 wv = lds128(slab_addr + i * 512);
            const uint32_t a[4] = {wv.x, wv.y, wv.z, wv.w};
            mma16816((i & 1) ? d1 : d0, a, bf[2 * i], bf[2 * i + 1]);
          }
#pragma unroll
          for (int i = 0; i < 4; i++) { d0[i] += d1[i]; d0[i] += __shfl_xor_sync(0xffffffffu, d0[i], 6); }
          const uint32_t dst = mapa(sb + SM_MISC, t & 1) - SM_MISC;
          if (!(lane & 6)) st_async_f32x4(dst + SM_RED + warp * 128 + rank * 64 + g * 8, d0, dst + BAR_RED);
          TH(4);
    };
    {
      asm volatile("barrier.cluster.arrive.relaxed.aligned;" ::: "memory");
      if (lane == 0) st_pkt16(&g_lnst[8 * b0 + warp], 0, 0, 0, 0);
      TH(1);
      asm volatile("setmaxnreg.inc.sync.aligned.u32 240;");
      TH(2);
#pragma unroll
      for (int i = 0; i < 8; i++) {
        const float sv = silu_f((g & 4) ? hi2f(cw[i]) : lo2f(cw[i]));
        const uint32_t sp = (g & 1) ? pack2(0.f, sv) : pack2(sv, 0.f);
        bf[2 * i] = (g & 2) ? 0 : sp; bf[2 * i + 1] = (g & 2) ? sp : 0;
      }
      asm volatile("barrier.cluster.wait.aligned;" ::: "memory");
#pragma unroll
      for (int i = 0; i < 128; i++) acc[i] = 0.f;
      reg_fence<128>(acc);
      tag = __shfl_sync(0xffffffffu, epoch, 0) + 1;
      TH(3);
      if (slab && !late) gemv();
      {
        {
          mbar_wait(sb + BAR_XH + 8 * wg, 0);
          TH(5);
          float ds[4] = {0.f, 0.f, 0.f, 0.f}, dq[4][4];
#pragma unroll
          for (int i = 0; i < 4; i++) { dq[i][0] = dq[i][1] = dq[i][2] = dq[i][3] = 0.f; }
#pragma unroll
          for (int i = 0; i < 8; i++) {
            uint32_t a[4];
            ldsm4(sb + SM_XROW + wg * ST1 + wq * 4096 + ((lane >> 3) & 1) * 2048 + i * 256 + (lane >> 4) * 128 + (lane & 7) * 16, a);
            mma16816(ds, a, ONE2, ONE2);
            mma16816(dq[2 * (i & 1)], a, a[0], a[2]); mma16816(dq[1 + 2 * (i & 1)], a, a[1], a[3]);
          }
          float q0 = (g & 1) ? dq[0][1] + dq[2][1] : dq[0][0] + dq[2][0], q1 = (g & 1) ? dq[1][3] + dq[3][3] : dq[1][2] + dq[3][2];
          float s0 = ds[0], s1 = ds[2];
#pragma unroll
          for (int o = 0; o < 3; o++) {
            const int m = o == 0 ? 4 : o == 1 ? 9 : 18;
            q0 += __shfl_xor_sync(0xffffffffu, q0, m); q1 += __shfl_xor_sync(0xffffffffu, q1, m);
            s0 += __shfl_xor_sync(0xffffffffu, s0, m); s1 += __shfl_xor_sync(0xffffffffu, s1, m);
          }
          s0 *= 1.f / 1024.f; s1 *= 1.f / 1024.f;
          const uint32_t rh = pack2(rcp_f(rbf(sqrt_f(rbf(rbf(fmaxf(fmaf(-s0, s0, q0 * (1.f / 1024.f)), 0.f)) + 1e-5f)))),
                                    rcp_f(rbf(sqrt_f(rbf(rbf(fmaxf(fmaf(-s1, s1, q1 * (1.f / 1024.f)), 0.f)) + 1e-5f)))));
          if (lane == 0) st_pkt16(&g_lnst[8 * b0 + warp], pack2(-rbf(s0) * lo2f(rh), -rbf(s1) * hi2f(rh)), rh, 0, tag);
          TH(6);
          if (tid == 0) TS(2);
        }
      }
    }
    if (slab && late) gemv();
    TILE_ROLES();
    const uint32_t xa0 = sb + SM_RING + (warp * 16 + (lane & 15)) * 128 + (((lane >> 4) ^ (lane & 7)) * 16);
    uint32_t V[16];
    {
      const uint4* mp = &g_rec[tag & 1][(b0 >> 1) & (NREP - 1)][RV * wg + (lane >> 2) * RS + (lane & 3)];
      const uint4* lp = &g_lnst[(8 * rt + warp) * 8 + (g >> 1)];
      mbar_wait(sb + BAR_FULL1, 0);
#pragma unroll
      for (int kk = 0; kk < 4; kk++) ldsm4(xa0 ^ (kk * 32), V + 4 * kk);
      uint4 v0 = make_uint4(1, 0, 0, 0), l0, l1;
      int it = 0;
      while ((uint32_t)clock() - c0 < HD) {}
      do { if (wq == 0) v0 = ld_pkt16(mp);
           l0 = ld_pkt16(lp); l1 = ld_pkt16(lp + 4); spin_guard(it); }
        while (!(__all_sync(0xffffffffu, v0.x != 0 && l0.w == tag && l1.w == tag)));
      TH(7);
      if (wq == 0) put_record(sb, 128 * wg + lane, v0);
      const uint32_t sel = (g & 1) ? 0x3232 : 0x1010;
      ln[0] = __byte_perm(l0.x, 0, sel); ln[1] = __byte_perm(l0.y, 0, sel);
      ln[2] = __byte_perm(l1.x, 0, sel); ln[3] = __byte_perm(l1.y, 0, sel);
      __syncwarp();
      if (lane < 2) mbar_arrive_cl(mapa(sb + BAR_G, lane));
      normalise_frags(V, ln);
      nb_sync(NB_CONS, 256);
      if (tid == 0) TS(3);
      TH(13);
    }

    const uint32_t rel = mapa(sb + SM_MISC, lane & 1) - SM_MISC;
    const uint32_t stsm_addr = sb + SM_STASH + wg * 16384 + (wq * 16 + (lane & 15)) * 128 + (((lane >> 4) ^ (lane & 7)) * 16);

    uint32_t ph = 0;
    uint32_t X[32];
    {
      const uint32_t tab0 = sb + SM_STASH + wg * 16384 + t * 16;
      const uint64_t db0 = mk_desc(sb + SM_RING + 16384, 8192);
      uint32_t A[2][16];
      uint32_t xa[4];
#pragma unroll
      for (int kk = 0; kk < 4; kk++) xa[kk] = xa0 ^ (kk * 32);
      uint32_t tab = tab0;
      reg_fence<4>(xa);
      asm volatile("{\n.reg .pred p;\nsetp.eq.u32 p, %4, 0;\n@p ld.shared.v4.u32 {%0,%1,%2,%3}, [%5];\n}"
        : "+r"(ln[2]), "+r"(ln[0]), "+r"(ln[3]), "+r"(ln[1]) : "r"(tag), "r"(sb));
      int hs = 2 * ct;
      uint4 R[4];
#pragma unroll
      for (int kk = 0; kk < 4; kk++) R[kk] = lds128(tab + (kk >> 1) * 2048 + (kk & 1) * 64);
#pragma unroll 1
      for (int k4 = 0; k4 < 4; k4++) {
#pragma unroll
        for (int s = 0; s < 4; s++) {
          uint32_t* a = A[s & 1];
          const int sn = (s + 1) & 3;
          const uint32_t pn = (k4 + (s == 3)) & 1;
          modulate_frags(a, V, R);
          if (hs == (s & 2)) {
            if (s & 1) mbar_wait(sb + BAR_HS + 16 * wg, 0);
#pragma unroll
            for (int kk = 0; kk < 4; kk++) stsm4((stsm_addr + 4096) ^ (kk * 32), a[4 * kk], a[4 * kk + 1], a[4 * kk + 2], a[4 * kk + 3]);
            nb_arrive(NB_OST + wg, 160);
          }
          if (s == 0 && k4 == 0) TH(8);
          TQ(3 * s);
          if (s == 0 && k4 == 0 && tid == 0) { TS(6); TSC(61); }
          wg_fence();
#pragma unroll
          for (int kk = 0; kk < 4; kk++) wgmma_rs256<1>(acc, a + 4 * kk, db0 + s * (ST1 >> 4) + kk * 128);
          wg_commit();
          if (s == 3) TQ(12);
          if (s == 3 && k4 < 3) mbar_wait(sb + BAR_TAB + 8 * k4, 0);
          if (s == 3) TQ(13);
#pragma unroll
          for (int kk = 0; kk < 4; kk++) R[kk] = lds128(tab + (s + 1) * 128 + (kk >> 1) * 2048 + (kk & 1) * 64);
          wg_wait<1>();
          if (k4 == 0) TH(9 + s);
          TQ(3 * s + 1);
          reg_fence<16>(A[(s & 1) ^ 1]);
          if ((tid & 127) < 2 && (s | k4)) mbar_arrive_cl(rel + BAR_EMPTY1 + 8 * ((s + 3) & 3));
          if (s < 3 || k4 < 3) {
            mbar_wait(sb + BAR_FULL1 + 8 * sn, pn);
            TQ(3 * s + 2);
#pragma unroll
            for (int kk = 0; kk < 4; kk++) ldsm4(xa[kk] + sn * ST1, V + 4 * kk);
            normalise_frags(V, ln);
          }
        }
        tab += 512; hs -= 4;
      }
      mbar_wait(sb + BAR_HS + 16 * wg + 8, 0);
      wg_wait<0>();
      reg_fence<128>(acc);
    }
#pragma unroll 1
    for (int pair = 0; pair < 2; pair++) {
      uint32_t Q[32];
      TR(0);
      {
        if ((tid & 127) < 2) mbar_arrive_cl(rel + BAR_EMPTY1 + 8 * 3);
        if (pair == 1) mbar_wait(sb + BAR_STASH + 8 * wg, 1);
#pragma unroll
        for (int i = 0; i < 32; i++) Q[i] = pack2(acc[2 * i], acc[2 * i + 1]);
        const uint32_t qs = sb + SM_STASH + wg * 16384 + wq * 2048 + lane * 16;
#pragma unroll
        for (int i = 0; i < 8; i++)
          sts128(qs + (i & 3) * 512 + (i >> 2) * 8192, pack2(acc[64 + 8 * i], acc[65 + 8 * i]), pack2(acc[66 + 8 * i], acc[67 + 8 * i]),
                 pack2(acc[68 + 8 * i], acc[69 + 8 * i]), pack2(acc[70 + 8 * i], acc[71 + 8 * i]));
      }
      if (tid == 0) TS(8 + pair * 2);
      TR(1);
      float O[64], SL[32], SH[32];
      uint32_t PL[16], PH[16];
      SoftmaxState z;
      const uint64_t d0 = mk_desc(sb + SM_RING, 8192);
      {
        mbar_wait(sb + BAR_FULL1, ph);
        wg_fence();
        issue_qk(SL, Q, d0);
        wg_commit();
        issue_qk(SH, Q, d0 + 1024);
        wg_commit();
#pragma unroll
        for (int i = 0; i < 64; i++) O[i] = 0.f;
        reg_fence<64>(O);
        wg_wait<1>();
        reg_fence<32>(SL);
        softmax_start(z);
        softmax_half(SL, PL, O, z, true, tag);
        wg_wait<0>();
        reg_fence<32>(SH);
        if ((tid & 127) < 2) mbar_arrive_cl(rel + BAR_EMPTY1);
      }
      float lp0 = 0.f, lp1 = 0.f;
      uint32_t dB = (uint32_t)d0 + 1 * (ST1 >> 4), dA = (uint32_t)d0 + 2 * (ST1 >> 4);
      const uint32_t dBx = dB ^ ((uint32_t)d0 + 3 * (ST1 >> 4)), dAx = dA ^ (uint32_t)d0;
      uint32_t so = 0;
      bool ready = false;
#pragma unroll 1
      for (int i = 0; i < 7; i++) {
        TA(0);
        TR(2 + i);
        if (!ready) mbar_wait(sb + BAR_FULL1 + 8 + so, ph);
        TA(1);
        TA(2);
        wg_fence();
        issue_qk(SL, Q, (d0 & 0xffffffff00000000ull) | dB);
        if (i == 4) {
          __syncwarp();
          stage_o(O, lp0, lp1, stsm_addr);
        }
        wg_fence();
        issue_pv(O, PL, ((d0 & 0xffffffff00000000ull) | dB) + 1024, i != 4);
        wg_commit();
        if (i == 4) {
          nb_arrive(NB_OST + wg, 160);
        }
        TA(3);
        ph ^= i & 1;
        ready = mbar_test(sb + BAR_FULL1 + 16 - so, ph);
        softmax_half(SH, PH, O, z, false, tag);
        TA(4);
        wg_wait<0>();
        TA(5);
        reg_fence<32>(SL); reg_fence<16>(PL);
        if ((tid & 127) < 2) mbar_arrive_cl(rel + BAR_EMPTY1 + 8 + so);
        if (!ready) mbar_wait(sb + BAR_FULL1 + 16 - so, ph);
        TA(6);
        wg_fence();
        issue_qk(SH, Q, (d0 & 0xffffffff00000000ull) | dA);
        wg_commit();
        issue_pv(O, PH, ((d0 & 0xffffffff00000000ull) | dA) + 1024, 1);
        wg_commit();
        if (i == 2) {
          wg_wait<1>();
          reg_fence<32>(Q);
          const uint32_t qs = sb + SM_STASH + wg * 16384 + wq * 2048 + lane * 16;
#pragma unroll
          for (int j = 0; j < 8; j++) { const uint4 v = lds128(qs + (j & 3) * 512 + (j >> 2) * 8192); Q[4 * j] = v.x; Q[4 * j + 1] = v.y; Q[4 * j + 2] = v.z; Q[4 * j + 3] = v.w; }
        }
        TA(10);
        if (i == 3) { lp0 = z.l0; lp1 = z.l1; row_rcp(lp0, lp1); softmax_start(z); }
        TA(7);
        so ^= 16; dB ^= dBx; dA ^= dAx;
        ready = mbar_test(sb + BAR_FULL1 + 8 + so, ph);
        softmax_half(SL, PL, O, z, i == 3, tag);
        TA(8);
        wg_wait<0>();
        TA(9);
        reg_fence<32>(SH); reg_fence<16>(PH); reg_fence<64>(O); reg_fence<32>(Q);
        if ((tid & 127) < 2) mbar_arrive_cl(rel + BAR_EMPTY1 + so);
      }
      TAFLUSH();
      TR(9);
      {
        if (!ready) mbar_wait(sb + BAR_FULL1 + 8 * 3, ph);
        ph ^= 1;
        const uint64_t dv = d0 + 3 * (ST1 >> 4);
        wg_fence();
        issue_pv(O, PL, dv, 1);
        wg_commit();
        bb_fence(tag);
        softmax_half(SH, PH, O, z, false, tag);
        wg_fence();
        issue_pv(O, PH, dv + 1024, 1);
        wg_commit();
        TR(10);
        row_rcp(z.l0, z.l1);
        mbar_wait(sb + (pair ? BAR_X : BAR_STASH) + 8 * wg, 0);
#pragma unroll
        for (int kk = 0; kk < 8; kk++) ldsm4((stsm_addr + (kk >> 2) * 8192) ^ ((kk & 3) * 32), X + 4 * kk);
        reg_fence<32>(X);
        __syncwarp();
        wg_wait<0>();
        reg_fence<64>(O);
        TR(11);
        if ((tid & 127) < 2) mbar_arrive_cl(rel + BAR_EMPTY1 + 8 * 3);
        stage_o(O, z.l0, z.l1, stsm_addr);
        nb_arrive(NB_OST + wg, 160);
      }
      TR(12);
      if (tid == 0) { TS(9 + pair * 2); TSC(62); }
      if (pair == 1) break;
      {
        mbar_wait(sb + BAR_FULL1, ph);
        const uint64_t da = mk_desc(sb + SM_RING + wg * 8192, 16), db = mk_desc(sb + SM_RING + 16384, 8192);
        wg_fence();
        wgmma_ss256_z<1>(acc, da, db);
#pragma unroll
        for (int kk = 1; kk < 4; kk++) wgmma_ss256<1>(acc, da + kk * 2, db + kk * 128, 1);
        wg_commit();
      }
#pragma unroll 1
      for (int kt = 1; kt < 16; kt++) {
        const uint32_t s = kt & 3;
        if (s == 0) ph ^= 1;
        mbar_wait(sb + BAR_FULL1 + 8 * s, ph);
        const uint32_t st = sb + SM_RING + s * ST1;
        const uint64_t da = mk_desc(st + wg * 8192, 16), db = mk_desc(st + 16384, 8192);
        wg_fence();
#pragma unroll
        for (int kk = 0; kk < 4; kk++) wgmma_ss256<1>(acc, da + kk * 2, db + kk * 128, 1);
        wg_commit();
        wg_wait<1>();
        if ((tid & 127) < 2) mbar_arrive_cl(rel + BAR_EMPTY1 + 8 * ((s + 3) & 3));
      }
      ph ^= 1;
      wg_wait<0>();
      reg_fence<128>(acc);
      TR(13);
    }

    uint4 WG[16], WU[16];
    const int fp = 64 * warp + 8 * g + t;
    uint32_t fsb0, fsb1, fcb0, fcb1, fgb0, fgb1;
    const uint32_t gu_base = sb + SM_RING + (warp >> 1) * ST1 + 32768 + (warp & 1) * 8192;
    const uint32_t gu_addr = gu_base + t * 128 + (g & 1) * 64 + ((g >> 1) ^ t) * 16;
    {
      const uint64_t da0 = mk_desc(sb + SM_RING + __shfl_sync(0xffffffffu, wg, 0) * 8192, 16), db0 = mk_desc(sb + SM_RING + 16384, 8192);
#pragma unroll
      for (int n = 0; n < 4 + 5 * PEEL; n++) {
        const int s = n < 4 ? n : (n - 4) % 5;
        mbar_wait(sb + BAR_FULL1 + 8 * s, n < 4 ? 0 : ((n - 4) / 5 + (s < 4)) & 1);
        if (n < 4) TSX(40 + wg * 6 + n);
        const uint64_t da = da0 + s * (ST1 >> 4), db = db0 + s * (ST1 >> 4);
        wg_fence();
        if (n == 0) wgmma_ss128_z<1>(acc, da, db); else wgmma_ss128<1>(acc, da, db, 1);
#pragma unroll
        for (int kk = 1; kk < 4; kk++) wgmma_ss128<1>(acc, da + kk * 2, db + kk * 128, 1);
        wg_commit();
        if (n == 0 && b < NFFN) mbar_wait(sb + BAR_FFN, 0);
        {
          constexpr int NT = 4 + 5 * PEEL, F0 = NT > 16 ? NT - 16 : 0;
#pragma unroll
          for (int i = 0; i < 16; i++) if (F0 + i * (NT - F0) / 16 == n) WG[i] = lds128(gu_addr + i * 512);
        }
        if (n > 0) {
          wg_wait<1>();
          if ((tid & 127) < 2) mbar_arrive_cl(rel + BAR_EMPTY1 + 8 * (n == 4 ? 3 : s ? s - 1 : 4));
        }
      }
      TSX(44 + wg * 6);
      {
        uint32_t dep = 0;
#pragma unroll
        for (int i = 0; i < 16; i++) dep ^= WG[i].x;
        if (__shfl_sync(0xffffffffu, tag, dep & 31) == tag && lane == 2) mbar_arrive(sb + BAR_TFREE);
      }
      {
        uint32_t so = 0, sp = 4 * 8, par = PEEL + 1;
#pragma unroll 1
        for (int n = 4 + 5 * PEEL; n < 64; n++) {
          mbar_wait(sb + BAR_FULL1 + so, (par + (so >> 5)) & 1);
          const uint64_t da = da0 + so * (ST1 >> 7), db = db0 + so * (ST1 >> 7);
          wg_fence();
#pragma unroll
          for (int kk = 0; kk < 4; kk++) wgmma_ss128<1>(acc, da + kk * 2, db + kk * 128, 1);
          wg_commit();
          wg_wait<1>();
          if ((tid & 127) < 2) mbar_arrive_cl(rel + BAR_EMPTY1 + sp);
          sp = so; so += 8;
          if (so == 40) { so = 0; par++; }
        }
      }
    }
    mbar_wait(sb + BAR_VEC, 0);
    const int lrow = warp * 16 + g;
    uint2 ga[8], b1[8];
#pragma unroll
    for (int kk = 0; kk < 8; kk++) { ga[kk] = lds64(sb + SM_GA + kk * 32 + t * 8); b1[kk] = lds64(sb + SM_B1 + min(g, 3) * 32 + t * 8 + kk * 128); }
    uint4* const stp = &g_stats[b * 128 + lrow + 8 * t];
    bb_fence(tag);
    wg_wait<0>();
    reg_fence<64>(acc);
    if (tid == 0) { TS(12); TSC(63); }

    TT(0);
    {
      float d1[4] = {0.f, 0.f, 0.f, 0.f}, d2[4] = {0.f, 0.f, 0.f, 0.f}, d3[4] = {0.f, 0.f, 0.f, 0.f};
      float d4[4] = {0.f, 0.f, 0.f, 0.f}, d5[4] = {0.f, 0.f, 0.f, 0.f};
#pragma unroll
      for (int kk = 0; kk < 8; kk++) {
        uint32_t* x = X + 4 * kk;
        x[0] = hfma2(ga[kk].x, pack2(acc[8 * kk + 0], acc[8 * kk + 1]), x[0]);
        x[1] = hfma2(ga[kk].x, pack2(acc[8 * kk + 2], acc[8 * kk + 3]), x[1]);
        x[2] = hfma2(ga[kk].y, pack2(acc[8 * kk + 4], acc[8 * kk + 5]), x[2]);
        x[3] = hfma2(ga[kk].y, pack2(acc[8 * kk + 6], acc[8 * kk + 7]), x[3]);
        mma16816(d1, x, b1[kk].x, b1[kk].y);
        mma1688(d2, x[0], x[1], x[0]); mma1688(d3, x[0], x[1], x[1]);
        mma1688(d4, x[2], x[3], x[2]); mma1688(d5, x[2], x[3], x[3]);
      }
      const int qb = lane & 28;
      const float q0 = __shfl_sync(0xffffffffu, (g & 1) ? d2[1] + d4[1] : d2[0] + d4[0], qb | (g >> 1));
      const float q1 = __shfl_sync(0xffffffffu, (g & 1) ? d3[3] + d5[3] : d3[2] + d5[2], qb | (g >> 1));
      const float e0 = __shfl_xor_sync(0xffffffffu, t ? d1[0] : d1[3], 1);
      const float e1 = __shfl_sync(0xffffffffu, d1[2], qb);
      if (t < 2) st_pkt16(stp, __float_as_uint(t ? e1 : d1[0]), __float_as_uint(t ? q1 : q0),
                          __float_as_uint((t ? d1[2] : d1[1]) + e0), tag);
    }
    {
      const uint2* mp = &g_mod[3 * 512 + fp];
      fsb0 = ld_pkt8(mp).x; fsb1 = ld_pkt8(mp + 4).x; fcb0 = ld_pkt8(mp + 512).x; fcb1 = ld_pkt8(mp + 516).x;
      fgb0 = ld_pkt8(mp + 1024).x; fgb1 = ld_pkt8(mp + 1028).x;
    }
    TSY(13);
    TT(1);
    float mb, rd, den, br;
    {
      const uint4* sp = &g_stats[(rt * 8 + 4 * (t & 1)) * 128 + lrow + 4 * (t & 2)];
      mbar_wait(sb + BAR_EMPTY1 + 8 * 3, 0);
#pragma unroll
      for (int kk = 0; kk < 8; kk++) stsm4((stsm_addr - SM_STASH + SM_X2 + (kk >> 2) * 8192) ^ ((kk & 3) * 32), X[4 * kk], X[4 * kk + 1], X[4 * kk + 2], X[4 * kk + 3]);
      if (b < NFFN) mbar_wait(sb + BAR_FFN, 1);
#pragma unroll
      for (int i = 0; i < WU1; i++) WU[i] = lds128(gu_addr + i * 512);
      bb_fence(tag);
      TT(2);
      uint4 v0, v1, v2, v3;
      int it = 0;
      do { v0 = ld_pkt16(sp); v1 = ld_pkt16(sp + 128); v2 = ld_pkt16(sp + 256); v3 = ld_pkt16(sp + 384); spin_guard(it); }
        while (!(__all_sync(0xffffffffu, v0.w == tag && v1.w == tag && v2.w == tag && v3.w == tag)));
      TT(3);
      float sm = (__uint_as_float(v0.x) + __uint_as_float(v1.x)) + (__uint_as_float(v2.x) + __uint_as_float(v3.x));
      float sq = (__uint_as_float(v0.y) + __uint_as_float(v1.y)) + (__uint_as_float(v2.y) + __uint_as_float(v3.y));
      float dt = (__uint_as_float(v0.z) + __uint_as_float(v1.z)) + (__uint_as_float(v2.z) + __uint_as_float(v3.z));
      sm += __shfl_xor_sync(0xffffffffu, sm, 1); sq += __shfl_xor_sync(0xffffffffu, sq, 1); dt += __shfl_xor_sync(0xffffffffu, dt, 1);
      const uint2 scal = lds64(sb + SM_SCAL);
      const float mu = sm * (1.f / 1024.f);
      mb = rbf(mu);
      den = rbf(sqrt_f(rbf(rbf(fmaxf(fmaf(-mu, mu, sq * (1.f / 1024.f)), 0.f)) + 1e-5f)));
      rd = rcp_f(den);
      br = fmaf(fmaf(-mb, __uint_as_float(scal.x), dt), rd, __uint_as_float(scal.y));
    }
    TSY(14);
    TT(4);
    {
      const int rb = __float_as_int(br);
      const int key = ((rb ^ ((rb >> 31) & 0x7fffffff)) | 127) - (lrow + 4 * (t & 2));
      if (key == __reduce_max_sync(0xffffffffu, key)) sts64(sb + SM_AMAX + warp * 8, (uint32_t)key, pack2(mb, den));
      __syncwarp();
      nb_arrive(NB_AMAX, 288);
    }
    TT(5);
    const uint4* ep = &g_entry[(warp * 16 + (lane & 15)) * 8];
    const uint32_t slot = sb + SM_STASH + wg * 8192 + (tid & 127) * 16;
    cp_async16(slot, ep);
    {
      const float rh = rbf(rd);
      const uint32_t u = pack2(-mb * rh, rh);
      const int qb = lane & 28;
      const uint32_t u0 = __shfl_sync(0xffffffffu, u, qb), u1 = __shfl_sync(0xffffffffu, u, qb | 2);
      const uint32_t m0 = __byte_perm(u0, 0, 0x1010), h0 = __byte_perm(u0, 0, 0x3232);
      const uint32_t m1 = __byte_perm(u1, 0, 0x1010), h1 = __byte_perm(u1, 0, 0x3232);
#pragma unroll
      for (int j = 0; j < 16; j++) {
        const uint4 rec = lds128(sb + SM_REC + (4 * j + t) * 16);
        X[2 * j] = hfma2(rec.z, hfma2(hfma2(X[2 * j], h0, m0), rec.x, rec.y), X[2 * j]);
        X[2 * j + 1] = hfma2(rec.z, hfma2(hfma2(X[2 * j + 1], h1, m1), rec.x, rec.y), X[2 * j + 1]);
      }
#pragma unroll
      for (int kk = 0; kk < 8; kk++) stsm4((stsm_addr - SM_STASH + SM_OUT + (kk >> 2) * 8192) ^ ((kk & 3) * 32), X[4 * kk], X[4 * kk + 1], X[4 * kk + 2], X[4 * kk + 3]);
    }
    cp_async_wait();
    uint4 ent = lds128(slot);
    TSY(16);
    TT(6);
    int wrow;
    uint32_t xs0, xs1, hs0, hs1;
    uint32_t WD[64];
    const uint32_t wd_addr = sb + SM_RING + wg * ST1 + wq * 8192 + ((lane & 7) + ((lane >> 4) << 3)) * 128 + ((((lane >> 3) & 1) ^ (lane & 7)) * 16);
    {
      int gmax;
      auto leader = [&]() {
        gmax = __reduce_max_sync(0xffffffffu, ent.w == tag ? (int)ent.x : (int)0x8000000f);
        return ~gmax & 15;
      };
      int wt = leader(), it = 0;
      TT(7);
      nb_arrive(NB_OST + wg, 160);
      TT(8);
      cp_async16(slot + 2048, &g_cand[(wt * 8 + warp) * 32 + lane]);
      if (ent.w != tag) cp_async16(slot, ep);
#pragma unroll
      for (int i = WU1; i < 16; i++) WU[i] = lds128(gu_addr + i * 512);
      if (b < NFFN) mbar_wait(sb + BAR_FFN + 8, 0);
#pragma unroll
      for (int mt = 0; mt < 8; mt++)
#pragma unroll
        for (int s = 0; s < 2; s++) ldsm4t((wd_addr + (mt >> 2) * 4096 + s * 2048) ^ ((mt & 3) * 32), WD + (mt * 2 + s) * 4);
      cp_async_wait();
      uint4 v = lds128(slot + 2048);
      ent = lds128(slot);
      TT(9);
      while (true) {
        const int have = wt;
        wt = leader();
        if (__all_sync(0xffffffffu, ent.w == tag && have == wt && v.z == tag)) break;
        v = ld_pkt16(&g_cand[(wt * 8 + warp) * 32 + lane]);
        if (ent.w != tag) ent = ld_pkt16(ep);
        spin_guard(it);
      }
      TT(10);
      ent.x = gmax ^ ((gmax >> 31) & 0x7fffffff);
      wrow = __shfl_sync(0xffffffffu, ent.y, wt); ent.z = __shfl_sync(0xffffffffu, ent.z, wt);
      xs0 = v.x; xs1 = v.y;
      const uint32_t mm = __byte_perm(ent.z, 0, 0x1010);
      const float rs = rcp_f(hi2f(ent.z));
      const uint32_t e0 = hsub2(xs0, mm), e1 = hsub2(xs1, mm);
      hs0 = hfma2(pack2(lo2f(e0) * rs, hi2f(e0) * rs), hadd2(fcb0, ONE2), fsb0);
      hs1 = hfma2(pack2(lo2f(e1) * rs, hi2f(e1) * rs), hadd2(fcb1, ONE2), fsb1);
    }
    if ((tid & 127) == 0) sts32(sb + SM_WROW + 4 * wg, wrow);
    nb_arrive(NB_WIN + wg, 160);
    TSY(17);
    TT(11);
    if (b < NFFN) {
      float da[4][4];
#pragma unroll
      for (int i = 0; i < 4; i++) { da[i][0] = da[i][1] = da[i][2] = da[i][3] = 0.f; }
      const uint32_t selv = ((g & 1) ? 0x1044 : 0x4410) + ((g & 4) ? ((g & 1) ? 0x2200 : 0x0022) : 0);
      const uint32_t sel0 = (g & 2) ? 0x4444 : selv, sel1 = (g & 2) ? selv : 0x4444;
#pragma unroll
      for (int s = 0; s < 16; s++) {
        const uint32_t v = __shfl_sync(0xffffffffu, (s & 1) ? hs1 : hs0, 4 * (s >> 1) + t);
        const uint32_t b0 = __byte_perm(v, 0, sel0), b1 = __byte_perm(v, 0, sel1);
        const uint32_t a0[4] = {WG[s].x, WG[s].y, WG[s].z, WG[s].w};
        const uint32_t a1[4] = {WU[s].x, WU[s].y, WU[s].z, WU[s].w};
        mma16816(da[(s & 1) * 2], a0, b0, b1);
        mma16816(da[(s & 1) * 2 + 1], a1, b0, b1);
      }
      {
        float v[4];
#pragma unroll
        for (int i = 0; i < 4; i++) {
          const float vg = da[0][i] + da[2][i], vu = da[1][i] + da[3][i];
          v[i] = ((g & 1) ? vu : vg) + __shfl_xor_sync(0xffffffffu, (g & 1) ? vg : vu, 6);
        }
        if ((t >> 1) == (g & 1))
          sts128(gu_base + (g & 1) * 128 + (g >> 1) * 32 + (t & 1) * 16, __float_as_uint(v[0]), __float_as_uint(v[1]), __float_as_uint(v[2]), __float_as_uint(v[3]));
      }
      TT(12);
      nb_sync(NB_CONS, 256);
      float gp[8], up[8];
#pragma unroll
      for (int w = 0; w < 8; w++) {
        const uint32_t a = sb + SM_RING + (w >> 1) * ST1 + 32768 + (w & 1) * 8192 + lane * 4;
        gp[w] = lds_f32(a); up[w] = lds_f32(a + 128);
      }
      const float gsum = ((gp[0] + gp[1]) + (gp[2] + gp[3])) + ((gp[4] + gp[5]) + (gp[6] + gp[7]));
      const float usum = ((up[0] + up[1]) + (up[2] + up[3])) + ((up[4] + up[5]) + (up[6] + up[7]));
      const float act = rbf(silu_f(rbf(gsum))) * rbf(usum);
      TT(13);
      const uint32_t ap = pack2(act, __shfl_down_sync(0xffffffffu, act, 1));
      const uint32_t b00 = __shfl_sync(0xffffffffu, ap, 2 * t), b01 = __shfl_sync(0xffffffffu, ap, 2 * t + 8);
      const uint32_t b10 = __shfl_sync(0xffffffffu, ap, 2 * t + 16), b11 = __shfl_sync(0xffffffffu, ap, 2 * t + 24);
      float y[8][4];
#pragma unroll
      for (int mt = 0; mt < 8; mt++) {
        y[mt][0] = y[mt][1] = y[mt][2] = y[mt][3] = 0.f;
        mma16816(y[mt], WD + (mt * 2) * 4, b00, b01);
        mma16816(y[mt], WD + (mt * 2 + 1) * 4, b10, b11);
      }
#pragma unroll
      for (int e = 0; e < 2; e++) {
        const float v0 = t == 0 ? y[e][0] : t == 1 ? y[2 + e][0] : t == 2 ? y[4 + e][0] : y[6 + e][0];
        const float v1 = t == 0 ? y[e][2] : t == 1 ? y[2 + e][2] : t == 2 ? y[4 + e][2] : y[6 + e][2];
        st_pkt8(reinterpret_cast<uint2*>(g_ypart) + (((tag & 1) * 64 + 8 * warp + 2 * t + e) * NFFN + b) * 8 + g, ~__float_as_uint(v0), __float_as_uint(v1));
      }
    }
    TSY(18);
    TT(14);
    if (b & 1) return;
    {
      const int pw = warp - (warp > (b >> 4));
      if (warp != (b >> 4)) {
        const uint4* yp = &g_ypart[((tag & 1) * 64 + (b >> 1)) * NFFN * 4 + pw * 64 + lane];
        uint4 v0, v1;
        int it = 0;
        { const uint32_t c1 = clock(); while ((uint32_t)clock() - c1 < (b < NFFN ? YD : YD + 1500)) {} }
        do { v0 = ld_pkt8x2(yp); v1 = ld_pkt8x2(yp + 32); spin_guard(it); }
        while (!(__all_sync(0xffffffffu, v0.x != 0 && v0.z != 0 && v1.x != 0 && v1.z != 0)));
        float y[4] = {__uint_as_float(~v0.x) + __uint_as_float(~v1.x), __uint_as_float(~v0.z) + __uint_as_float(~v1.z),
                      __uint_as_float(v0.y) + __uint_as_float(v1.y), __uint_as_float(v0.w) + __uint_as_float(v1.w)};
#pragma unroll
        for (int o = 4; o <= 16; o <<= 1)
#pragma unroll
          for (int i = 0; i < 4; i++) y[i] += __shfl_xor_sync(0xffffffffu, y[i], o);
        if (lane < 4) sts128(sb + SM_B1 + pw * 64 + lane * 16, __float_as_uint(y[0]), __float_as_uint(y[1]), __float_as_uint(y[2]), __float_as_uint(y[3]));
      }
    }
    TT(15);
    if (warp != (b >> 4)) {
      nb_arrive(NB_CONS, 256);
    } else {
      nb_sync(NB_CONS, 256);
      float y[4] = {0.f, 0.f, 0.f, 0.f};
      if (lane < 28) { const uint4 e = lds128(sb + SM_B1 + lane * 16); y[0] = __uint_as_float(e.x); y[1] = __uint_as_float(e.y); y[2] = __uint_as_float(e.z); y[3] = __uint_as_float(e.w); }
#pragma unroll
      for (int o = 4; o <= 16; o <<= 1)
#pragma unroll
        for (int i = 0; i < 4; i++) y[i] += __shfl_xor_sync(0xffffffffu, y[i], o);
      const float ya = y[0], yb = y[1], yc = y[2], yd = y[3];
      if (g == ((b >> 1) & 7)) {
        const float rs = rbf(__uint_as_float(ent.x));
        const float sg = sigmoid_f(rs);
        const uint32_t sg2 = pack2(sg, sg);
        const uint32_t o0 = hadd2(xs0, hmul2(fgb0, hadd2(hs0, hmul2(pack2(ya, yb), sg2))));
        const uint32_t o1 = hadd2(xs1, hmul2(fgb1, hadd2(hs1, hmul2(pack2(yc, yd), sg2))));
        uint32_t* op = reinterpret_cast<uint32_t*>(p.out + (size_t)wrow * 1024) + fp;
        op[0] = o0; op[4] = o1;
      }
      if (b == 0) {
        if (lane < 8) st_relaxed(&p.sc->ticket[lane * 32], 0);
        st_relaxed(&p.sc->epoch[lane], tag);
      }
      if (lane == 0) TS(19);
    }
  }
}

typedef CUresult (*EncodeFn)(CUtensorMap*, CUtensorMapDataType, cuuint32_t, void*, const cuuint64_t*, const cuuint64_t*,
                             const cuuint32_t*, const cuuint32_t*, CUtensorMapInterleave, CUtensorMapSwizzle,
                             CUtensorMapL2promotion, CUtensorMapFloatOOBfill);

CUtensorMap make_map(EncodeFn enc, const void* ptr, uint64_t rows, uint64_t cols, uint32_t box_rows, uint32_t box_cols, CUtensorMapSwizzle sw) {
  CUtensorMap m;
  cuuint64_t dims[2] = {cols, rows};
  cuuint64_t strides[1] = {cols * 2};
  cuuint32_t box[2] = {box_cols, box_rows};
  cuuint32_t es[2] = {1, 1};
  enc(&m, CU_TENSOR_MAP_DATA_TYPE_BFLOAT16, 2, const_cast<void*>(ptr), dims, strides, box, es, CU_TENSOR_MAP_INTERLEAVE_NONE, sw,
      CU_TENSOR_MAP_L2_PROMOTION_L2_128B, CU_TENSOR_MAP_FLOAT_OOB_FILL_NONE);
  return m;
}

CUtensorMap make_map3(EncodeFn enc, const void* ptr, uint64_t rows, uint64_t cols, uint32_t box_rows, uint32_t box_blks) {
  CUtensorMap m;
  cuuint64_t dims[3] = {64, rows, cols / 64};
  cuuint64_t strides[2] = {cols * 2, 128};
  cuuint32_t box[3] = {64, box_rows, box_blks};
  cuuint32_t es[3] = {1, 1, 1};
  enc(&m, CU_TENSOR_MAP_DATA_TYPE_BFLOAT16, 3, const_cast<void*>(ptr), dims, strides, box, es, CU_TENSOR_MAP_INTERLEAVE_NONE,
      CU_TENSOR_MAP_SWIZZLE_128B, CU_TENSOR_MAP_L2_PROMOTION_L2_128B, CU_TENSOR_MAP_FLOAT_OOB_FILL_NONE);
  return m;
}

}

extern "C" void kernel_launch(void* const* d_in, const int* in_sizes, int n_in, void* d_out, int out_size) {
  (void)in_sizes; (void)n_in; (void)out_size;
  Params p;
  p.x = (const bf16*)d_in[0]; p.kc = (const bf16*)d_in[1]; p.vc = (const bf16*)d_in[2];
  p.wq = (const bf16*)d_in[3]; p.wo = (const bf16*)d_in[4]; p.w_r = (const bf16*)d_in[6];
  p.wg = (const bf16*)d_in[7]; p.wu = (const bf16*)d_in[8]; p.wd = (const bf16*)d_in[9];
  p.c = (const bf16*)d_in[10]; p.w_mod = (const bf16*)d_in[11]; p.out = (bf16*)d_out;

  void* fn = nullptr;
  cudaDriverEntryPointQueryResult st;
  cudaGetDriverEntryPoint("cuTensorMapEncodeTiled", &fn, cudaEnableDefault, &st);
  EncodeFn enc = (EncodeFn)fn;
  void* scp = nullptr;
  cudaGetSymbolAddress(&scp, g_scratch);
  p.sc = (Scratch*)scp;
  void *hp = p.sc->h, *op = p.sc->o;
  const CUtensorMapSwizzle S128 = CU_TENSOR_MAP_SWIZZLE_128B;
  CUtensorMap mH = make_map(enc, hp, 2048, 1024, 64, 64, S128);
  CUtensorMap mWq = make_map3(enc, p.wq, 1024, 4096, 64, 4);
  CUtensorMap mK = make_map(enc, p.kc, 8192, 128, 64, 64, S128);
  CUtensorMap mV = make_map(enc, p.vc, 8192, 128, 64, 64, S128);
  CUtensorMap mO = make_map(enc, op, 2048, 4096, 64, 64, S128);
  CUtensorMap mOs = make_map(enc, op, 2048, 4096, 16, 64, S128);
  CUtensorMap mWo = make_map3(enc, p.wo, 4096, 1024, 64, 2);
  CUtensorMap mX = make_map(enc, p.x, 2048, 1024, 64, 64, S128);
  CUtensorMap mOut = make_map(enc, p.out, 2048, 1024, 64, 64, S128);
  CUtensorMap mWg = make_map(enc, p.wg, 1024, 3584, 256, 32, CU_TENSOR_MAP_SWIZZLE_64B);
  CUtensorMap mWu = make_map(enc, p.wu, 1024, 3584, 256, 32, CU_TENSOR_MAP_SWIZZLE_64B);
  CUtensorMap mWd = make_map3(enc, p.wd, 3584, 1024, 32, 8);
  CUtensorMap mWm = make_map(enc, p.w_mod, 1024, 6144, 16, 256, CU_TENSOR_MAP_SWIZZLE_NONE);
  CUtensorMap mWh = make_map(enc, p.w_mod, 1024, 6144, 256, 32, CU_TENSOR_MAP_SWIZZLE_64B);
  CUtensorMap mWs = make_map(enc, p.w_mod, 1024, 6144, 128, 128, CU_TENSOR_MAP_SWIZZLE_NONE);
  cudaFuncSetAttribute(fused_kernel, cudaFuncAttributeMaxDynamicSharedMemorySize, SMEM_BYTES);
  fused_kernel<<<NCTA, NTHREADS, SMEM_BYTES>>>(p, mH, mWq, mK, mV, mO, mWo, mX, mOut, mWg, mWu, mWd, mWm, mWs, mWh, mOs);
}
```

```cpp
#include <cuda_runtime.h>
#include <cuda_bf16.h>
#include <cuda.h>
#include <stdint.h>
#include <stddef.h>

#define UPD 200
#define GATED 700
#define PFW 100
#define OP0 200
#define OP3 90
#define PLD 200
#define WL 3500
#define SPT 5000
#define W2T 5200
#define HD 6000
#define YD 300
#define PEEL 1
#define WU1 12

namespace {

typedef __nv_bfloat16 bf16;

constexpr int NTHREADS = 384;
constexpr int NMAIN = 128;
constexpr int NCTA = 132;
constexpr int RS = 8, RV = 16 * RS + 64;
constexpr int NREP = 4;
constexpr int NFFN = 112;

constexpr uint32_t SM_RING = 0;
constexpr uint32_t ST1 = 49152;
constexpr uint32_t ST2 = 32768;
constexpr int NST2 = 6;
constexpr uint32_t SM_STASH = 196608;
constexpr uint32_t SM_MISC = 229376;
constexpr uint32_t BAR_FULL1 = SM_MISC + 0;
constexpr uint32_t BAR_EMPTY1 = SM_MISC + 40;
constexpr uint32_t BAR_FULL2 = SM_MISC + 0;
constexpr uint32_t BAR_EMPTY2 = SM_MISC + 48;
constexpr uint32_t BAR_STASH = SM_MISC + 160;
constexpr uint32_t BAR_SFREE = SM_MISC + 176;
constexpr uint32_t BAR_TFREE = SM_MISC + 184;
constexpr uint32_t BAR_FFN = SM_MISC + 192;
constexpr uint32_t BAR_VEC = SM_MISC + 208;
constexpr uint32_t BAR_RED = SM_MISC + 216;
constexpr uint32_t BAR_XH = SM_MISC + 968;
constexpr uint32_t BAR_HS = SM_MISC + 80;
constexpr uint32_t BAR_G = SM_MISC + 112;
constexpr uint32_t BAR_T1 = SM_MISC + 120;
constexpr uint32_t BAR_HF = SM_MISC + 128;
constexpr uint32_t BAR_X = SM_MISC + 136;
constexpr uint32_t BAR_OF = SM_MISC + 224;
constexpr uint32_t BAR_ROLE = SM_MISC + 240;
constexpr uint32_t SM_ROLE = SM_MISC + 248;
constexpr uint32_t SM_GA = SM_MISC + 256;
constexpr uint32_t SM_SCAL = SM_MISC + 512;
constexpr uint32_t SM_WROW = SM_MISC + 520;
constexpr uint32_t SM_AMAX = SM_MISC + 528;
constexpr uint32_t SM_X2 = 2 * ST1, SM_OUT = 3 * ST1;
constexpr uint32_t SM_REC = SM_MISC + 1024;
constexpr uint32_t BAR_TAB = SM_MISC + 1000;
constexpr uint32_t BAR_CAND = SM_MISC + 880;
constexpr uint32_t SM_CAND = SM_MISC + 888;
constexpr uint32_t BAR_WH = SM_MISC + 960;
constexpr uint32_t SM_WSLAB = 3 * 49152 + 16384;
constexpr uint32_t SM_XROW = 2 * 49152;
constexpr uint32_t SM_RED = SM_MISC + 2048;
constexpr uint32_t SM_B1 = SM_MISC + 2048;
constexpr uint32_t SMEM_BYTES = 232448;

constexpr int NB_CONS = 1, NB_WIN = 2  , NB_OST = 4  , NB_AMAX = 6;

struct __align__(1024) Scratch {
  uint32_t epoch[32];
  uint32_t hflag[16 * 32];
  uint32_t oflag[64 * 32];
  uint2 vdone[4 * 16];
  uint32_t pad[96 + 512];
  uint32_t ticket[8 * 32];
  uint2 mod[3072];
  uint4 rec[2][NREP][2 * RV];
  uint4 lnst[1024];
  uint4 entry[8 * 16 * 8];
  uint4 cand[16 * 8 * 32];
  uint4 stats[16 * 8 * 128];
  uint4 ypart[2 * 64 * NFFN * 4];
  unsigned long long ts[NCTA * 64];
  uint16_t h[2048 * 1024];
  uint16_t o[2048 * 4096];
};
__device__ Scratch g_scratch;
#define g_epoch (p.sc->epoch[0])
#define g_hflag (p.sc->hflag)
#define g_oflag (p.sc->oflag)
#define g_mod (p.sc->mod)
#define g_entry (p.sc->entry)
#define g_cand (p.sc->cand)
#define g_stats (p.sc->stats)
#define g_ypart (p.sc->ypart)
#define g_vdone (p.sc->vdone)
#define g_lnst (p.sc->lnst)
#define g_rec (p.sc->rec)
#define g_ts (p.sc->ts)
#define g_h (p.sc->h)

struct Params {
  const bf16* w_mod; const bf16* c; Scratch* sc; const bf16* x; const bf16* w_r; bf16* out;
  const bf16* wq; const bf16* wo; const bf16* wg; const bf16* wu; const bf16* wd; const bf16* kc; const bf16* vc;
};

__device__ __forceinline__ uint32_t smem_u32(const void* p) { return (uint32_t)__cvta_generic_to_shared(p); }
__device__ __forceinline__ void mbar_init(uint32_t bar, uint32_t cnt) { asm volatile("mbarrier.init.shared::cta.b64 [%0], %1;" :: "r"(bar), "r"(cnt) : "memory"); }
__device__ __forceinline__ void mbar_expect_tx(uint32_t bar, uint32_t bytes) { asm volatile("mbarrier.arrive.expect_tx.shared::cta.b64 _, [%0], %1;" :: "r"(bar), "r"(bytes) : "memory"); }
__device__ __forceinline__ void mbar_arrive(uint32_t bar) { asm volatile("mbarrier.arrive.shared::cta.b64 _, [%0];" :: "r"(bar) : "memory"); }
__device__ __forceinline__ void mbar_arrive_cl(uint32_t cluster_addr) { asm volatile("mbarrier.arrive.shared::cluster.b64 _, [%0];" :: "r"(cluster_addr) : "memory"); }
__device__ __forceinline__ uint32_t mapa(uint32_t addr, uint32_t cta) { uint32_t r; asm("mapa.shared::cluster.u32 %0, %1, %2;" : "=r"(r) : "r"(addr), "r"(cta)); return r; }
__device__ __forceinline__ bool mbar_test(uint32_t bar, uint32_t parity) {
  uint32_t ok;
  asm volatile("{\n.reg .pred p;\nmbarrier.test_wait.parity.shared::cta.b64 p, [%1], %2;\nselp.u32 %0, 1, 0, p;\n}" : "=r"(ok) : "r"(bar), "r"(parity) : "memory");
  return ok;
}
constexpr int SPIN_LIMIT = 300000;
__device__ __forceinline__ void spin_guard(int& it) {
  asm volatile("{\n.reg .pred p;\n.reg .b64 z;\nadd.s32 %0, %0, 1;\nsetp.gt.s32 p, %0, %1;\nmov.b64 z, 0;\n@p st.volatile.global.u32 [z], %0;\n}" : "+r"(it) : "n"(SPIN_LIMIT));
}
__device__ __forceinline__ void mbar_wait_g(uint32_t bar, uint32_t parity) {
  asm volatile("{\n.reg .pred p, q;\n.reg .b32 c;\n.reg .b64 z;\nmov.b32 c, 0;\nmov.b64 z, 0;\nMW_LOOP:\n"
               "mbarrier.try_wait.parity.shared::cta.b64 p, [%0], %1;\nadd.s32 c, c, 1;\nsetp.gt.s32 q, c, %2;\n"
               "@q st.volatile.global.u32 [z], c;\n@!p bra MW_LOOP;\n}" :: "r"(bar), "r"(parity), "n"(SPIN_LIMIT) : "memory");
}
__device__ __forceinline__ void mbar_wait(uint32_t bar, uint32_t parity) {
  asm volatile("{\n.reg .pred p;\nMW_LOOP:\nmbarrier.try_wait.parity.shared::cta.b64 p, [%0], %1;\n@!p bra MW_LOOP;\n}" :: "r"(bar), "r"(parity) : "memory");
}
__device__ __forceinline__ void bb_fence(uint32_t v) {
  asm volatile("{\n.reg .pred p;\n.reg .u32 c;\nsetp.ne.u32 p, %0, 0;\n@p bra.uni BF_DONE;\nBF_LOOP:\nnanosleep.u32 1;\nmov.u32 c, %%clock;\nsetp.eq.u32 p, c, 0;\n@p bra.uni BF_LOOP;\nBF_DONE:\n}" :: "r"(v) : "memory");
}
__device__ __forceinline__ bool elect_one() {
  uint32_t pred;
  asm volatile("{\n.reg .pred P;\nelect.sync _|P, 0xffffffff;\nselp.u32 %0, 1, 0, P;\n}" : "=r"(pred));
  return pred;
}
__device__ __forceinline__ void tma_ld_hint(uint32_t dst, const CUtensorMap* m, int c0, int c1, uint32_t bar, uint64_t pol) {
  asm volatile("cp.async.bulk.tensor.2d.shared::cluster.global.mbarrier::complete_tx::bytes.L2::cache_hint [%0], [%1, {%3, %4}], [%2], %5;"
    :: "r"(dst), "l"(m), "r"(bar), "r"(c0), "r"(c1), "l"(pol) : "memory");
}
__device__ __forceinline__ void tma_ld_mc(uint32_t dst, const CUtensorMap* m, int c0, int c1, uint32_t bar) {
  asm volatile("cp.async.bulk.tensor.2d.shared::cluster.global.mbarrier::complete_tx::bytes.multicast::cluster [%0], [%1, {%3, %4}], [%2], %5;"
    :: "r"(dst), "l"(m), "r"(bar), "r"(c0), "r"(c1), "h"((uint16_t)3) : "memory");
}
__device__ __forceinline__ void tma_ld_mc_hint(uint32_t dst, const CUtensorMap* m, int c0, int c1, uint32_t bar, uint64_t pol) {
  asm volatile("cp.async.bulk.tensor.2d.shared::cluster.global.mbarrier::complete_tx::bytes.multicast::cluster.L2::cache_hint [%0], [%1, {%3, %4}], [%2], %5, %6;"
    :: "r"(dst), "l"(m), "r"(bar), "r"(c0), "r"(c1), "h"((uint16_t)3), "l"(pol) : "memory");
}
__device__ __forceinline__ void tma_ld3_hint(uint32_t dst, const CUtensorMap* m, int row, int blk, uint32_t bar, uint64_t pol) {
  asm volatile("cp.async.bulk.tensor.3d.shared::cluster.global.mbarrier::complete_tx::bytes.L2::cache_hint [%0], [%1, {0, %3, %4}], [%2], %5;"
    :: "r"(dst), "l"(m), "r"(bar), "r"(row), "r"(blk), "l"(pol) : "memory");
}
__device__ __forceinline__ void tma_st(const CUtensorMap* m, int c0, int c1, uint32_t src) {
  asm volatile("cp.async.bulk.tensor.2d.global.shared::cta.bulk_group [%0, {%2, %3}], [%1];" :: "l"(m), "r"(src), "r"(c0), "r"(c1) : "memory");
}
__device__ __forceinline__ void tma_prefetch_desc(const CUtensorMap* m) { asm volatile("prefetch.tensormap [%0];" :: "l"(m) : "memory"); }
__device__ __forceinline__ void l2_prefetch(const void* p, uint32_t bytes) { asm volatile("cp.async.bulk.prefetch.L2.global [%0], %1;" :: "l"(p), "r"(bytes) : "memory"); }
__device__ __forceinline__ void bulk_commit() { asm volatile("cp.async.bulk.commit_group;" ::: "memory"); }
__device__ __forceinline__ void bulk_wait_read() { asm volatile("cp.async.bulk.wait_group.read 0;" ::: "memory"); }
__device__ __forceinline__ void bulk_wait_all() { asm volatile("cp.async.bulk.wait_group 0;" ::: "memory"); }
__device__ __forceinline__ void fence_async_smem() { asm volatile("fence.proxy.async.shared::cta;" ::: "memory"); }
__device__ __forceinline__ void fence_async_global() { asm volatile("fence.proxy.async.global;" ::: "memory"); }
__device__ __forceinline__ void fence_acquire_gpu() { asm volatile("fence.acquire.gpu;" ::: "memory"); }
__device__ __forceinline__ void fence_release_gpu() { asm volatile("fence.release.gpu;" ::: "memory"); }
__device__ __forceinline__ void st_async_f32x4(uint32_t cluster_addr, const float* v, uint32_t cluster_bar) {
  asm volatile("st.async.weak.shared::cluster.mbarrier::complete_tx::bytes.v4.f32 [%0], {%1,%2,%3,%4}, [%5];"
    :: "r"(cluster_addr), "f"(v[0]), "f"(v[1]), "f"(v[2]), "f"(v[3]), "r"(cluster_bar) : "memory");
}
__device__ __forceinline__ void nb_sync(int id, int n) { asm volatile("bar.sync %0, %1;" :: "r"(id), "r"(n) : "memory"); }
__device__ __forceinline__ void nb_arrive(int id, int n) { asm volatile("bar.arrive %0, %1;" :: "r"(id), "r"(n) : "memory"); }
__device__ __forceinline__ void wg_fence() { asm volatile("wgmma.fence.sync.aligned;" ::: "memory"); }
__device__ __forceinline__ void wg_commit() { asm volatile("wgmma.commit_group.sync.aligned;" ::: "memory"); }
template <int N> __device__ __forceinline__ void wg_wait() { asm volatile("wgmma.wait_group.sync.aligned %0;" :: "n"(N) : "memory"); }
template <int N> __device__ __forceinline__ void reg_fence(float* a) {
#pragma unroll
  for (int i = 0; i < N; i++) asm volatile("" : "+f"(a[i]) :: "memory");
}
template <int N> __device__ __forceinline__ void reg_fence(uint32_t* a) {
#pragma unroll
  for (int i = 0; i < N; i++) asm volatile("" : "+r"(a[i]) :: "memory");
}
__device__ __forceinline__ uint64_t mk_desc(uint32_t addr, uint32_t lbo) {
  return (uint64_t)((addr & 0x3FFFF) >> 4) | ((uint64_t)(lbo >> 4) << 16) | ((uint64_t)(1024 >> 4) << 32) | (1ull << 62);
}

__device__ __forceinline__ uint64_t policy_evict_first() { uint64_t pol; asm("createpolicy.fractional.L2::evict_first.b64 %0, 1.0;" : "=l"(pol)); return pol; }
__device__ __forceinline__ uint32_t ld_relaxed(const uint32_t* p) { uint32_t v; asm volatile("ld.relaxed.gpu.global.u32 %0, [%1];" : "=r"(v) : "l"(p) : "memory"); return v; }
__device__ __forceinline__ void st_relaxed(uint32_t* p, uint32_t v) { asm volatile("st.relaxed.gpu.global.u32 [%0], %1;" :: "l"(p), "r"(v) : "memory"); }
__device__ __forceinline__ void red_add_relaxed(uint32_t* p, uint32_t v) { asm volatile("red.relaxed.gpu.global.add.u32 [%0], %1;" :: "l"(p), "r"(v) : "memory"); }
__device__ __forceinline__ uint2 ld_pkt8(const uint2* p) {
  uint2 v; asm volatile("{\n.reg .b64 t;\nld.relaxed.gpu.global.b64 t, [%2];\nmov.b64 {%0,%1}, t;\n}" : "=r"(v.x), "=r"(v.y) : "l"(p) : "memory"); return v;
}
__device__ __forceinline__ uint4 ld_pkt8x2(const uint4* p) {
  uint4 v; asm volatile("{\n.reg .b64 a, b;\nld.relaxed.gpu.global.v2.b64 {a, b}, [%4];\nmov.b64 {%0,%1}, a;\nmov.b64 {%2,%3}, b;\n}"
    : "=r"(v.x), "=r"(v.y), "=r"(v.z), "=r"(v.w) : "l"(p) : "memory"); return v;
}
__device__ __forceinline__ void st_pkt8(uint2* p, uint32_t a, uint32_t b) {
  asm volatile("{\n.reg .b64 t;\nmov.b64 t, {%1,%2};\nst.relaxed.gpu.global.b64 [%0], t;\n}" :: "l"(p), "r"(a), "r"(b) : "memory");
}
__device__ __forceinline__ uint4 ld_pkt16(const uint4* p) {
  uint4 v; asm volatile("{\n.reg .b128 t;\n.reg .b64 a, b;\nld.relaxed.gpu.global.b128 t, [%4];\nmov.b128 {a, b}, t;\nmov.b64 {%0,%1}, a;\nmov.b64 {%2,%3}, b;\n}"
    : "=r"(v.x), "=r"(v.y), "=r"(v.z), "=r"(v.w) : "l"(p) : "memory"); return v;
}
__device__ __forceinline__ void st_pkt16(uint4* p, uint32_t x, uint32_t y, uint32_t z, uint32_t w) {
  asm volatile("{\n.reg .b128 t;\n.reg .b64 a, b;\nmov.b64 a, {%1,%2};\nmov.b64 b, {%3,%4};\nmov.b128 t, {a, b};\nst.relaxed.gpu.global.b128 [%0], t;\n}"
    :: "l"(p), "r"(x), "r"(y), "r"(z), "r"(w) : "memory");
}
__device__ __forceinline__ void cp_async16(uint32_t dst, const void* src) { asm volatile("cp.async.cg.shared.global [%0], [%1], 16;" :: "r"(dst), "l"(src) : "memory"); }
__device__ __forceinline__ void cp_async_wait() { asm volatile("cp.async.wait_all;" ::: "memory"); }
__device__ __forceinline__ uint32_t lds32(uint32_t a) { uint32_t v; asm volatile("ld.shared.u32 %0, [%1];" : "=r"(v) : "r"(a) : "memory"); return v; }
__device__ __forceinline__ float lds_f32(uint32_t a) { float v; asm volatile("ld.shared.f32 %0, [%1];" : "=f"(v) : "r"(a) : "memory"); return v; }
__device__ __forceinline__ uint2 lds64(uint32_t a) { uint2 v; asm volatile("ld.shared.v2.u32 {%0,%1}, [%2];" : "=r"(v.x), "=r"(v.y) : "r"(a) : "memory"); return v; }
__device__ __forceinline__ uint4 lds128(uint32_t a) { uint4 v; asm volatile("ld.shared.v4.u32 {%0,%1,%2,%3}, [%4];" : "=r"(v.x), "=r"(v.y), "=r"(v.z), "=r"(v.w) : "r"(a) : "memory"); return v; }
__device__ __forceinline__ void sts32(uint32_t a, uint32_t v) { asm volatile("st.shared.u32 [%0], %1;" :: "r"(a), "r"(v) : "memory"); }
__device__ __forceinline__ void sts64(uint32_t a, uint32_t x, uint32_t y) { asm volatile("st.shared.v2.u32 [%0], {%1,%2};" :: "r"(a), "r"(x), "r"(y) : "memory"); }
__device__ __forceinline__ void sts128(uint32_t a, uint32_t x, uint32_t y, uint32_t z, uint32_t w) { asm volatile("st.shared.v4.u32 [%0], {%1,%2,%3,%4};" :: "r"(a), "r"(x), "r"(y), "r"(z), "r"(w) : "memory"); }
__device__ __forceinline__ void stsm4(uint32_t a, uint32_t x, uint32_t y, uint32_t z, uint32_t w) {
  asm volatile("stmatrix.sync.aligned.m8n8.x4.shared.b16 [%0], {%1,%2,%3,%4};" :: "r"(a), "r"(x), "r"(y), "r"(z), "r"(w) : "memory");
}
__device__ __forceinline__ void ldsm4(uint32_t a, uint32_t* r) {
  asm volatile("ldmatrix.sync.aligned.m8n8.x4.shared.b16 {%0,%1,%2,%3}, [%4];" : "=r"(r[0]), "=r"(r[1]), "=r"(r[2]), "=r"(r[3]) : "r"(a) : "memory");
}
__device__ __forceinline__ void ldsm4t(uint32_t a, uint32_t* r) {
  asm volatile("ldmatrix.sync.aligned.m8n8.x4.trans.shared.b16 {%0,%1,%2,%3}, [%4];" : "=r"(r[0]), "=r"(r[1]), "=r"(r[2]), "=r"(r[3]) : "r"(a) : "memory");
}
__device__ __forceinline__ void mma16816(float* d, const uint32_t* a, uint32_t b0, uint32_t b1) {
  asm volatile("mma.sync.aligned.m16n8k16.row.col.f32.bf16.bf16.f32 {%0,%1,%2,%3}, {%4,%5,%6,%7}, {%8,%9}, {%0,%1,%2,%3};"
    : "+f"(d[0]), "+f"(d[1]), "+f"(d[2]), "+f"(d[3]) : "r"(a[0]), "r"(a[1]), "r"(a[2]), "r"(a[3]), "r"(b0), "r"(b1));
}
__device__ __forceinline__ void mma1688(float* d, uint32_t a0, uint32_t a1, uint32_t b0) {
  asm volatile("mma.sync.aligned.m16n8k8.row.col.f32.bf16.bf16.f32 {%0,%1,%2,%3}, {%4,%5}, {%6}, {%0,%1,%2,%3};"
    : "+f"(d[0]), "+f"(d[1]), "+f"(d[2]), "+f"(d[3]) : "r"(a0), "r"(a1), "r"(b0));
}
__device__ __forceinline__ uint32_t pack2(float lo, float hi) { uint32_t r; asm("cvt.rn.bf16x2.f32 %0, %1, %2;" : "=r"(r) : "f"(hi), "f"(lo)); return r; }
__device__ __forceinline__ float lo2f(uint32_t v) { return __uint_as_float(v << 16); }
__device__ __forceinline__ float hi2f(uint32_t v) { return __uint_as_float(v & 0xffff0000u); }
__device__ __forceinline__ uint32_t hmul2(uint32_t a, uint32_t b) { uint32_t r; asm("mul.rn.bf16x2 %0, %1, %2;" : "=r"(r) : "r"(a), "r"(b)); return r; }
__device__ __forceinline__ uint32_t hadd2(uint32_t a, uint32_t b) { uint32_t r; asm("add.rn.bf16x2 %0, %1, %2;" : "=r"(r) : "r"(a), "r"(b)); return r; }
__device__ __forceinline__ uint32_t hsub2(uint32_t a, uint32_t b) { uint32_t r; asm("sub.rn.bf16x2 %0, %1, %2;" : "=r"(r) : "r"(a), "r"(b)); return r; }
__device__ __forceinline__ uint32_t hfma2(uint32_t a, uint32_t b, uint32_t c) { uint32_t r; asm("fma.rn.bf16x2 %0, %1, %2, %3;" : "=r"(r) : "r"(a), "r"(b), "r"(c)); return r; }
__device__ __forceinline__ float rbf(float v) { return lo2f(pack2(v, 0.f)); }
__device__ __forceinline__ float ex2(float v) { float r; asm("ex2.approx.ftz.f32 %0, %1;" : "=f"(r) : "f"(v)); return r; }
__device__ __forceinline__ float rcp_f(float v) { float r; asm("rcp.approx.ftz.f32 %0, %1;" : "=f"(r) : "f"(v)); return r; }
__device__ __forceinline__ float sqrt_f(float v) { float r; asm("sqrt.approx.ftz.f32 %0, %1;" : "=f"(r) : "f"(v)); return r; }
__device__ __forceinline__ float sigmoid_f(float v) { return rcp_f(1.f + ex2(-1.4426950408889634f * v)); }
__device__ __forceinline__ float silu_f(float v) { return v * sigmoid_f(v); }
constexpr uint32_t ONE2 = 0x3f803f80u;

#define R8(a,o) "+f"(a[o+0]), "+f"(a[o+1]), "+f"(a[o+2]), "+f"(a[o+3]), "+f"(a[o+4]), "+f"(a[o+5]), "+f"(a[o+6]), "+f"(a[o+7])
#define R64(a,o) R8(a,o), R8(a,o+8), R8(a,o+16), R8(a,o+24), R8(a,o+32), R8(a,o+40), R8(a,o+48), R8(a,o+56)
#define D64 "{%0,%1,%2,%3,%4,%5,%6,%7,%8,%9,%10,%11,%12,%13,%14,%15,%16,%17,%18,%19,%20,%21,%22,%23,%24,%25,%26,%27,%28,%29,%30,%31," \
            "%32,%33,%34,%35,%36,%37,%38,%39,%40,%41,%42,%43,%44,%45,%46,%47,%48,%49,%50,%51,%52,%53,%54,%55,%56,%57,%58,%59,%60,%61,%62,%63"
#define D128 D64 ",%64,%65,%66,%67,%68,%69,%70,%71,%72,%73,%74,%75,%76,%77,%78,%79,%80,%81,%82,%83,%84,%85,%86,%87,%88,%89,%90,%91,%92,%93,%94,%95," \
            "%96,%97,%98,%99,%100,%101,%102,%103,%104,%105,%106,%107,%108,%109,%110,%111,%112,%113,%114,%115,%116,%117,%118,%119,%120,%121,%122,%123,%124,%125,%126,%127"

template <int TB> __device__ __forceinline__ void wgmma_ss128(float* d, uint64_t da, uint64_t db, int acc) {
  asm volatile("{\n.reg .pred p;\nsetp.ne.b32 p, %66, 0;\nwgmma.mma_async.sync.aligned.m64n128k16.f32.bf16.bf16 " D64 "}, %64, %65, p, 1, 1, 0, %67;\n}"
    : R64(d, 0) : "l"(da), "l"(db), "r"(acc), "n"(TB));
}
template <int TB> __device__ __forceinline__ void wgmma_rs128(float* d, const uint32_t* a, uint64_t db, int acc) {
  asm volatile("{\n.reg .pred p;\nsetp.ne.b32 p, %69, 0;\nwgmma.mma_async.sync.aligned.m64n128k16.f32.bf16.bf16 " D64 "}, {%64,%65,%66,%67}, %68, p, 1, 1, %70;\n}"
    : R64(d, 0) : "r"(a[0]), "r"(a[1]), "r"(a[2]), "r"(a[3]), "l"(db), "r"(acc), "n"(TB));
}
template <int TB> __device__ __forceinline__ void wgmma_ss256(float* d, uint64_t da, uint64_t db, int acc) {
  asm volatile("{\n.reg .pred p;\nsetp.ne.b32 p, %130, 0;\nwgmma.mma_async.sync.aligned.m64n256k16.f32.bf16.bf16 " D128 "}, %128, %129, p, 1, 1, 0, %131;\n}"
    : R64(d, 0), R64(d, 64) : "l"(da), "l"(db), "r"(acc), "n"(TB));
}

#define W8(a,o) "=f"(a[o+0]), "=f"(a[o+1]), "=f"(a[o+2]), "=f"(a[o+3]), "=f"(a[o+4]), "=f"(a[o+5]), "=f"(a[o+6]), "=f"(a[o+7])
#define W64(a,o) W8(a,o), W8(a,o+8), W8(a,o+16), W8(a,o+24), W8(a,o+32), W8(a,o+40), W8(a,o+48), W8(a,o+56)
template <int TB> __device__ __forceinline__ void wgmma_ss128_z(float* d, uint64_t da, uint64_t db) {
  asm volatile("wgmma.mma_async.sync.aligned.m64n128k16.f32.bf16.bf16 " D64 "}, %64, %65, 0, 1, 1, 0, %66;"
    : W64(d, 0) : "l"(da), "l"(db), "n"(TB));
}
template <int TB> __device__ __forceinline__ void wgmma_rs128_z(float* d, const uint32_t* a, uint64_t db) {
  asm volatile("wgmma.mma_async.sync.aligned.m64n128k16.f32.bf16.bf16 " D64 "}, {%64,%65,%66,%67}, %68, 0, 1, 1, %69;"
    : W64(d, 0) : "r"(a[0]), "r"(a[1]), "r"(a[2]), "r"(a[3]), "l"(db), "n"(TB));
}
template <int TB> __device__ __forceinline__ void wgmma_ss256_z(float* d, uint64_t da, uint64_t db) {
  asm volatile("wgmma.mma_async.sync.aligned.m64n256k16.f32.bf16.bf16 " D128 "}, %128, %129, 0, 1, 1, 0, %130;"
    : W64(d, 0), W64(d, 64) : "l"(da), "l"(db), "n"(TB));
}

template <int TB> __device__ __forceinline__ void wgmma_rs256(float* d, const uint32_t* a, uint64_t db) {
  asm volatile("wgmma.mma_async.sync.aligned.m64n256k16.f32.bf16.bf16 " D128 "}, {%128,%129,%130,%131}, %132, 1, 1, 1, %133;"
    : R64(d, 0), R64(d, 64) : "r"(a[0]), "r"(a[1]), "r"(a[2]), "r"(a[3]), "l"(db), "n"(TB));
}
template <int TB> __device__ __forceinline__ void wgmma_rs256_z(float* d, const uint32_t* a, uint64_t db) {
  asm volatile("wgmma.mma_async.sync.aligned.m64n256k16.f32.bf16.bf16 " D128 "}, {%128,%129,%130,%131}, %132, 0, 1, 1, %133;"
    : W64(d, 0), W64(d, 64) : "r"(a[0]), "r"(a[1]), "r"(a[2]), "r"(a[3]), "l"(db), "n"(TB));
}
#define D32 "{%0,%1,%2,%3,%4,%5,%6,%7,%8,%9,%10,%11,%12,%13,%14,%15,%16,%17,%18,%19,%20,%21,%22,%23,%24,%25,%26,%27,%28,%29,%30,%31}"
__device__ __forceinline__ void wgmma_rs64(float* d, const uint32_t* a, uint64_t db) {
  asm volatile("wgmma.mma_async.sync.aligned.m64n64k16.f32.bf16.bf16 " D32 ", {%32,%33,%34,%35}, %36, 1, 1, 1, 0;"
    : R8(d, 0), R8(d, 8), R8(d, 16), R8(d, 24) : "r"(a[0]), "r"(a[1]), "r"(a[2]), "r"(a[3]), "l"(db));
}
__device__ __forceinline__ void wgmma_rs64_z(float* d, const uint32_t* a, uint64_t db) {
  asm volatile("wgmma.mma_async.sync.aligned.m64n64k16.f32.bf16.bf16 " D32 ", {%32,%33,%34,%35}, %36, 0, 1, 1, 0;"
    : W8(d, 0), W8(d, 8), W8(d, 16), W8(d, 24) : "r"(a[0]), "r"(a[1]), "r"(a[2]), "r"(a[3]), "l"(db));
}
__device__ __forceinline__ void issue_qk(float* S, const uint32_t* Q, uint64_t dk) {
  wgmma_rs64_z(S, Q, dk);
#pragma unroll
  for (int kk = 1; kk < 8; kk++) wgmma_rs64(S, Q + 4 * kk, dk + (kk >> 2) * 512 + (kk & 3) * 2);
}
__device__ __forceinline__ void issue_pv(float* O, const uint32_t* P, uint64_t dv, int acc) {
#pragma unroll
  for (int kk = 0; kk < 4; kk++) wgmma_rs128<1>(O, P + 4 * kk, dv + kk * 128, kk ? 1 : acc);
}

#define TS(i)
#define TSC(i)
#define TSX(i)
#define TSY(k) do { if ((tid & 127) == 0) TS((k) + 40 * wg); } while (0)
#define TT(k)
#define TV(k)
#define TR(k)
#define TQ(k)
#define TH(k)
#define TA(k)
#define TAFLUSH()

struct SoftmaxState { float c0, c1, l0, l1; bool shifted; };
constexpr float SM_SCALE = 0.08838834764831845f * 1.4426950408889634f;
__device__ __forceinline__ void softmax_start(SoftmaxState& z) { z.c0 = z.c1 = z.l0 = z.l1 = 0.f; z.shifted = false; }
__device__ __forceinline__ void softmax_half(float* S, uint32_t* P, float* O, SoftmaxState& z, bool first, uint32_t tag) {
  const float lo0 = z.l0, lo1 = z.l1;
  float lim = 1.2676506002282294e30f;
  const float low = first ? 8.673617379884035e-19f : 0.f;
  if (z.shifted) {
#pragma unroll
    for (int j = 0; j < 32; j++) S[j] += (j & 2) ? z.c1 : z.c0;
  }
#pragma unroll 1
  while (true) {
    bb_fence(tag);
#pragma unroll
    for (int j = 0; j < 8; j++) {
      const float p0 = ex2(S[4 * j]), p1 = ex2(S[4 * j + 1]), p2 = ex2(S[4 * j + 2]), p3 = ex2(S[4 * j + 3]);
      z.l0 += p0; z.l1 += p2; z.l0 += p1; z.l1 += p3;
      P[2 * j] = pack2(p0, p1); P[2 * j + 1] = pack2(p2, p3);
    }
    if (!__any_sync(0xffffffffu, !(z.l0 < lim && z.l1 < lim && fminf(z.l0, z.l1) >= low) && lim > 0.f)) break;
    float d0 = fmaxf(S[0], S[1]), d1 = fmaxf(S[2], S[3]);
#pragma unroll
    for (int j = 1; j < 8; j++) { d0 = fmaxf(d0, fmaxf(S[4 * j], S[4 * j + 1])); d1 = fmaxf(d1, fmaxf(S[4 * j + 2], S[4 * j + 3])); }
    d0 = fmaxf(d0, __shfl_xor_sync(0xffffffffu, d0, 1)); d1 = fmaxf(d1, __shfl_xor_sync(0xffffffffu, d1, 1));
    d0 = fmaxf(d0, __shfl_xor_sync(0xffffffffu, d0, 2)); d1 = fmaxf(d1, __shfl_xor_sync(0xffffffffu, d1, 2));
    if (!first) { d0 = fmaxf(d0, 0.f); d1 = fmaxf(d1, 0.f); }
    z.shifted = true;
    z.c0 -= d0; z.c1 -= d1;
#pragma unroll
    for (int j = 0; j < 32; j++) S[j] -= (j & 2) ? d1 : d0;
    const float a0 = first ? 1.f : ex2(-d0), a1 = first ? 1.f : ex2(-d1);
    z.l0 = lo0 * a0; z.l1 = lo1 * a1;
    lim = -1.f;
    wg_wait<0>();
    reg_fence<64>(O);
#pragma unroll
    for (int j = 0; j < 16; j++) { O[4 * j] *= a0; O[4 * j + 1] *= a0; O[4 * j + 2] *= a1; O[4 * j + 3] *= a1; }
  }
}

__device__ __forceinline__ void normalise_frags(uint32_t* V, const uint32_t* ln) {
#pragma unroll
  for (int i = 0; i < 16; i++) V[i] = hfma2(V[i], ln[(i & 1) * 2 + 1], ln[(i & 1) * 2]);
}
__device__ __forceinline__ void modulate_frags(uint32_t* A, const uint32_t* V, const uint4* R) {
#pragma unroll
  for (int kk = 0; kk < 4; kk++) {
    const uint4 sa = R[kk >> 1], c1 = R[2 + (kk >> 1)];
#pragma unroll
    for (int j = 0; j < 4; j++) {
      const uint32_t n = V[4 * kk + j];
      A[4 * kk + j] = (kk & 1) ? ((j & 2) ? hfma2(n, c1.w, sa.x) : hfma2(n, c1.z, sa.w)) : ((j & 2) ? hfma2(n, c1.y, sa.z) : hfma2(n, c1.x, sa.y));
    }
  }
}
__device__ __forceinline__ void publish_record(uint4* dst, uint32_t pk, int src, int vec, bool doit) {
  const int r = vec ? 0 : 12;
  const uint32_t x = __shfl_sync(0xffffffffu, pk, src + r), y = __shfl_sync(0xffffffffu, pk, src + ((r + 4) & 12));
  const uint32_t z = __shfl_sync(0xffffffffu, pk, src + ((r + 8) & 12)), w = __shfl_sync(0xffffffffu, pk, src + ((r + 12) & 12));
  if (doit) st_pkt16(dst, ~x, y, z, w);
}
__device__ __forceinline__ void put_record(uint32_t sb, int idx, const uint4& v) {
  sts128(sb + SM_STASH + idx * 16, ~v.x, v.y, v.z, v.w);
  sts128(sb + SM_STASH + 16384 + idx * 16, ~v.x, v.y, v.z, v.w);
}
__device__ __forceinline__ float mod_value(float v, int vec) {
  v = rbf(v);
  return (vec ? rbf(1.f + v) : v) * SM_SCALE;
}

__device__ __forceinline__ void row_rcp(float& l0, float& l1) {
  l0 += __shfl_xor_sync(0xffffffffu, l0, 1); l1 += __shfl_xor_sync(0xffffffffu, l1, 1);
  l0 += __shfl_xor_sync(0xffffffffu, l0, 2); l1 += __shfl_xor_sync(0xffffffffu, l1, 2);
  l0 = rcp_f(l0); l1 = rcp_f(l1);
}
__device__ __forceinline__ void stage_o(const float* O, float r0, float r1, uint32_t stsm_addr) {
#pragma unroll
  for (int kk = 0; kk < 8; kk++) {
    stsm4((stsm_addr + (kk >> 2) * 8192) ^ ((kk & 3) * 32),
          pack2(O[8 * kk + 0] * r0, O[8 * kk + 1] * r0), pack2(O[8 * kk + 2] * r1, O[8 * kk + 3] * r1),
          pack2(O[8 * kk + 4] * r0, O[8 * kk + 5] * r0), pack2(O[8 * kk + 6] * r1, O[8 * kk + 7] * r1));
  }
}

__global__ void __cluster_dims__(2, 1, 1) __launch_bounds__(NTHREADS, 1)
fused_kernel(const Params p, const __grid_constant__ CUtensorMap mH, const __grid_constant__ CUtensorMap mWq,
             const __grid_constant__ CUtensorMap mK, const __grid_constant__ CUtensorMap mV,
             const __grid_constant__ CUtensorMap mO, const __grid_constant__ CUtensorMap mWo,
             const __grid_constant__ CUtensorMap mX, const __grid_constant__ CUtensorMap mOut,
             const __grid_constant__ CUtensorMap mWg, const __grid_constant__ CUtensorMap mWu,
             const __grid_constant__ CUtensorMap mWd, const __grid_constant__ CUtensorMap mWm,
             const __grid_constant__ CUtensorMap mWs, const __grid_constant__ CUtensorMap mWh,
             const __grid_constant__ CUtensorMap mOs) {
  extern __shared__ __align__(1024) uint8_t smem_raw[];
  TH(0);
  const uint32_t sb = smem_u32(smem_raw);
  const int tid = threadIdx.x;
  const int b0 = blockIdx.x;
  const int lane = tid & 31;
  const int role = __shfl_sync(0xffffffffu, tid >> 8, 0);

  if (b0 >= NMAIN) {
    const uint32_t cs = clock();
    const uint32_t tag = ld_relaxed(&g_epoch) + 1;
    const int sp = b0 - NMAIN, vec = 2 + sp;
    const int warp = __shfl_sync(0xffffffffu, tid >> 5, 0);
    float* sc = reinterpret_cast<float*>(smem_raw + SM_STASH);
    float* red = reinterpret_cast<float*>(smem_raw + SM_STASH + 4096);
    const int ridx = (lane >> 3) * 2 * RV + (sp & 1) * RV + 16 * RS + (sp >> 1) * 16 + (warp & 1) * 8 + (lane & 7);
    if (warp < 8) st_pkt16(&g_rec[warp >> 2][0][ridx + (warp & 2) * 16], 0, 0, 0, 0);
#pragma unroll 1
    for (int i = tid; i < 1024; i += NTHREADS) sc[i] = rbf(silu_f(__bfloat162float(p.c[i])));
    if (tid == 0) {
      tma_prefetch_desc(&mWs);
      for (int s = 0; s < NST2; s++) { mbar_init(sb + BAR_FULL2 + 8 * s, 1); mbar_init(sb + BAR_EMPTY2 + 8 * s, 8); }
      fence_async_smem();
      while ((uint32_t)clock() - cs < SPT) {}
    }
    __syncthreads();
    int s = 0; uint32_t ph = 0;
    if (tid == 0) TS(0);
    if (warp == 8) {
      const uint64_t pol = policy_evict_first();
#pragma unroll 1
      for (int n = 0; n < 80; n++) {
        mbar_wait_g(sb + BAR_EMPTY2 + 8 * s, ph ^ 1);
        if (elect_one()) {
          mbar_expect_tx(sb + BAR_FULL2 + 8 * s, 32768);
          if (n < 16) {
            tma_ld_hint(sb + s * ST2, &mWs, (sp & 1) * 1024 + 512 + (n >> 3) * 256 + (sp >> 1) * 128, (n & 7) * 128, sb + BAR_FULL2 + 8 * s, pol);
          } else {
#pragma unroll
            for (int j = 0; j < 4; j++) tma_ld_hint(sb + s * ST2 + j * 8192, &mWm, vec * 1024 + j * 256, (n - 16) * 16, sb + BAR_FULL2 + 8 * s, pol);
          }
        }
        __syncwarp();
        if (++s == NST2) { s = 0; ph ^= 1; }
      }
    } else if (warp < 8) {
      float acc[8];
#pragma unroll
      for (int i = 0; i < 8; i++) acc[i] = 0.f;
      auto stage = [&](uint32_t a0, int da, const float* cp, int dc) {
        mbar_wait_g(sb + BAR_FULL2 + 8 * s, ph);
#pragma unroll
        for (int i = 0; i < 8; i++) {
          const uint4 v = lds128(a0 + s * ST2 + i * da);
          const float c = cp[i * dc];
          acc[0] = fmaf(lo2f(v.x), c, acc[0]); acc[1] = fmaf(hi2f(v.x), c, acc[1]);
          acc[2] = fmaf(lo2f(v.y), c, acc[2]); acc[3] = fmaf(hi2f(v.y), c, acc[3]);
          acc[4] = fmaf(lo2f(v.z), c, acc[4]); acc[5] = fmaf(hi2f(v.z), c, acc[5]);
          acc[6] = fmaf(lo2f(v.w), c, acc[6]); acc[7] = fmaf(hi2f(v.w), c, acc[7]);
        }
        if (__shfl_sync(0xffffffffu, lane, __float_as_uint(acc[7]) & 31) < 32 && lane == 0) mbar_arrive(sb + BAR_EMPTY2 + 8 * s);
        if (++s == NST2) { s = 0; ph ^= 1; }
      };
#pragma unroll 1
      for (int n = 0; n < 16; n++) {
        stage(sb + tid * 16, 4096, sc + (n & 7) * 128 + (tid >> 4), 16);
        if ((n & 7) == 7) {
          float* r2 = red + 2048 + (n & 8) * 256;
#pragma unroll
          for (int i = 0; i < 8; i++) { r2[tid * 8 + i] = acc[i]; acc[i] = 0.f; }
          nb_sync(NB_CONS, 256);
          if (warp < 2) {
            float v0 = 0.f, v1 = 0.f;
#pragma unroll 4
            for (int i = 0; i < 16; i++) { const float2 e = reinterpret_cast<const float2*>(r2)[i * 64 + tid]; v0 += e.x; v1 += e.y; }
            publish_record(&g_rec[tag & 1][0][ridx + (n >> 3) * 32], pack2(mod_value(v0, sp & 1), mod_value(v1, sp & 1)),
                           (lane & 4) * 4 + (lane & 3), sp & 1, true);
          }
          if (tid == 0) TS(1 + (n >> 3));
        }
      }
#pragma unroll 1
      for (int n = 0; n < 64; n++) {
        stage(sb + ((tid >> 5) & 3) * 8192 + (tid >> 7) * 4096 + (tid & 31) * 16, 512, sc + n * 16 + (tid >> 7) * 8, 1);
      }
#pragma unroll
      for (int i = 0; i < 8; i++) red[(tid >> 7) * 1024 + (tid & 127) * 8 + i] = acc[i];
    }
    __syncthreads();
    float dot = 0.f;
#pragma unroll 1
    for (int i = tid; i < 512; i += NTHREADS) {
      uint32_t v = pack2(red[2 * i] + red[1024 + 2 * i], red[2 * i + 1] + red[1024 + 2 * i + 1]);
      st_pkt8(&g_mod[vec * 512 + i], v, tag);
      if (vec == 4) v = hadd2(v, ONE2);
      const uint32_t wr = reinterpret_cast<const uint32_t*>(p.w_r)[i];
      dot = fmaf(lo2f(v), lo2f(wr), fmaf(hi2f(v), hi2f(wr), dot));
    }
#pragma unroll
    for (int o = 16; o; o >>= 1) dot += __shfl_xor_sync(0xffffffffu, dot, o);
    if (lane == 0) sc[warp] = dot;
    __syncthreads();
    if (tid == 0) {
      dot = 0.f;
      for (int w = 0; w < 12; w++) dot += sc[w];
      fence_release_gpu();
      st_pkt8(&g_vdone[(vec - 2) * 16], __float_as_uint(dot), tag);
      TS(11);
#pragma unroll 1
      for (int i = 0; i < 128; i++) {
        const int u = i * 4 + (b0 - NMAIN);
        l2_prefetch(p.wo + (size_t)((4 * ((u >> 4) & 7) + (u >> 7)) * 128 + (u & 15) * 8) * 1024, 16384);
        __nanosleep(PFW);
      }
    }
    return;
  }

  const uint32_t rank = b0 & 1;
  const bool slab = !(b0 & 32), late = b0 & 16;
  const uint32_t c0 = clock();
  if (tid == 352) TS(0);
  const uint32_t slab_addr = sb + SM_WSLAB + (tid >> 5) * 4096 + (lane & 3) * 128 + (lane & 4) * 16 + (((lane >> 3) ^ lane) & 3) * 16;
  auto load_slab = [&]() {
    const bf16* wp = p.w_mod + (size_t)(512 * rank + 2 * (tid & ~31) + 2 * (lane & 3) + ((lane >> 2) & 1)) * 6144 + 32 * (b0 >> 1) + 8 * (lane >> 3);
    const uint64_t pef = policy_evict_first();
#pragma unroll
    for (int i = 0; i < 8; i++)
      asm volatile("cp.async.cg.shared.global.L2::cache_hint [%0], [%1], 16, %2;"
        :: "r"(slab_addr + i * 512), "l"(wp + (size_t)i * 8 * 6144), "l"(pef) : "memory");
  };
  if (tid == 256) {
    mbar_init(sb + BAR_XH, 1); mbar_init(sb + BAR_XH + 8, 1);
    fence_async_smem();
#pragma unroll
    for (int i = 0; i < 2; i++) {
      mbar_expect_tx(sb + BAR_XH + 8 * i, 16384);
      asm volatile("cp.async.bulk.shared::cluster.global.mbarrier::complete_tx::bytes [%0], [%1], 16384, [%2];"
        :: "r"(sb + SM_XROW + i * ST1), "l"(p.x + (size_t)b0 * 16384 + i * 8192), "r"(sb + BAR_XH + 8 * i) : "memory");
    }
  }
  __syncwarp();
  uint32_t cw[8];
#pragma unroll
  for (int i = 0; i < 8; i++) cw[i] = 0;
  if (!role && slab) {
#pragma unroll
    for (int i = 0; i < 8; i++) cw[i] = ld_relaxed(reinterpret_cast<const uint32_t*>(p.c) + 256 * rank + (tid & ~28) + 4 * i);
  }
  uint32_t epoch = 0;
  if (!role) epoch = ld_relaxed(&p.sc->epoch[lane]);
  if (!role && slab && !late) load_slab();
#define TILE_ROLES() \
  mbar_wait(sb + BAR_ROLE, 0); \
  const int b = 2 * __shfl_sync(0xffffffffu, lds32(sb + SM_ROLE), 0) + rank; \
  const int rt = b >> 3;     \
  const int ct = b & 7;

  if (role) {
    asm volatile("setmaxnreg.dec.sync.aligned.u32 24;");
    const int warp = __shfl_sync(0xffffffffu, tid >> 5, 0);
    if (tid == 256) {
      mbar_init(sb + BAR_RED, 1); mbar_init(sb + BAR_WH, 1);
      for (int s = 0; s < 2; s++) mbar_init(sb + BAR_OF + 8 * s, 1);
      mbar_init(sb + BAR_ROLE, 1);
      for (int s = 0; s < 5; s++) { mbar_init(sb + BAR_FULL1 + 8 * s, 1); mbar_init(sb + BAR_EMPTY1 + 8 * s, 4); }
      for (int s = 0; s < 2; s++) { mbar_init(sb + BAR_STASH + 8 * s, 1); mbar_init(sb + BAR_X + 8 * s, 1); }
      for (int s = 0; s < 4; s++) mbar_init(sb + BAR_HS + 8 * s, 1);
      mbar_init(sb + BAR_G, 16); mbar_init(sb + BAR_T1, 1); mbar_init(sb + BAR_HF, 1);
      mbar_init(sb + BAR_SFREE, 4); mbar_init(sb + BAR_TFREE, 8);
      mbar_init(sb + BAR_FFN, 4); mbar_init(sb + BAR_FFN + 8, 2);
      mbar_init(sb + BAR_CAND, 1); mbar_init(sb + BAR_VEC, 32); for (int s = 0; s < 3; s++) mbar_init(sb + BAR_TAB + 8 * s, 32);
      mbar_expect_tx(sb + BAR_RED, 1024);
      mbar_expect_tx(sb + BAR_ROLE, 4);
      asm volatile("fence.mbarrier_init.release.cluster;" ::: "memory");
    }
    __syncwarp();
    asm volatile("barrier.cluster.arrive.relaxed.aligned;" ::: "memory");
    const int ridx = ((lane >> 1) & 3) * 2 * RV + (b0 >> 6) * RV + ((b0 >> 1) & 31) * RS + 2 * rank + (lane & 1) + (lane >> 3) * 4;
    if (warp == 11 && slab && lane < 2 * RS) { st_pkt16(&g_rec[0][0][ridx], 0, 0, 0, 0); st_pkt16(&g_rec[1][0][ridx], 0, 0, 0, 0); }
    if (tid == 256) {
      tma_prefetch_desc(&mWq); tma_prefetch_desc(&mX); tma_prefetch_desc(&mH); tma_prefetch_desc(&mK); tma_prefetch_desc(&mV); tma_prefetch_desc(&mOs);
    }
    uint32_t pairid = 0;
    if (tid == 320 && rank == 0) {
      uint32_t t;
      asm("mov.u32 %0, %%smid;" : "=r"(t));
      t >>= 1;
      uint32_t grp = ((0x73216540u >> (4 * ((t < 32 ? t : t < 60 ? 1 + (t - 32) % 7 : t < 62 ? t - 54 : 0) & 7))) & 7) - 1, slot;
      int it = 0;
      do {
        grp = (grp + 1) & 7;
        asm volatile("atom.relaxed.gpu.global.add.u32 %0, [%1], 1;" : "=r"(slot) : "l"(&p.sc->ticket[grp * 32]) : "memory");
        spin_guard(it);
      } while (slot >= 8);
      pairid = slot * 8 + grp;
    }
    __syncwarp();
    asm volatile("barrier.cluster.wait.aligned;" ::: "memory");
    if (tid == 320 && rank == 0) {
#pragma unroll
      for (int r = 0; r < 2; r++)
        asm volatile("st.async.weak.shared::cluster.mbarrier::complete_tx::bytes.b32 [%0], %1, [%2];"
          :: "r"(mapa(sb + SM_ROLE, r)), "r"(pairid), "r"(mapa(sb + BAR_ROLE, r)) : "memory");
    }
    __syncwarp();
    const uint32_t tag = ld_relaxed(&g_epoch) + 1;
    if (warp == 8) {
      TILE_ROLES();
      const int kvrow = (ct >> 1) * 2048 + 1536, arow = rt * 128 + rank * 64;
      const uint64_t pef = policy_evict_first();
#pragma unroll 1
      for (int pair = 0; pair < 2; pair++) {
        const int wblk = (4 * ct + 2 * pair) * 2;
        if (pair) { mbar_wait_g(sb + BAR_HF, 0); fence_async_global(); }
#pragma unroll 1
        for (int n = 0; n < 16; n++) {
          const uint32_t s = n & 3, st = sb + SM_RING + s * ST1, fb = sb + BAR_FULL1 + 8 * s;
          if (n == 2 && pair == 0) {
            while ((uint32_t)clock() - c0 < W2T) {}
            if (elect_one()) { mbar_expect_tx(fb, 49152); tma_ld3_hint(st + 16384, &mWq, n * 64, wblk, fb, pef); }
            __syncwarp();
            mbar_wait_g(sb + BAR_G, 0);
            if (elect_one()) tma_ld_mc(st + rank * 8192, &mX, n * 64, arow, fb);
            __syncwarp();
            continue;
          }
          mbar_wait_g(fb + (BAR_EMPTY1 - BAR_FULL1), ((n >> 2) & 1) ^ 1);
          if (elect_one()) {
            mbar_expect_tx(fb, 49152);
            if (pair) tma_ld_mc_hint(st + rank * 8192, &mH, n * 64, arow, fb, pef); else
            tma_ld_mc(st + rank * 8192, pair ? &mH : &mX, n * 64, arow, fb);
            tma_ld3_hint(st + 16384, &mWq, n * 64, wblk, fb, pef);
          }
          __syncwarp();
        }
#pragma unroll 1
        for (int n = 0; n < 16; n++) {
          const uint32_t s = n & 3, st = sb + SM_RING + s * ST1 + rank * 8192, fb = sb + BAR_FULL1 + 8 * s;
          const int h0 = n == 0 ? 0 : n == 15 ? 14 : n + 1, h1 = n == 0 ? 1 : n == 15 ? 15 : n - 1;
          mbar_wait_g(fb + (BAR_EMPTY1 - BAR_FULL1), ((n >> 2) & 1) ^ 1);
          if (elect_one()) {
            mbar_expect_tx(fb, 32768);
            tma_ld_mc(st, n == 15 ? &mV : &mK, rank * 64, kvrow + (h0 & 7) * 64, fb);
            tma_ld_mc(st + 16384, n == 0 ? &mK : &mV, rank * 64, kvrow + (h1 & 7) * 64, fb);
            if (n == 3 && pair == 1) mbar_arrive(sb + BAR_T1);
          }
          __syncwarp();
        }
      }
      {
        uint32_t s = 0, ph = 1;
#pragma unroll 1
        for (int half = 0; half < 2; half++) {
          mbar_wait_g(sb + BAR_OF + 8 * half, 0);
          fence_async_global();
#pragma unroll 1
          for (int n = 32 * half; n < 32 * half + 32; n++) {
            const uint32_t st = sb + SM_RING + s * ST1, fb = sb + BAR_FULL1 + 8 * s;
            const int k0 = ((n & 14) * 2 + (n >> 4)) * 128 + (n & 1) * 64;
            mbar_wait_g(n == 8 ? sb + BAR_SFREE : fb + (BAR_EMPTY1 - BAR_FULL1), n == 8 ? 0 : ph ^ (s >> 2));
            if (elect_one()) {
              mbar_expect_tx(fb, 32768);
              tma_ld_mc_hint(st + rank * 8192, &mO, k0, arow, fb, pef);
              tma_ld3_hint(st + 16384, &mWo, k0, 2 * ct, fb, pef);
            }
            __syncwarp();
            if (++s == 5 || n == 3) { s = 0; ph ^= 1; }
          }
        }
        if (b < NFFN) {
#pragma unroll 1
          for (s = 0; s < 2; s++) {
            mbar_wait_g(sb + BAR_EMPTY1 + 8 * s, 0);
            if (elect_one()) {
              mbar_expect_tx(sb + BAR_FFN + 8, 32768);
              tma_ld3_hint(sb + SM_RING + s * ST1, &mWd, b * 32, s * 8, sb + BAR_FFN + 8, pef);
            }
            __syncwarp();
          }
        }
      }
    } else if (warp <= 10) {
      const int w = warp - 9;
      if (slab && late && w == 0 && lane == 0) {
        tma_prefetch_desc(&mWh);
        mbar_expect_tx(sb + BAR_WH, 32768);
        while ((uint32_t)clock() - c0 < WL) {}
        const uint64_t pef = policy_evict_first();
#pragma unroll
        for (int i = 0; i < 2; i++) tma_ld_hint(sb + SM_WSLAB + i * 16384, &mWh, 32 * (b0 >> 1), 512 * rank + 256 * i, sb + BAR_WH, pef);
      }
      __syncwarp();
      TILE_ROLES();
      const uint32_t st = sb + SM_STASH + w * 16384;
#pragma unroll 1
      for (int j = 0; j < 2; j++) {
        nb_sync(NB_OST + w, 160);
        if (elect_one()) {
          fence_async_smem();
          tma_st(&mH, (2 * ct + j) * 64, rt * 128 + w * 64, st + 4096);
          bulk_commit();
          bulk_wait_read();
          mbar_arrive(sb + BAR_HS + 16 * w + 8 * j);
          if (j) {
            bulk_wait_all();
            fence_async_global();
            fence_release_gpu();
            red_add_relaxed(&g_hflag[rt * 32], 1);
          }
        }
        __syncwarp();
      }
#pragma unroll 1
      for (int r = 0; r < 4; r++) {
        nb_sync(NB_OST + w, 160);
        if (elect_one()) {
          fence_async_smem();
          const int hcol = (4 * ct + r) * 128;
#pragma unroll 1
          for (int i = 0; i < 8; i++) {
            tma_st(&mOs, hcol + (i & 4) * 16, rt * 128 + w * 64 + (i & 3) * 16, st + i * 2048);
            __nanosleep(r == 3 ? OP3 : OP0);
          }
          bulk_commit();
          bulk_wait_read();
          if (r < 2) {
            mbar_arrive(sb + BAR_STASH + 8 * w);
          } else if (r == 2) {
            mbar_expect_tx(sb + BAR_X + 8 * w, 16384);
            tma_ld_hint(st, &mX, ct * 128, rt * 128 + w * 64, sb + BAR_X + 8 * w, policy_evict_first());
            tma_ld_hint(st + 8192, &mX, ct * 128 + 64, rt * 128 + w * 64, sb + BAR_X + 8 * w, policy_evict_first());
          } else {
            mbar_arrive_cl(mapa(sb + BAR_SFREE, 0)); mbar_arrive_cl(mapa(sb + BAR_SFREE, 1));
          }
          bulk_wait_all();
          fence_async_global();
          fence_release_gpu();
          red_add_relaxed(&g_oflag[(rt * 4 + r) * 32], 1);
        }
        __syncwarp();
      }
      nb_sync(NB_OST + w, 160);
      int skip = -1;
      mbar_wait_g(sb + BAR_CAND, 0);
      const bool has_cand = (lds32(sb + SM_CAND) >> 6) == w;
      if (has_cand) {
        nb_sync(NB_WIN + w, 160);
        skip = (int)lds32(sb + SM_WROW + 4 * w) - (rt * 128 + w * 64);
      }
      if ((unsigned)skip >= 64u) {
        if (elect_one()) {
          fence_async_smem();
          tma_st(&mOut, ct * 128, rt * 128 + w * 64, sb + SM_OUT + w * 16384);
          tma_st(&mOut, ct * 128 + 64, rt * 128 + w * 64, sb + SM_OUT + w * 16384 + 8192);
          bulk_commit();
          bulk_wait_read();
        }
        __syncwarp();
      } else {
        uint4* dst = reinterpret_cast<uint4*>(p.out + (size_t)(rt * 128 + w * 64 + (lane >> 4)) * 1024 + ct * 128) + (lane & 15);
#pragma unroll 2
        for (int r = lane >> 4; r < 64; r += 2) {
          const uint4 v = lds128(sb + SM_OUT + w * 16384 + ((lane >> 3) & 1) * 8192 + r * 128 + (((lane ^ r) & 7) * 16));
          if (r != skip) *dst = v;
          dst += 256;
        }
      }
      if (!has_cand) nb_sync(NB_WIN + w, 160);
    } else {
      if (slab) {
        mbar_wait_g(sb + BAR_RED, 0);
        float v = 0.f;
#pragma unroll
        for (int w = 0; w < 8; w++) v += lds_f32(sb + SM_RED + w * 128 + lane * 4);
        v += __shfl_xor_sync(0xffffffffu, v, 16);
        v = mod_value(v, b0 >> 6);
        publish_record(&g_rec[tag & 1][0][ridx], pack2(v, __shfl_down_sync(0xffffffffu, v, 1)), 2 * (lane & 1), b0 >> 6, lane < 8);
        if (lane == 0) TS(1);
      }
      mbar_wait_g(sb + BAR_G, 0);
#pragma unroll 1
      for (int i = 1; i < 4; i++) {
        const uint4* mp = &g_rec[tag & 1][(b0 >> 1) & (NREP - 1)][i == 1 ? (8 + (lane >> 2)) * RS + (lane & 3) : 16 * RS - 64 + 32 * i + lane];
        uint4 v0, v1; int it = 0;
        while (true) {
          v0 = ld_pkt16(mp); v1 = ld_pkt16(mp + RV);
          if (v0.x != 0 && v1.x != 0) break;
          spin_guard(it); __nanosleep(PLD);
        }
        put_record(sb, 32 * i + lane, v0);
        put_record(sb, 128 + 32 * i + lane, v1);
        mbar_arrive(sb + BAR_TAB - 8 + 8 * i);
        if (lane == 0) {
          TS(3 + i + (i > 2));
          if (i == 1) l2_prefetch(((b0 & 64) ? p.vc : p.kc) + (size_t)(((b0 >> 4) & 3) * 2048 + 1536) * 128 + (b0 & 15) * 4096, 8192);
        }
        __syncwarp();
      }
      TILE_ROLES();
      if (lane == 0) {
        int it = 0;
        do { __nanosleep(500); spin_guard(it); } while (ld_relaxed(&g_hflag[rt * 32]) != tag * 16u);
        fence_acquire_gpu();
        mbar_arrive(sb + BAR_HF);
        if (b < NFFN) for (int i = 0; i < 8; i++) { __nanosleep(800); l2_prefetch(p.wd + (size_t)(b * 32 + i * 4) * 1024, 8192); }
      }
      __syncwarp();
      {
        uint2 v; int it = 0;
        do { __nanosleep(1000); v = ld_pkt8(&g_vdone[(lane & 3) * 16]); spin_guard(it); }
        while (!(v.y == tag));
        __syncwarp();
        fence_acquire_gpu();
        if (lane == 1 || lane == 2) sts32(sb + SM_SCAL + (2 - lane) * 4, v.x);
      }
#pragma unroll 1
      for (int i = 0; i < 2; i++) {
        const int q = i * 32 + lane, pi = ct * 64 + q;
        const uint32_t vga = g_mod[2 * 512 + pi].x, vsb = g_mod[3 * 512 + pi].x, vcb = g_mod[4 * 512 + pi].x, vgb = g_mod[5 * 512 + pi].x;
        const uint32_t wr = reinterpret_cast<const uint32_t*>(p.w_r)[pi];
        const uint32_t c1 = hadd2(vcb, ONE2);
        const float al = lo2f(c1) * lo2f(wr), ah = hi2f(c1) * hi2f(wr);
        const uint32_t o8 = (q & 3) * 8 + ((q >> 2) & 1) * 4;
        sts32(sb + SM_GA + (q >> 3) * 32 + o8, vga);
        sts128(sb + SM_REC + q * 16, c1, vsb, vgb, 0);
        const uint32_t ahi = pack2(al, ah), alo = pack2(al - lo2f(ahi), ah - hi2f(ahi));
        const uint32_t ba = sb + SM_B1 + (q >> 3) * 128 + o8;
        sts32(ba, ONE2); sts32(ba + 32, ahi); sts32(ba + 64, alo); sts32(ba + 96, 0);
      }
      if (lane == 0) TS(28);
      if (lane == 0) {
        tma_prefetch_desc(&mWo); tma_prefetch_desc(&mO); tma_prefetch_desc(&mOut); tma_prefetch_desc(&mWd); tma_prefetch_desc(&mWg); tma_prefetch_desc(&mWu);
#pragma unroll 1
        for (int r = 0; r < 4; r++) {
          int it = 0;
          do { __nanosleep(200); spin_guard(it); } while (ld_relaxed(&g_oflag[(rt * 4 + r) * 32]) != tag * 16u);
          if (r & 1) { fence_acquire_gpu(); mbar_arrive(sb + BAR_OF + 8 * (r >> 1)); }
          if (r == 1 && b < NFFN) {
            const uint64_t pef = policy_evict_first();
            mbar_wait_g(sb + BAR_T1, 0);
#pragma unroll 1
            for (int i = 0; i < 4; i++) {
              mbar_expect_tx(sb + BAR_FFN, 16384);
              tma_ld_hint(sb + SM_RING + i * ST1 + 32768, &mWg, b * 32, i * 256, sb + BAR_FFN, pef);
              __nanosleep(GATED);
            }
          }
        }
      }
      __syncwarp();
      if (b < NFFN) {
        mbar_wait_g(sb + BAR_TFREE, 0);
        const uint64_t pef = policy_evict_first();
#pragma unroll 1
        for (int i = 0; i < 5; i++) {
          if (i > 0 && lane == 0) {
            mbar_expect_tx(sb + BAR_FFN, 16384);
            tma_ld_hint(sb + SM_RING + (i - 1) * ST1 + 32768, &mWu, b * 32, (i - 1) * 256, sb + BAR_FFN, pef);
          }
          if (i < 4) {
#pragma unroll 1
            for (int j = 0; j < 8; j++) {
              asm volatile("prefetch.global.L2 [%0];" :: "l"(p.wu + (size_t)(i * 256 + j * 32 + lane) * 3584 + b * 32) : "memory");
              __nanosleep(UPD);
            }
            __nanosleep(500);
          }
        }
      }
      if (lane == 0) TS(29);
#pragma unroll 1
      for (int i = lane; i < 128; i += 32) st_pkt16(&g_stats[b * 128 + i], 0, 0, 0, 0);
      st_pkt16(&g_cand[b * 32 + lane], 0, 0, 0, 0);
      if (lane < 8) st_pkt16(&g_entry[(ct * 16 + rt) * 8 + lane], 0, 0, 0, 0);
#pragma unroll 1
      for (int i = lane; i < (b < NFFN ? 512 : 0); i += 32) st_pkt16(&g_ypart[((i >> 2) * NFFN + b) * 4 + (i & 3)], 0, 0, 0, 0);
      mbar_arrive(sb + BAR_VEC);
      uint4* const cp = &g_cand[b * 32 + lane];
      uint4* const ep = &g_entry[(ct * 16 + rt) * 8];
      nb_sync(NB_AMAX, 288);
      TV(0);
      const uint2 e = lds64(sb + SM_AMAX + (lane & 7) * 8);
      const int tmax = __reduce_max_sync(0xffffffffu, (int)e.x);
      const uint32_t row = ~tmax & 127;
      const int wl = row >> 4;
      const uint32_t xa = sb + SM_X2 + (row >> 6) * 16384 + (lane >> 4) * 8192 + (row & 63) * 128 + (lane & 3) * 4
                        + ((((lane >> 1) & 6) ^ (row & 7)) * 16);
      const uint32_t v0 = lds32(xa), v1 = lds32(xa ^ 16);
      if (lane == wl) st_pkt16(ep, (tmax | 127) - rt, rt * 128 + row, e.y, tag);
      st_pkt16(cp, v0, v1, tag, 0);
      if (lane == 0) { sts32(sb + SM_CAND, row); mbar_arrive(sb + BAR_CAND); }
      TV(1);
      if (lane == 0) TS(15);
    }
  } else {
    const int warp = tid >> 5;
    const int wg = warp >> 2, wq = warp & 3;
    const int g = lane >> 2, t = lane & 3;
    uint32_t tag;
    uint32_t ln[4];
    float acc[128];
    uint32_t bf[16];
    auto gemv = [&]() {
          if (late) mbar_wait(sb + BAR_WH, 0); else
          asm volatile("cp.async.wait_all;" ::: "memory");
          float d0[4] = {0.f, 0.f, 0.f, 0.f}, d1[4] = {0.f, 0.f, 0.f, 0.f};
#pragma unroll
          for (int i = 0; i < 8; i++) {
            const uint4 wv = lds128(slab_addr + i * 512);
            const uint32_t a[4] = {wv.x, wv.y, wv.z, wv.w};
            mma16816((i & 1) ? d1 : d0, a, bf[2 * i], bf[2 * i + 1]);
          }
#pragma unroll
          for (int i = 0; i < 4; i++) { d0[i] += d1[i]; d0[i] += __shfl_xor_sync(0xffffffffu, d0[i], 6); }
          const uint32_t dst = mapa(sb + SM_MISC, t & 1) - SM_MISC;
          if (!(lane & 6)) st_async_f32x4(dst + SM_RED + warp * 128 + rank * 64 + g * 8, d0, dst + BAR_RED);
          TH(4);
    };
    {
      asm volatile("barrier.cluster.arrive.relaxed.aligned;" ::: "memory");
      if (lane == 0) st_pkt16(&g_lnst[8 * b0 + warp], 0, 0, 0, 0);
      TH(1);
      asm volatile("setmaxnreg.inc.sync.aligned.u32 240;");
      TH(2);
#pragma unroll
      for (int i = 0; i < 8; i++) {
        const float sv = silu_f((g & 4) ? hi2f(cw[i]) : lo2f(cw[i]));
        const uint32_t sp = (g & 1) ? pack2(0.f, sv) : pack2(sv, 0.f);
        bf[2 * i] = (g & 2) ? 0 : sp; bf[2 * i + 1] = (g & 2) ? sp : 0;
      }
      asm volatile("barrier.cluster.wait.aligned;" ::: "memory");
#pragma unroll
      for (int i = 0; i < 128; i++) acc[i] = 0.f;
      reg_fence<128>(acc);
      tag = __shfl_sync(0xffffffffu, epoch, 0) + 1;
      TH(3);
      if (slab && !late) gemv();
      {
        {
          mbar_wait(sb + BAR_XH + 8 * wg, 0);
          TH(5);
          float ds[4] = {0.f, 0.f, 0.f, 0.f}, dq[4][4];
#pragma unroll
          for (int i = 0; i < 4; i++) { dq[i][0] = dq[i][1] = dq[i][2] = dq[i][3] = 0.f; }
#pragma unroll
          for (int i = 0; i < 8; i++) {
            uint32_t a[4];
            ldsm4(sb + SM_XROW + wg * ST1 + wq * 4096 + ((lane >> 3) & 1) * 2048 + i * 256 + (lane >> 4) * 128 + (lane & 7) * 16, a);
            mma16816(ds, a, ONE2, ONE2);
            mma16816(dq[2 * (i & 1)], a, a[0], a[2]); mma16816(dq[1 + 2 * (i & 1)], a, a[1], a[3]);
          }
          float q0 = (g & 1) ? dq[0][1] + dq[2][1] : dq[0][0] + dq[2][0], q1 = (g & 1) ? dq[1][3] + dq[3][3] : dq[1][2] + dq[3][2];
          float s0 = ds[0], s1 = ds[2];
#pragma unroll
          for (int o = 0; o < 3; o++) {
            const int m = o == 0 ? 4 : o == 1 ? 9 : 18;
            q0 += __shfl_xor_sync(0xffffffffu, q0, m); q1 += __shfl_xor_sync(0xffffffffu, q1, m);
            s0 += __shfl_xor_sync(0xffffffffu, s0, m); s1 += __shfl_xor_sync(0xffffffffu, s1, m);
          }
          s0 *= 1.f / 1024.f; s1 *= 1.f / 1024.f;
          const uint32_t rh = pack2(rcp_f(rbf(sqrt_f(rbf(rbf(fmaxf(fmaf(-s0, s0, q0 * (1.f / 1024.f)), 0.f)) + 1e-5f)))),
                                    rcp_f(rbf(sqrt_f(rbf(rbf(fmaxf(fmaf(-s1, s1, q1 * (1.f / 1024.f)), 0.f)) + 1e-5f)))));
          if (lane == 0) st_pkt16(&g_lnst[8 * b0 + warp], pack2(-rbf(s0) * lo2f(rh), -rbf(s1) * hi2f(rh)), rh, 0, tag);
          TH(6);
          if (tid == 0) TS(2);
        }
      }
    }
    if (slab && late) gemv();
    TILE_ROLES();
    const uint32_t xa0 = sb + SM_RING + (warp * 16 + (lane & 15)) * 128 + (((lane >> 4) ^ (lane & 7)) * 16);
    uint32_t V[16];
    {
      const uint4* mp = &g_rec[tag & 1][(b0 >> 1) & (NREP - 1)][RV * wg + (lane >> 2) * RS + (lane & 3)];
      const uint4* lp = &g_lnst[(8 * rt + warp) * 8 + (g >> 1)];
      mbar_wait(sb + BAR_FULL1, 0);
#pragma unroll
      for (int kk = 0; kk < 4; kk++) ldsm4(xa0 ^ (kk * 32), V + 4 * kk);
      uint4 v0 = make_uint4(1, 0, 0, 0), l0, l1;
      int it = 0;
      while ((uint32_t)clock() - c0 < HD) {}
      do { if (wq == 0) v0 = ld_pkt16(mp);
           l0 = ld_pkt16(lp); l1 = ld_pkt16(lp + 4); spin_guard(it); }
        while (!(__all_sync(0xffffffffu, v0.x != 0 && l0.w == tag && l1.w == tag)));
      TH(7);
      if (wq == 0) put_record(sb, 128 * wg + lane, v0);
      const uint32_t sel = (g & 1) ? 0x3232 : 0x1010;
      ln[0] = __byte_perm(l0.x, 0, sel); ln[1] = __byte_perm(l0.y, 0, sel);
      ln[2] = __byte_perm(l1.x, 0, sel); ln[3] = __byte_perm(l1.y, 0, sel);
      __syncwarp();
      if (lane < 2) mbar_arrive_cl(mapa(sb + BAR_G, lane));
      normalise_frags(V, ln);
      nb_sync(NB_CONS, 256);
      if (tid == 0) TS(3);
      TH(13);
    }

    const uint32_t rel = mapa(sb + SM_MISC, lane & 1) - SM_MISC;
    const uint32_t stsm_addr = sb + SM_STASH + wg * 16384 + (wq * 16 + (lane & 15)) * 128 + (((lane >> 4) ^ (lane & 7)) * 16);

    uint32_t ph = 0;
    uint32_t X[32];
    {
      const uint32_t tab0 = sb + SM_STASH + wg * 16384 + t * 16;
      const uint64_t db0 = mk_desc(sb + SM_RING + 16384, 8192);
      uint32_t A[2][16];
      uint32_t xa[4];
#pragma unroll
      for (int kk = 0; kk < 4; kk++) xa[kk] = xa0 ^ (kk * 32);
      uint32_t tab = tab0;
      reg_fence<4>(xa);
      asm volatile("{\n.reg .pred p;\nsetp.eq.u32 p, %4, 0;\n@p ld.shared.v4.u32 {%0,%1,%2,%3}, [%5];\n}"
        : "+r"(ln[2]), "+r"(ln[0]), "+r"(ln[3]), "+r"(ln[1]) : "r"(tag), "r"(sb));
      int hs = 2 * ct;
      uint4 R[4];
#pragma unroll
      for (int kk = 0; kk < 4; kk++) R[kk] = lds128(tab + (kk >> 1) * 2048 + (kk & 1) * 64);
#pragma unroll 1
      for (int k4 = 0; k4 < 4; k4++) {
#pragma unroll
        for (int s = 0; s < 4; s++) {
          uint32_t* a = A[s & 1];
          const int sn = (s + 1) & 3;
          const uint32_t pn = (k4 + (s == 3)) & 1;
          modulate_frags(a, V, R);
          if (hs == (s & 2)) {
            if (s & 1) mbar_wait(sb + BAR_HS + 16 * wg, 0);
#pragma unroll
            for (int kk = 0; kk < 4; kk++) stsm4((stsm_addr + 4096) ^ (kk * 32), a[4 * kk], a[4 * kk + 1], a[4 * kk + 2], a[4 * kk + 3]);
            nb_arrive(NB_OST + wg, 160);
          }
          if (s == 0 && k4 == 0) TH(8);
          TQ(3 * s);
          if (s == 0 && k4 == 0 && tid == 0) { TS(6); TSC(61); }
          wg_fence();
#pragma unroll
          for (int kk = 0; kk < 4; kk++) wgmma_rs256<1>(acc, a + 4 * kk, db0 + s * (ST1 >> 4) + kk * 128);
          wg_commit();
          if (s == 3) TQ(12);
          if (s == 3 && k4 < 3) mbar_wait(sb + BAR_TAB + 8 * k4, 0);
          if (s == 3) TQ(13);
#pragma unroll
          for (int kk = 0; kk < 4; kk++) R[kk] = lds128(tab + (s + 1) * 128 + (kk >> 1) * 2048 + (kk & 1) * 64);
          wg_wait<1>();
          if (k4 == 0) TH(9 + s);
          TQ(3 * s + 1);
          reg_fence<16>(A[(s & 1) ^ 1]);
          if ((tid & 127) < 2 && (s | k4)) mbar_arrive_cl(rel + BAR_EMPTY1 + 8 * ((s + 3) & 3));
          if (s < 3 || k4 < 3) {
            mbar_wait(sb + BAR_FULL1 + 8 * sn, pn);
            TQ(3 * s + 2);
#pragma unroll
            for (int kk = 0; kk < 4; kk++) ldsm4(xa[kk] + sn * ST1, V + 4 * kk);
            normalise_frags(V, ln);
          }
        }
        tab += 512; hs -= 4;
      }
      mbar_wait(sb + BAR_HS + 16 * wg + 8, 0);
      wg_wait<0>();
      reg_fence<128>(acc);
    }
#pragma unroll 1
    for (int pair = 0; pair < 2; pair++) {
      uint32_t Q[32];
      TR(0);
      {
        if ((tid & 127) < 2) mbar_arrive_cl(rel + BAR_EMPTY1 + 8 * 3);
        if (pair == 1) mbar_wait(sb + BAR_STASH + 8 * wg, 1);
#pragma unroll
        for (int i = 0; i < 32; i++) Q[i] = pack2(acc[2 * i], acc[2 * i + 1]);
        const uint32_t qs = sb + SM_STASH + wg * 16384 + wq * 2048 + lane * 16;
#pragma unroll
        for (int i = 0; i < 8; i++)
          sts128(qs + (i & 3) * 512 + (i >> 2) * 8192, pack2(acc[64 + 8 * i], acc[65 + 8 * i]), pack2(acc[66 + 8 * i], acc[67 + 8 * i]),
                 pack2(acc[68 + 8 * i], acc[69 + 8 * i]), pack2(acc[70 + 8 * i], acc[71 + 8 * i]));
      }
      if (tid == 0) TS(8 + pair * 2);
      TR(1);
      float O[64], SL[32], SH[32];
      uint32_t PL[16], PH[16];
      SoftmaxState z;
      const uint64_t d0 = mk_desc(sb + SM_RING, 8192);
      {
        mbar_wait(sb + BAR_FULL1, ph);
        wg_fence();
        issue_qk(SL, Q, d0);
        wg_commit();
        issue_qk(SH, Q, d0 + 1024);
        wg_commit();
#pragma unroll
        for (int i = 0; i < 64; i++) O[i] = 0.f;
        reg_fence<64>(O);
        wg_wait<1>();
        reg_fence<32>(SL);
        softmax_start(z);
        softmax_half(SL, PL, O, z, true, tag);
        wg_wait<0>();
        reg_fence<32>(SH);
        if ((tid & 127) < 2) mbar_arrive_cl(rel + BAR_EMPTY1);
      }
      float lp0 = 0.f, lp1 = 0.f;
      uint32_t dB = (uint32_t)d0 + 1 * (ST1 >> 4), dA = (uint32_t)d0 + 2 * (ST1 >> 4);
      const uint32_t dBx = dB ^ ((uint32_t)d0 + 3 * (ST1 >> 4)), dAx = dA ^ (uint32_t)d0;
      uint32_t so = 0;
      bool ready = false;
#pragma unroll 1
      for (int i = 0; i < 7; i++) {
        TA(0);
        TR(2 + i);
        if (!ready) mbar_wait(sb + BAR_FULL1 + 8 + so, ph);
        TA(1);
        TA(2);
        wg_fence();
        issue_qk(SL, Q, (d0 & 0xffffffff00000000ull) | dB);
        if (i == 4) {
          __syncwarp();
          stage_o(O, lp0, lp1, stsm_addr);
        }
        wg_fence();
        issue_pv(O, PL, ((d0 & 0xffffffff00000000ull) | dB) + 1024, i != 4);
        wg_commit();
        if (i == 4) {
          nb_arrive(NB_OST + wg, 160);
        }
        TA(3);
        ph ^= i & 1;
        ready = mbar_test(sb + BAR_FULL1 + 16 - so, ph);
        softmax_half(SH, PH, O, z, false, tag);
        TA(4);
        wg_wait<0>();
        TA(5);
        reg_fence<32>(SL); reg_fence<16>(PL);
        if ((tid & 127) < 2) mbar_arrive_cl(rel + BAR_EMPTY1 + 8 + so);
        if (!ready) mbar_wait(sb + BAR_FULL1 + 16 - so, ph);
        TA(6);
        wg_fence();
        issue_qk(SH, Q, (d0 & 0xffffffff00000000ull) | dA);
        wg_commit();
        issue_pv(O, PH, ((d0 & 0xffffffff00000000ull) | dA) + 1024, 1);
        wg_commit();
        if (i == 2) {
          wg_wait<1>();
          reg_fence<32>(Q);
          const uint32_t qs = sb + SM_STASH + wg * 16384 + wq * 2048 + lane * 16;
#pragma unroll
          for (int j = 0; j < 8; j++) { const uint4 v = lds128(qs + (j & 3) * 512 + (j >> 2) * 8192); Q[4 * j] = v.x; Q[4 * j + 1] = v.y; Q[4 * j + 2] = v.z; Q[4 * j + 3] = v.w; }
        }
        TA(10);
        if (i == 3) { lp0 = z.l0; lp1 = z.l1; row_rcp(lp0, lp1); softmax_start(z); }
        TA(7);
        so ^= 16; dB ^= dBx; dA ^= dAx;
        ready = mbar_test(sb + BAR_FULL1 + 8 + so, ph);
        softmax_half(SL, PL, O, z, i == 3, tag);
        TA(8);
        wg_wait<0>();
        TA(9);
        reg_fence<32>(SH); reg_fence<16>(PH); reg_fence<64>(O); reg_fence<32>(Q);
        if ((tid & 127) < 2) mbar_arrive_cl(rel + BAR_EMPTY1 + so);
      }
      TAFLUSH();
      TR(9);
      {
        if (!ready) mbar_wait(sb + BAR_FULL1 + 8 * 3, ph);
        ph ^= 1;
        const uint64_t dv = d0 + 3 * (ST1 >> 4);
        wg_fence();
        issue_pv(O, PL, dv, 1);
        wg_commit();
        bb_fence(tag);
        softmax_half(SH, PH, O, z, false, tag);
        wg_fence();
        issue_pv(O, PH, dv + 1024, 1);
        wg_commit();
        TR(10);
        row_rcp(z.l0, z.l1);
        mbar_wait(sb + (pair ? BAR_X : BAR_STASH) + 8 * wg, 0);
#pragma unroll
        for (int kk = 0; kk < 8; kk++) ldsm4((stsm_addr + (kk >> 2) * 8192) ^ ((kk & 3) * 32), X + 4 * kk);
        reg_fence<32>(X);
        __syncwarp();
        wg_wait<0>();
        reg_fence<64>(O);
        TR(11);
        if ((tid & 127) < 2) mbar_arrive_cl(rel + BAR_EMPTY1 + 8 * 3);
        stage_o(O, z.l0, z.l1, stsm_addr);
        nb_arrive(NB_OST + wg, 160);
      }
      TR(12);
      if (tid == 0) { TS(9 + pair * 2); TSC(62); }
      if (pair == 1) break;
      {
        mbar_wait(sb + BAR_FULL1, ph);
        const uint64_t da = mk_desc(sb + SM_RING + wg * 8192, 16), db = mk_desc(sb + SM_RING + 16384, 8192);
        wg_fence();
        wgmma_ss256_z<1>(acc, da, db);
#pragma unroll
        for (int kk = 1; kk < 4; kk++) wgmma_ss256<1>(acc, da + kk * 2, db + kk * 128, 1);
        wg_commit();
      }
#pragma unroll 1
      for (int kt = 1; kt < 16; kt++) {
        const uint32_t s = kt & 3;
        if (s == 0) ph ^= 1;
        mbar_wait(sb + BAR_FULL1 + 8 * s, ph);
        const uint32_t st = sb + SM_RING + s * ST1;
        const uint64_t da = mk_desc(st + wg * 8192, 16), db = mk_desc(st + 16384, 8192);
        wg_fence();
#pragma unroll
        for (int kk = 0; kk < 4; kk++) wgmma_ss256<1>(acc, da + kk * 2, db + kk * 128, 1);
        wg_commit();
        wg_wait<1>();
        if ((tid & 127) < 2) mbar_arrive_cl(rel + BAR_EMPTY1 + 8 * ((s + 3) & 3));
      }
      ph ^= 1;
      wg_wait<0>();
      reg_fence<128>(acc);
      TR(13);
    }

    uint4 WG[16], WU[16];
    const int fp = 64 * warp + 8 * g + t;
    uint32_t fsb0, fsb1, fcb0, fcb1, fgb0, fgb1;
    const uint32_t gu_base = sb + SM_RING + (warp >> 1) * ST1 + 32768 + (warp & 1) * 8192;
    const uint32_t gu_addr = gu_base + t * 128 + (g & 1) * 64 + ((g >> 1) ^ t) * 16;
    {
      const uint64_t da0 = mk_desc(sb + SM_RING + __shfl_sync(0xffffffffu, wg, 0) * 8192, 16), db0 = mk_desc(sb + SM_RING + 16384, 8192);
#pragma unroll
      for (int n = 0; n < 4 + 5 * PEEL; n++) {
        const int s = n < 4 ? n : (n - 4) % 5;
        mbar_wait(sb + BAR_FULL1 + 8 * s, n < 4 ? 0 : ((n - 4) / 5 + (s < 4)) & 1);
        if (n < 4) TSX(40 + wg * 6 + n);
        const uint64_t da = da0 + s * (ST1 >> 4), db = db0 + s * (ST1 >> 4);
        wg_fence();
        if (n == 0) wgmma_ss128_z<1>(acc, da, db); else wgmma_ss128<1>(acc, da, db, 1);
#pragma unroll
        for (int kk = 1; kk < 4; kk++) wgmma_ss128<1>(acc, da + kk * 2, db + kk * 128, 1);
        wg_commit();
        if (n == 0 && b < NFFN) mbar_wait(sb + BAR_FFN, 0);
        {
          constexpr int NT = 4 + 5 * PEEL, F0 = NT > 16 ? NT - 16 : 0;
#pragma unroll
          for (int i = 0; i < 16; i++) if (F0 + i * (NT - F0) / 16 == n) WG[i] = lds128(gu_addr + i * 512);
        }
        if (n > 0) {
          wg_wait<1>();
          if ((tid & 127) < 2) mbar_arrive_cl(rel + BAR_EMPTY1 + 8 * (n == 4 ? 3 : s ? s - 1 : 4));
        }
      }
      TSX(44 + wg * 6);
      {
        uint32_t dep = 0;
#pragma unroll
        for (int i = 0; i < 16; i++) dep ^= WG[i].x;
        if (__shfl_sync(0xffffffffu, tag, dep & 31) == tag && lane == 2) mbar_arrive(sb + BAR_TFREE);
      }
      {
        uint32_t so = 0, sp = 4 * 8, par = PEEL + 1;
#pragma unroll 1
        for (int n = 4 + 5 * PEEL; n < 64; n++) {
          mbar_wait(sb + BAR_FULL1 + so, (par + (so >> 5)) & 1);
          const uint64_t da = da0 + so * (ST1 >> 7), db = db0 + so * (ST1 >> 7);
          wg_fence();
#pragma unroll
          for (int kk = 0; kk < 4; kk++) wgmma_ss128<1>(acc, da + kk * 2, db + kk * 128, 1);
          wg_commit();
          wg_wait<1>();
          if ((tid & 127) < 2) mbar_arrive_cl(rel + BAR_EMPTY1 + sp);
          sp = so; so += 8;
          if (so == 40) { so = 0; par++; }
        }
      }
    }
    mbar_wait(sb + BAR_VEC, 0);
    const int lrow = warp * 16 + g;
    uint2 ga[8], b1[8];
#pragma unroll
    for (int kk = 0; kk < 8; kk++) { ga[kk] = lds64(sb + SM_GA + kk * 32 + t * 8); b1[kk] = lds64(sb + SM_B1 + min(g, 3) * 32 + t * 8 + kk * 128); }
    uint4* const stp = &g_stats[b * 128 + lrow + 8 * t];
    bb_fence(tag);
    wg_wait<0>();
    reg_fence<64>(acc);
    if (tid == 0) { TS(12); TSC(63); }

    TT(0);
    {
      float d1[4] = {0.f, 0.f, 0.f, 0.f}, d2[4] = {0.f, 0.f, 0.f, 0.f}, d3[4] = {0.f, 0.f, 0.f, 0.f};
      float d4[4] = {0.f, 0.f, 0.f, 0.f}, d5[4] = {0.f, 0.f, 0.f, 0.f};
#pragma unroll
      for (int kk = 0; kk < 8; kk++) {
        uint32_t* x = X + 4 * kk;
        x[0] = hfma2(ga[kk].x, pack2(acc[8 * kk + 0], acc[8 * kk + 1]), x[0]);
        x[1] = hfma2(ga[kk].x, pack2(acc[8 * kk + 2], acc[8 * kk + 3]), x[1]);
        x[2] = hfma2(ga[kk].y, pack2(acc[8 * kk + 4], acc[8 * kk + 5]), x[2]);
        x[3] = hfma2(ga[kk].y, pack2(acc[8 * kk + 6], acc[8 * kk + 7]), x[3]);
        mma16816(d1, x, b1[kk].x, b1[kk].y);
        mma1688(d2, x[0], x[1], x[0]); mma1688(d3, x[0], x[1], x[1]);
        mma1688(d4, x[2], x[3], x[2]); mma1688(d5, x[2], x[3], x[3]);
      }
      const int qb = lane & 28;
      const float q0 = __shfl_sync(0xffffffffu, (g & 1) ? d2[1] + d4[1] : d2[0] + d4[0], qb | (g >> 1));
      const float q1 = __shfl_sync(0xffffffffu, (g & 1) ? d3[3] + d5[3] : d3[2] + d5[2], qb | (g >> 1));
      const float e0 = __shfl_xor_sync(0xffffffffu, t ? d1[0] : d1[3], 1);
      const float e1 = __shfl_sync(0xffffffffu, d1[2], qb);
      if (t < 2) st_pkt16(stp, __float_as_uint(t ? e1 : d1[0]), __float_as_uint(t ? q1 : q0),
                          __float_as_uint((t ? d1[2] : d1[1]) + e0), tag);
    }
    {
      const uint2* mp = &g_mod[3 * 512 + fp];
      fsb0 = ld_pkt8(mp).x; fsb1 = ld_pkt8(mp + 4).x; fcb0 = ld_pkt8(mp + 512).x; fcb1 = ld_pkt8(mp + 516).x;
      fgb0 = ld_pkt8(mp + 1024).x; fgb1 = ld_pkt8(mp + 1028).x;
    }
    TSY(13);
    TT(1);
    float mb, rd, den, br;
    {
      const uint4* sp = &g_stats[(rt * 8 + 4 * (t & 1)) * 128 + lrow + 4 * (t & 2)];
      mbar_wait(sb + BAR_EMPTY1 + 8 * 3, 0);
#pragma unroll
      for (int kk = 0; kk < 8; kk++) stsm4((stsm_addr - SM_STASH + SM_X2 + (kk >> 2) * 8192) ^ ((kk & 3) * 32), X[4 * kk], X[4 * kk + 1], X[4 * kk + 2], X[4 * kk + 3]);
      if (b < NFFN) mbar_wait(sb + BAR_FFN, 1);
#pragma unroll
      for (int i = 0; i < WU1; i++) WU[i] = lds128(gu_addr + i * 512);
      bb_fence(tag);
      TT(2);
      uint4 v0, v1, v2, v3;
      int it = 0;
      do { v0 = ld_pkt16(sp); v1 = ld_pkt16(sp + 128); v2 = ld_pkt16(sp + 256); v3 = ld_pkt16(sp + 384); spin_guard(it); }
        while (!(__all_sync(0xffffffffu, v0.w == tag && v1.w == tag && v2.w == tag && v3.w == tag)));
      TT(3);
      float sm = (__uint_as_float(v0.x) + __uint_as_float(v1.x)) + (__uint_as_float(v2.x) + __uint_as_float(v3.x));
      float sq = (__uint_as_float(v0.y) + __uint_as_float(v1.y)) + (__uint_as_float(v2.y) + __uint_as_float(v3.y));
      float dt = (__uint_as_float(v0.z) + __uint_as_float(v1.z)) + (__uint_as_float(v2.z) + __uint_as_float(v3.z));
      sm += __shfl_xor_sync(0xffffffffu, sm, 1); sq += __shfl_xor_sync(0xffffffffu, sq, 1); dt += __shfl_xor_sync(0xffffffffu, dt, 1);
      const uint2 scal = lds64(sb + SM_SCAL);
      const float mu = sm * (1.f / 1024.f);
      mb = rbf(mu);
      den = rbf(sqrt_f(rbf(rbf(fmaxf(fmaf(-mu, mu, sq * (1.f / 1024.f)), 0.f)) + 1e-5f)));
      rd = rcp_f(den);
      br = fmaf(fmaf(-mb, __uint_as_float(scal.x), dt), rd, __uint_as_float(scal.y));
    }
    TSY(14);
    TT(4);
    {
      const int rb = __float_as_int(br);
      const int key = ((rb ^ ((rb >> 31) & 0x7fffffff)) | 127) - (lrow + 4 * (t & 2));
      if (key == __reduce_max_sync(0xffffffffu, key)) sts64(sb + SM_AMAX + warp * 8, (uint32_t)key, pack2(mb, den));
      __syncwarp();
      nb_arrive(NB_AMAX, 288);
    }
    TT(5);
    const uint4* ep = &g_entry[(warp * 16 + (lane & 15)) * 8];
    const uint32_t slot = sb + SM_STASH + wg * 8192 + (tid & 127) * 16;
    cp_async16(slot, ep);
    {
      const float rh = rbf(rd);
      const uint32_t u = pack2(-mb * rh, rh);
      const int qb = lane & 28;
      const uint32_t u0 = __shfl_sync(0xffffffffu, u, qb), u1 = __shfl_sync(0xffffffffu, u, qb | 2);
      const uint32_t m0 = __byte_perm(u0, 0, 0x1010), h0 = __byte_perm(u0, 0, 0x3232);
      const uint32_t m1 = __byte_perm(u1, 0, 0x1010), h1 = __byte_perm(u1, 0, 0x3232);
#pragma unroll
      for (int j = 0; j < 16; j++) {
        const uint4 rec = lds128(sb + SM_REC + (4 * j + t) * 16);
        X[2 * j] = hfma2(rec.z, hfma2(hfma2(X[2 * j], h0, m0), rec.x, rec.y), X[2 * j]);
        X[2 * j + 1] = hfma2(rec.z, hfma2(hfma2(X[2 * j + 1], h1, m1), rec.x, rec.y), X[2 * j + 1]);
      }
#pragma unroll
      for (int kk = 0; kk < 8; kk++) stsm4((stsm_addr - SM_STASH + SM_OUT + (kk >> 2) * 8192) ^ ((kk & 3) * 32), X[4 * kk], X[4 * kk + 1], X[4 * kk + 2], X[4 * kk + 3]);
    }
    cp_async_wait();
    uint4 ent = lds128(slot);
    TSY(16);
    TT(6);
    int wrow;
    uint32_t xs0, xs1, hs0, hs1;
    uint32_t WD[64];
    const uint32_t wd_addr = sb + SM_RING + wg * ST1 + wq * 8192 + ((lane & 7) + ((lane >> 4) << 3)) * 128 + ((((lane >> 3) & 1) ^ (lane & 7)) * 16);
    {
      int gmax;
      auto leader = [&]() {
        gmax = __reduce_max_sync(0xffffffffu, ent.w == tag ? (int)ent.x : (int)0x8000000f);
        return ~gmax & 15;
      };
      int wt = leader(), it = 0;
      TT(7);
      nb_arrive(NB_OST + wg, 160);
      TT(8);
      cp_async16(slot + 2048, &g_cand[(wt * 8 + warp) * 32 + lane]);
      if (ent.w != tag) cp_async16(slot, ep);
#pragma unroll
      for (int i = WU1; i < 16; i++) WU[i] = lds128(gu_addr + i * 512);
      if (b < NFFN) mbar_wait(sb + BAR_FFN + 8, 0);
#pragma unroll
      for (int mt = 0; mt < 8; mt++)
#pragma unroll
        for (int s = 0; s < 2; s++) ldsm4t((wd_addr + (mt >> 2) * 4096 + s * 2048) ^ ((mt & 3) * 32), WD + (mt * 2 + s) * 4);
      cp_async_wait();
      uint4 v = lds128(slot + 2048);
      ent = lds128(slot);
      TT(9);
      while (true) {
        const int have = wt;
        wt = leader();
        if (__all_sync(0xffffffffu, ent.w == tag && have == wt && v.z == tag)) break;
        v = ld_pkt16(&g_cand[(wt * 8 + warp) * 32 + lane]);
        if (ent.w != tag) ent = ld_pkt16(ep);
        spin_guard(it);
      }
      TT(10);
      ent.x = gmax ^ ((gmax >> 31) & 0x7fffffff);
      wrow = __shfl_sync(0xffffffffu, ent.y, wt); ent.z = __shfl_sync(0xffffffffu, ent.z, wt);
      xs0 = v.x; xs1 = v.y;
      const uint32_t mm = __byte_perm(ent.z, 0, 0x1010);
      const float rs = rcp_f(hi2f(ent.z));
      const uint32_t e0 = hsub2(xs0, mm), e1 = hsub2(xs1, mm);
      hs0 = hfma2(pack2(lo2f(e0) * rs, hi2f(e0) * rs), hadd2(fcb0, ONE2), fsb0);
      hs1 = hfma2(pack2(lo2f(e1) * rs, hi2f(e1) * rs), hadd2(fcb1, ONE2), fsb1);
    }
    if ((tid & 127) == 0) sts32(sb + SM_WROW + 4 * wg, wrow);
    nb_arrive(NB_WIN + wg, 160);
    TSY(17);
    TT(11);
    if (b < NFFN) {
      float da[4][4];
#pragma unroll
      for (int i = 0; i < 4; i++) { da[i][0] = da[i][1] = da[i][2] = da[i][3] = 0.f; }
      const uint32_t selv = ((g & 1) ? 0x1044 : 0x4410) + ((g & 4) ? ((g & 1) ? 0x2200 : 0x0022) : 0);
      const uint32_t sel0 = (g & 2) ? 0x4444 : selv, sel1 = (g & 2) ? selv : 0x4444;
#pragma unroll
      for (int s = 0; s < 16; s++) {
        const uint32_t v = __shfl_sync(0xffffffffu, (s & 1) ? hs1 : hs0, 4 * (s >> 1) + t);
        const uint32_t b0 = __byte_perm(v, 0, sel0), b1 = __byte_perm(v, 0, sel1);
        const uint32_t a0[4] = {WG[s].x, WG[s].y, WG[s].z, WG[s].w};
        const uint32_t a1[4] = {WU[s].x, WU[s].y, WU[s].z, WU[s].w};
        mma16816(da[(s & 1) * 2], a0, b0, b1);
        mma16816(da[(s & 1) * 2 + 1], a1, b0, b1);
      }
      {
        float v[4];
#pragma unroll
        for (int i = 0; i < 4; i++) {
          const float vg = da[0][i] + da[2][i], vu = da[1][i] + da[3][i];
          v[i] = ((g & 1) ? vu : vg) + __shfl_xor_sync(0xffffffffu, (g & 1) ? vg : vu, 6);
        }
        if ((t >> 1) == (g & 1))
          sts128(gu_base + (g & 1) * 128 + (g >> 1) * 32 + (t & 1) * 16, __float_as_uint(v[0]), __float_as_uint(v[1]), __float_as_uint(v[2]), __float_as_uint(v[3]));
      }
      TT(12);
      nb_sync(NB_CONS, 256);
      float gp[8], up[8];
#pragma unroll
      for (int w = 0; w < 8; w++) {
        const uint32_t a = sb + SM_RING + (w >> 1) * ST1 + 32768 + (w & 1) * 8192 + lane * 4;
        gp[w] = lds_f32(a); up[w] = lds_f32(a + 128);
      }
      const float gsum = ((gp[0] + gp[1]) + (gp[2] + gp[3])) + ((gp[4] + gp[5]) + (gp[6] + gp[7]));
      const float usum = ((up[0] + up[1]) + (up[2] + up[3])) + ((up[4] + up[5]) + (up[6] + up[7]));
      const float act = rbf(silu_f(rbf(gsum))) * rbf(usum);
      TT(13);
      const uint32_t ap = pack2(act, __shfl_down_sync(0xffffffffu, act, 1));
      const uint32_t b00 = __shfl_sync(0xffffffffu, ap, 2 * t), b01 = __shfl_sync(0xffffffffu, ap, 2 * t + 8);
      const uint32_t b10 = __shfl_sync(0xffffffffu, ap, 2 * t + 16), b11 = __shfl_sync(0xffffffffu, ap, 2 * t + 24);
      float y[8][4];
#pragma unroll
      for (int mt = 0; mt < 8; mt++) {
        y[mt][0] = y[mt][1] = y[mt][2] = y[mt][3] = 0.f;
        mma16816(y[mt], WD + (mt * 2) * 4, b00, b01);
        mma16816(y[mt], WD + (mt * 2 + 1) * 4, b10, b11);
      }
#pragma unroll
      for (int e = 0; e < 2; e++) {
        const float v0 = t == 0 ? y[e][0] : t == 1 ? y[2 + e][0] : t == 2 ? y[4 + e][0] : y[6 + e][0];
        const float v1 = t == 0 ? y[e][2] : t == 1 ? y[2 + e][2] : t == 2 ? y[4 + e][2] : y[6 + e][2];
        st_pkt8(reinterpret_cast<uint2*>(g_ypart) + (((tag & 1) * 64 + 8 * warp + 2 * t + e) * NFFN + b) * 8 + g, ~__float_as_uint(v0), __float_as_uint(v1));
      }
    }
    TSY(18);
    TT(14);
    if (b & 1) return;
    {
      const int pw = warp - (warp > (b >> 4));
      if (warp != (b >> 4)) {
        const uint4* yp = &g_ypart[((tag & 1) * 64 + (b >> 1)) * NFFN * 4 + pw * 64 + lane];
        uint4 v0, v1;
        int it = 0;
        { const uint32_t c1 = clock(); while ((uint32_t)clock() - c1 < (b < NFFN ? YD : YD + 1500)) {} }
        do { v0 = ld_pkt8x2(yp); v1 = ld_pkt8x2(yp + 32); spin_guard(it); }
        while (!(__all_sync(0xffffffffu, v0.x != 0 && v0.z != 0 && v1.x != 0 && v1.z != 0)));
        float y[4] = {__uint_as_float(~v0.x) + __uint_as_float(~v1.x), __uint_as_float(~v0.z) + __uint_as_float(~v1.z),
                      __uint_as_float(v0.y) + __uint_as_float(v1.y), __uint_as_float(v0.w) + __uint_as_float(v1.w)};
#pragma unroll
        for (int o = 4; o <= 16; o <<= 1)
#pragma unroll
          for (int i = 0; i < 4; i++) y[i] += __shfl_xor_sync(0xffffffffu, y[i], o);
        if (lane < 4) sts128(sb + SM_B1 + pw * 64 + lane * 16, __float_as_uint(y[0]), __float_as_uint(y[1]), __float_as_uint(y[2]), __float_as_uint(y[3]));
      }
    }
    TT(15);
    if (warp != (b >> 4)) {
      nb_arrive(NB_CONS, 256);
    } else {
      nb_sync(NB_CONS, 256);
      float y[4] = {0.f, 0.f, 0.f, 0.f};
      if (lane < 28) { const uint4 e = lds128(sb + SM_B1 + lane * 16); y[0] = __uint_as_float(e.x); y[1] = __uint_as_float(e.y); y[2] = __uint_as_float(e.z); y[3] = __uint_as_float(e.w); }
#pragma unroll
      for (int o = 4; o <= 16; o <<= 1)
#pragma unroll
        for (int i = 0; i < 4; i++) y[i] += __shfl_xor_sync(0xffffffffu, y[i], o);
      const float ya = y[0], yb = y[1], yc = y[2], yd = y[3];
      if (g == ((b >> 1) & 7)) {
        const float rs = rbf(__uint_as_float(ent.x));
        const float sg = sigmoid_f(rs);
        const uint32_t sg2 = pack2(sg, sg);
        const uint32_t o0 = hadd2(xs0, hmul2(fgb0, hadd2(hs0, hmul2(pack2(ya, yb), sg2))));
        const uint32_t o1 = hadd2(xs1, hmul2(fgb1, hadd2(hs1, hmul2(pack2(yc, yd), sg2))));
        uint32_t* op = reinterpret_cast<uint32_t*>(p.out + (size_t)wrow * 1024) + fp;
        op[0] = o0; op[4] = o1;
      }
      if (b == 0) {
        if (lane < 8) st_relaxed(&p.sc->ticket[lane * 32], 0);
        st_relaxed(&p.sc->epoch[lane], tag);
      }
      if (lane == 0) TS(19);
    }
  }
}

typedef CUresult (*EncodeFn)(CUtensorMap*, CUtensorMapDataType, cuuint32_t, void*, const cuuint64_t*, const cuuint64_t*,
                             const cuuint32_t*, const cuuint32_t*, CUtensorMapInterleave, CUtensorMapSwizzle,
                             CUtensorMapL2promotion, CUtensorMapFloatOOBfill);

CUtensorMap make_map(EncodeFn enc, const void* ptr, uint64_t rows, uint64_t cols, uint32_t box_rows, uint32_t box_cols, CUtensorMapSwizzle sw) {
  CUtensorMap m;
  cuuint64_t dims[2] = {cols, rows};
  cuuint64_t strides[1] = {cols * 2};
  cuuint32_t box[2] = {box_cols, box_rows};
  cuuint32_t es[2] = {1, 1};
  enc(&m, CU_TENSOR_MAP_DATA_TYPE_BFLOAT16, 2, const_cast<void*>(ptr), dims, strides, box, es, CU_TENSOR_MAP_INTERLEAVE_NONE, sw,
      CU_TENSOR_MAP_L2_PROMOTION_L2_128B, CU_TENSOR_MAP_FLOAT_OOB_FILL_NONE);
  return m;
}

CUtensorMap make_map3(EncodeFn enc, const void* ptr, uint64_t rows, uint64_t cols, uint32_t box_rows, uint32_t box_blks) {
  CUtensorMap m;
  cuuint64_t dims[3] = {64, rows, cols / 64};
  cuuint64_t strides[2] = {cols * 2, 128};
  cuuint32_t box[3] = {64, box_rows, box_blks};
  cuuint32_t es[3] = {1, 1, 1};
  enc(&m, CU_TENSOR_MAP_DATA_TYPE_BFLOAT16, 3, const_cast<void*>(ptr), dims, strides, box, es, CU_TENSOR_MAP_INTERLEAVE_NONE,
      CU_TENSOR_MAP_SWIZZLE_128B, CU_TENSOR_MAP_L2_PROMOTION_L2_128B, CU_TENSOR_MAP_FLOAT_OOB_FILL_NONE);
  return m;
}

}

extern "C" void kernel_launch(void* const* d_in, const int* in_sizes, int n_in, void* d_out, int out_size) {
  (void)in_sizes; (void)n_in; (void)out_size;
  Params p;
  p.x = (const bf16*)d_in[0]; p.kc = (const bf16*)d_in[1]; p.vc = (const bf16*)d_in[2];
  p.wq = (const bf16*)d_in[3]; p.wo = (const bf16*)d_in[4]; p.w_r = (const bf16*)d_in[6];
  p.wg = (const bf16*)d_in[7]; p.wu = (const bf16*)d_in[8]; p.wd = (const bf16*)d_in[9];
  p.c = (const bf16*)d_in[10]; p.w_mod = (const bf16*)d_in[11]; p.out = (bf16*)d_out;

  void* fn = nullptr;
  cudaDriverEntryPointQueryResult st;
  cudaGetDriverEntryPoint("cuTensorMapEncodeTiled", &fn, cudaEnableDefault, &st);
  EncodeFn enc = (EncodeFn)fn;
  void* scp = nullptr;
  cudaGetSymbolAddress(&scp, g_scratch);
  p.sc = (Scratch*)scp;
  void *hp = p.sc->h, *op = p.sc->o;
  const CUtensorMapSwizzle S128 = CU_TENSOR_MAP_SWIZZLE_128B;
  CUtensorMap mH = make_map(enc, hp, 2048, 1024, 64, 64, S128);
  CUtensorMap mWq = make_map3(enc, p.wq, 1024, 4096, 64, 4);
  CUtensorMap mK = make_map(enc, p.kc, 8192, 128, 64, 64, S128);
  CUtensorMap mV = make_map(enc, p.vc, 8192, 128, 64, 64, S128);
  CUtensorMap mO = make_map(enc, op, 2048, 4096, 64, 64, S128);
  CUtensorMap mOs = make_map(enc, op, 2048, 4096, 16, 64, S128);
  CUtensorMap mWo = make_map3(enc, p.wo, 4096, 1024, 64, 2);
  CUtensorMap mX = make_map(enc, p.x, 2048, 1024, 64, 64, S128);
  CUtensorMap mOut = make_map(enc, p.out, 2048, 1024, 64, 64, S128);
  CUtensorMap mWg = make_map(enc, p.wg, 1024, 3584, 256, 32, CU_TENSOR_MAP_SWIZZLE_64B);
  CUtensorMap mWu = make_map(enc, p.wu, 1024, 3584, 256, 32, CU_TENSOR_MAP_SWIZZLE_64B);
  CUtensorMap mWd = make_map3(enc, p.wd, 3584, 1024, 32, 8);
  CUtensorMap mWm = make_map(enc, p.w_mod, 1024, 6144, 16, 256, CU_TENSOR_MAP_SWIZZLE_NONE);
  CUtensorMap mWh = make_map(enc, p.w_mod, 1024, 6144, 256, 32, CU_TENSOR_MAP_SWIZZLE_64B);
  CUtensorMap mWs = make_map(enc, p.w_mod, 1024, 6144, 128, 128, CU_TENSOR_MAP_SWIZZLE_NONE);
  cudaFuncSetAttribute(fused_kernel, cudaFuncAttributeMaxDynamicSharedMemorySize, SMEM_BYTES);
  fused_kernel<<<NCTA, NTHREADS, SMEM_BYTES>>>(p, mH, mWq, mK, mV, mO, mWo, mX, mOut, mWg, mWu, mWd, mWm, mWs, mWh, mOs);
}
```
